```python
import torch

def _softmax(x, axis=-1):
    return torch.softmax(x, dim=axis)
def _gelu(x):
    return torch.nn.functional.gelu(x, approximate="tanh")
def _silu(x):
    return torch.nn.functional.silu(x)
def _sigmoid(x):
    return torch.sigmoid(x)
def _layernorm(x, axis=-1, eps=1e-5):
    m = x.mean(dim=axis, keepdim=True)
    v = x.var(dim=axis, keepdim=True, unbiased=False)
    return (x - m) / torch.sqrt(v + eps)
def _scatter_add(tgt, idx, src, axis=0):
    return tgt.clone().index_add_(axis, idx, src)
def _segment_sum(src, seg, n):
    out = torch.zeros((n,) + src.shape[1:], dtype=src.dtype)
    return out.index_add_(0, seg, src)
def _pad(x, pw):
    flat = tuple(v for pair in reversed(pw) for v in pair)
    return torch.nn.functional.pad(x, flat)

kernel_name = 'gated_mix__ssm_conv_s4d__moe_arch_mod__prompt'

def setup_inputs():

    _w = (lambda a: (lambda t: t.to(torch.bfloat16) if t.is_floating_point() else t)(torch.as_tensor(a)))
    def _A_setup():
        Bsz, L, D, N = 1, 2048, 1024, 128
        return {
            "u": _w((lambda *s: torch.randn(*s, dtype=torch.bfloat16) * 0.05)(Bsz, L, D)),
            "log_A_real": _w((lambda *s: torch.randn(*s, dtype=torch.bfloat16) * 6.4)(D, N) * 0.5),
            "A_imag": _w((lambda *s: torch.randn(*s, dtype=torch.bfloat16) * 0.1)(D, N) * 3.14),
            "C_real": _w((lambda *s: torch.randn(*s, dtype=torch.bfloat16) * 0.4)(D, N) / N ** 0.5),
            "C_imag": _w((lambda *s: torch.randn(*s, dtype=torch.bfloat16) * 0.4)(D, N) / N ** 0.5),
            "log_dt": _w((lambda *s: torch.randn(*s, dtype=torch.bfloat16) * 0.1)(D) * 0.5 - 4.0),
            "D_skip": _w((lambda *s: torch.randn(*s, dtype=torch.bfloat16) * 0.1)(D)),
        }
    _A_in = _A_setup()

    def _B_setup():
        B, S, D, F, C = 1, 2048, 1024, 3584, 8
        return {
            "x": _w((lambda *s: torch.randn(*s, dtype=torch.bfloat16) * 0.05)(B, S, D)),
            "w_r": _w((lambda *s: torch.randn(*s, dtype=torch.bfloat16) * 6.4)(D)),
            "w_gate": _w((lambda *s: torch.randn(*s, dtype=torch.bfloat16) * 0.1)(D, F)),
            "w_up": _w((lambda *s: torch.randn(*s, dtype=torch.bfloat16) * 0.1)(D, F)),
            "w_down": _w((lambda *s: torch.randn(*s, dtype=torch.bfloat16) * 0.1)(F, D)),
        }
    _B_in = _B_setup()

    return {
        "A_u": _A_in["u"],
        "A_log_A_real": _A_in["log_A_real"],
        "A_A_imag": _A_in["A_imag"],
        "A_C_real": _A_in["C_real"],
        "A_C_imag": _A_in["C_imag"],
        "A_log_dt": _A_in["log_dt"],
        "A_D_skip": _A_in["D_skip"],
        "B_x": _B_in["x"],
        "B_w_r": _B_in["w_r"],
        "B_w_gate": _B_in["w_gate"],
        "B_w_up": _B_in["w_up"],
        "B_w_down": _B_in["w_down"],
        "gate_w": _w((lambda *s: torch.randn(*s, dtype=torch.bfloat16) * 0.05)(1024) * 16.0),
    }

def reference(A_u, A_log_A_real, A_A_imag, A_C_real, A_C_imag, A_log_dt, A_D_skip, B_x, B_w_r, B_w_gate, B_w_up, B_w_down, gate_w):
    def _A_ref(u, log_A_real, A_imag, C_real, C_imag, log_dt, D_skip):
        L = u.shape[1]
        dt = torch.exp(log_dt)
        A = -torch.exp(log_A_real) + 1j * A_imag
        C = (C_real + 1j * C_imag) * dt[:, None]
        pos = (lambda x, dt: x.to(dt))(torch.arange(L), log_dt.dtype)
        P = torch.exp((A * dt[:, None])[:, :, None] * pos[None, None, :])
        K = 2.0 * torch.einsum("dn,dnl->dl", C, P).real
        L2 = 2 * L
        u_t = (lambda x, *d: x.permute(*d))(u, 0, 2, 1)
        Kf = (lambda x, *a, **k: torch.fft.rfft(x.float(), *a, **k))(K, L2)
        Uf = (lambda x, *a, **k: torch.fft.rfft(x.float(), *a, **k))(u_t, L2)
        y = (lambda x, *a, **k: torch.fft.irfft(x, *a, **k).to(torch.bfloat16))(Uf * Kf[None, :, :], L2)[:, :, :L]
        y = (lambda x, *d: x.permute(*d))(y, 0, 2, 1)
        return y + u * D_skip[None, None, :]

    def _B_ref(x, w_r, w_gate, w_up, w_down):
        B, S, D = x.shape
        C = 8
        r = x @ w_r
        idx = torch.argsort(-r, axis=-1)[:, :C]
        idx_e = (lambda x, n, axis: torch.repeat_interleave(x, n, dim=axis))(idx.reshape(B, C, 1), D, axis=2)
        x_sel = (lambda x, i, axis: torch.take_along_dim(x, i, dim=axis))(x, idx_e, axis=1)
        g = _silu(x_sel @ w_gate)
        u = x_sel @ w_up
        y = (g * u) @ w_down
        r_sel = _sigmoid((lambda x, i, axis: torch.take_along_dim(x, i, dim=axis))(r, idx, axis=1))
        y = y * r_sel.reshape(B, C, 1)
        b_off = (torch.arange(B) * S).reshape(B, 1)
        flat_idx = (idx + b_off).reshape(B * C)
        zero = (x * 0.0).reshape(B * S, D)
        upd = _scatter_add(zero, flat_idx, y.reshape(B * C, D), axis=0)
        return x + upd.reshape(B, S, D)

    x = A_u
    g = _sigmoid((x * gate_w).sum(-1, keepdims=True))
    a = _A_ref(x, A_log_A_real, A_A_imag, A_C_real, A_C_imag, A_log_dt, A_D_skip)
    b = _B_ref(x, B_w_r, B_w_gate, B_w_up, B_w_down)
    return g * a + (1 - g) * b
```

```cpp
#include <cuda_runtime.h>
#include <cuda_bf16.h>
#include <cuda_fp16.h>
#include <cuda.h>
#include <stdint.h>

typedef __nv_bfloat16 bf16;

namespace {

constexpr int L_ = 2048, D_ = 1024, F_ = 3584;
constexpr int NCTA = 130;
constexpr int NTHREADS = 512;
constexpr int MAIN_W0 = 4;
#define DEPTH 6
#define DEPTH_D DEPTH
#define W_START 1
#define PSLEEP 40
#define GU_UNROLL 16
#define KS_UNROLL 4
#define START_MODE 0
#define X_DELAY 0
#define LDX_HINT ""
#define X_BATCH 16
#define EPI_AT 2
#define X_LEAD 2
#define KEEP_LIVE 0
#define MAIN_REGS "176"
#define HELP_REGS "24"
constexpr int kGuUnroll = GU_UNROLL, kKsUnroll = KS_UNROLL;
constexpr int NGU_CTA = 112;

constexpr int NSLOT    = 21;
constexpr int NST_GU   = 32, NST = 46;
constexpr int OFF_RING = 0;
constexpr int OFF_S    = 86528;
constexpr int ALT0     = OFF_S + 32768, ALT1 = OFF_S - 384;
constexpr int A_YIN    = 32, Y_CH = 2064;
constexpr int A_XSEL   = 16544, XS_ROW = 2064;
constexpr int A_DP     = A_XSEL + 8192;
constexpr int U_PL     = 1184;
constexpr int U_CH     = 4752;
constexpr int OFF_U    = 152448;
constexpr int T_CH     = 4112;
constexpr int OFF_TAB  = 190464;
constexpr int T_R2     = 2176, T2_S = 208;
constexpr int T_R3     = 3040, T3_S = 336;
constexpr int OFF_GP   = 223360;
constexpr int OFF_BAND = 227456;
constexpr int OFF_MISC = 228736;
constexpr int M_BARS   = OFF_MISC;
constexpr int M_DSK    = OFF_MISC + 672;
constexpr int M_IDX    = OFF_MISC + 704;
constexpr int M_RSEL   = OFF_MISC + 736;
constexpr int M_BMAP   = OFF_MISC + 768;
constexpr int M_MX     = OFF_MISC + 896;
constexpr int M_SC     = OFF_MISC + 960;
constexpr int M_RG     = OFF_MISC + 1024;
constexpr int SMEM_BYTES = OFF_MISC + 2048;
constexpr int SMEM_LAUNCH = SMEM_BYTES;

constexpr int B_FULL = 0, B_EMPTY = NST, B_S = B_EMPTY + (NST - NSLOT + 1) / 2, B_XS = B_S + 4, B_SC = B_XS + 1, B_DP = B_SC + 1, B_Y = B_DP + 1, B_MX = B_Y + 4,
              B_XF = B_MX + 1, B_X = B_XF + 1, NBAR = B_X + 4;
constexpr int X_SLOT = 13;
static_assert(NBAR <= 84, "barrier area");

struct Exchange {
    uint4 h[8 * F_ / 8];
    uint4 r[L_ / 4];
    uint4 g[L_ / 4];
    uint2 top[16];
    unsigned epoch;
};
__device__ __align__(128) Exchange g_ex;

struct Params {
    const bf16 *u, *logA, *Aim, *Cre, *Cim, *logdt, *Dskip, *wr, *gatew;
    bf16* out;
    Exchange* ex;
    uint32_t zero;
    uint32_t swap_gu;
};

#define TSTAMP(i) do {} while (0)
#define CSTAMP(i) do {} while (0)
#define TSDUMP(mask) do {} while (0)

__device__ __forceinline__ uint32_t smem_u32(const void* p) { return (uint32_t)__cvta_generic_to_shared(p); }
__device__ __forceinline__ void mbar_init(uint32_t b, uint32_t c) { asm volatile("mbarrier.init.shared::cta.b64 [%0], %1;" :: "r"(b), "r"(c) : "memory"); }
__device__ __forceinline__ void mbar_expect(uint32_t b, uint32_t tx) { asm volatile("mbarrier.arrive.expect_tx.shared::cta.b64 _, [%0], %1;" :: "r"(b), "r"(tx) : "memory"); }
__device__ __forceinline__ void mbar_arrive(uint32_t b) { asm volatile("mbarrier.arrive.shared::cta.b64 _, [%0];" :: "r"(b) : "memory"); }
#define WSLEEP "40"
__device__ __forceinline__ void mbar_wait(uint32_t b) {
    asm volatile("{\n\t.reg .pred p, q;\n\t.reg .u32 n;\n\tmov.u32 n, 0;\n"
                 "W%=:\n\tmbarrier.try_wait.parity.shared::cta.b64 p, [%0], 0;\n\t"
                 "@p bra D%=;\n\tnanosleep.u32 " WSLEEP ";\n\tadd.u32 n, n, 1;\n\tsetp.lt.u32 q, n, 4194304;\n\t@q bra W%=;\n"
                 "D%=:\n\t}" :: "r"(b) : "memory");
}
__device__ __forceinline__ void mbar_spin(uint32_t b) {
    asm volatile("{\n\t.reg .pred p, q;\n\t.reg .u32 n;\n\tmov.u32 n, 0;\n"
                 "W%=:\n\tmbarrier.try_wait.parity.shared::cta.b64 p, [%0], 0;\n\t"
                 "@p bra D%=;\n\tadd.u32 n, n, 1;\n\tsetp.lt.u32 q, n, 4194304;\n\t@q bra W%=;\n"
                 "D%=:\n\t}" :: "r"(b) : "memory");
}
__device__ __forceinline__ uint32_t mapa(uint32_t addr, uint32_t rank) { uint32_t r; asm("mapa.shared::cluster.u32 %0, %1, %2;" : "=r"(r) : "r"(addr), "r"(rank)); return r; }
__device__ __forceinline__ void bulk_load(uint32_t dst, const void* src, uint32_t bytes, uint32_t bar) {
    asm volatile("cp.async.bulk.shared::cluster.global.mbarrier::complete_tx::bytes [%0], [%1], %2, [%3];" :: "r"(dst), "l"(src), "r"(bytes), "r"(bar) : "memory");
}
__device__ __forceinline__ void tma2d(uint32_t dst, const CUtensorMap* tm, int c0, int c1, uint32_t bar) {
    asm volatile("cp.async.bulk.tensor.2d.shared::cluster.global.mbarrier::complete_tx::bytes [%0], [%1, {%3, %4}], [%2];"
        :: "r"(dst), "l"(tm), "r"(bar), "r"(c0), "r"(c1) : "memory");
}
__device__ __forceinline__ void tma3d(uint32_t dst, const CUtensorMap* tm, int c0, int c1, int c2, uint32_t bar) {
    asm volatile("cp.async.bulk.tensor.3d.shared::cluster.global.mbarrier::complete_tx::bytes [%0], [%1, {%3, %4, %5}], [%2];"
        :: "r"(dst), "l"(tm), "r"(bar), "r"(c0), "r"(c1), "r"(c2) : "memory");
}
__device__ __forceinline__ void tma4d(uint32_t dst, const CUtensorMap* tm, int c0, int c1, int c2, int c3, uint32_t bar) {
    asm volatile("cp.async.bulk.tensor.4d.shared::cluster.global.mbarrier::complete_tx::bytes [%0], [%1, {%3, %4, %5, %6}], [%2];"
        :: "r"(dst), "l"(tm), "r"(bar), "r"(c0), "r"(c1), "r"(c2), "r"(c3) : "memory");
}
__device__ __forceinline__ void tma4d_both(uint32_t dst, const CUtensorMap* tm, int c0, int c1, int c2, int c3, uint32_t bar) {
    asm volatile("cp.async.bulk.tensor.4d.shared::cluster.global.mbarrier::complete_tx::bytes.multicast::cluster [%0], [%1, {%3, %4, %5, %6}], [%2], %7;"
        :: "r"(dst), "l"(tm), "r"(bar), "r"(c0), "r"(c1), "r"(c2), "r"(c3), "h"((unsigned short)3) : "memory");
}
__device__ __forceinline__ void st_async16(uint32_t dst, uint32_t x, uint32_t y, uint32_t z, uint32_t w, uint32_t bar) {
    asm volatile("st.async.weak.shared::cluster.mbarrier::complete_tx::bytes.v4.b32 [%0], {%1,%2,%3,%4}, [%5];"
                 :: "r"(dst), "r"(x), "r"(y), "r"(z), "r"(w), "r"(bar) : "memory");
}
__device__ __forceinline__ void st_async4(uint32_t dst, uint32_t v, uint32_t bar) {
    asm volatile("st.async.weak.shared::cluster.mbarrier::complete_tx::bytes.b32 [%0], %1, [%2];" :: "r"(dst), "r"(v), "r"(bar) : "memory");
}
__device__ __forceinline__ void bar_sync(int id, int n) { asm volatile("bar.sync %0, %1;" :: "r"(id), "r"(n) : "memory"); }
__device__ __forceinline__ void bar_arrive(int id, int n) { asm volatile("bar.arrive %0, %1;" :: "r"(id), "r"(n) : "memory"); }
__device__ __forceinline__ void cp16(uint32_t dst, const void* src) { asm volatile("cp.async.cg.shared.global [%0], [%1], 16;" :: "r"(dst), "l"(src) : "memory"); }
__device__ __forceinline__ void cp_wait_all() { asm volatile("cp.async.wait_all;" ::: "memory"); }
__device__ __forceinline__ uint32_t ldg16(const void* p) { uint32_t v; asm volatile("ld.global.nc.u16 %0, [%1];" : "=r"(v) : "l"(p)); return v; }
__device__ __forceinline__ uint2 ldg64(const void* p) { uint2 v; asm volatile("ld.global.nc.v2.u32 {%0,%1}, [%2];" : "=r"(v.x), "=r"(v.y) : "l"(p)); return v; }
__device__ __forceinline__ uint4 ldg128(const void* p) { uint4 v; asm volatile("ld.global.nc" LDX_HINT ".v4.u32 {%0,%1,%2,%3}, [%4];" : "=r"(v.x), "=r"(v.y), "=r"(v.z), "=r"(v.w) : "l"(p)); return v; }
__device__ __forceinline__ uint4 ld_gpu128(const void* p) { uint4 v; asm volatile("ld.relaxed.gpu.global.v4.u32 {%0,%1,%2,%3}, [%4];" : "=r"(v.x), "=r"(v.y), "=r"(v.z), "=r"(v.w) : "l"(p) : "memory"); return v; }
__device__ __forceinline__ void st_gpu32(void* p, uint32_t v) { asm volatile("st.relaxed.gpu.global.u32 [%0], %1;" :: "l"(p), "r"(v) : "memory"); }
__device__ __forceinline__ void st_gpu128(void* p, const uint4& v) { asm volatile("st.relaxed.gpu.global.v4.u32 [%0], {%1,%2,%3,%4};" :: "l"(p), "r"(v.x), "r"(v.y), "r"(v.z), "r"(v.w) : "memory"); }

__device__ __forceinline__ void ldsm4(uint32_t a, uint32_t& r0, uint32_t& r1, uint32_t& r2, uint32_t& r3) {
    asm volatile("ldmatrix.sync.aligned.m8n8.x4.shared.b16 {%0,%1,%2,%3}, [%4];" : "=r"(r0), "=r"(r1), "=r"(r2), "=r"(r3) : "r"(a) : "memory");
}
__device__ __forceinline__ void ldsm2(uint32_t a, uint32_t& r0, uint32_t& r1) {
    asm volatile("ldmatrix.sync.aligned.m8n8.x2.shared.b16 {%0,%1}, [%2];" : "=r"(r0), "=r"(r1) : "r"(a) : "memory");
}
__device__ __forceinline__ void ldsm4t(uint32_t a, uint32_t& r0, uint32_t& r1, uint32_t& r2, uint32_t& r3) {
    asm volatile("ldmatrix.sync.aligned.m8n8.x4.trans.shared.b16 {%0,%1,%2,%3}, [%4];" : "=r"(r0), "=r"(r1), "=r"(r2), "=r"(r3) : "r"(a) : "memory");
}
__device__ __forceinline__ uint32_t lds16(uint32_t a) { uint32_t v; asm volatile("ld.shared.u16 %0, [%1];" : "=r"(v) : "r"(a) : "memory"); return v; }
__device__ __forceinline__ uint32_t lds32(uint32_t a) { uint32_t v; asm volatile("ld.shared.u32 %0, [%1];" : "=r"(v) : "r"(a) : "memory"); return v; }
__device__ __forceinline__ uint2 lds64(uint32_t a) { uint2 v; asm volatile("ld.shared.v2.u32 {%0,%1}, [%2];" : "=r"(v.x), "=r"(v.y) : "r"(a) : "memory"); return v; }
__device__ __forceinline__ uint4 lds128(uint32_t a) { uint4 v; asm volatile("ld.shared.v4.u32 {%0,%1,%2,%3}, [%4];" : "=r"(v.x), "=r"(v.y), "=r"(v.z), "=r"(v.w) : "r"(a) : "memory"); return v; }
__device__ __forceinline__ void sts16(uint32_t a, uint32_t v) { asm volatile("st.shared.u16 [%0], %1;" :: "r"(a), "h"((unsigned short)v) : "memory"); }
__device__ __forceinline__ void sts32(uint32_t a, uint32_t v) { asm volatile("st.shared.u32 [%0], %1;" :: "r"(a), "r"(v) : "memory"); }
__device__ __forceinline__ void sts64(uint32_t a, uint32_t x, uint32_t y) { asm volatile("st.shared.v2.u32 [%0], {%1,%2};" :: "r"(a), "r"(x), "r"(y) : "memory"); }
__device__ __forceinline__ void sts128(uint32_t a, uint32_t x, uint32_t y, uint32_t z, uint32_t w) { asm volatile("st.shared.v4.u32 [%0], {%1,%2,%3,%4};" :: "r"(a), "r"(x), "r"(y), "r"(z), "r"(w) : "memory"); }
__device__ __forceinline__ void sts16_if(bool p, uint32_t a, uint32_t v) { asm volatile("{ .reg .pred q; setp.ne.u32 q, %2, 0; @q st.shared.u16 [%0], %1; }" :: "r"(a), "h"((unsigned short)v), "r"((uint32_t)p) : "memory"); }
__device__ __forceinline__ void sts128_if(bool p, uint32_t a, uint32_t x, uint32_t y, uint32_t z, uint32_t w) {
    asm volatile("{ .reg .pred q; setp.ne.u32 q, %5, 0; @q st.shared.v4.u32 [%0], {%1,%2,%3,%4}; }" :: "r"(a), "r"(x), "r"(y), "r"(z), "r"(w), "r"((uint32_t)p) : "memory");
}
__device__ __forceinline__ void stsf(uint32_t a, float v) { asm volatile("st.shared.f32 [%0], %1;" :: "r"(a), "f"(v) : "memory"); }
__device__ __forceinline__ float ldsf(uint32_t a) { float v; asm volatile("ld.shared.f32 %0, [%1];" : "=f"(v) : "r"(a) : "memory"); return v; }

__device__ __forceinline__ void mma_bf(float (&d)[4], uint32_t a0, uint32_t a1, uint32_t a2, uint32_t a3, uint32_t b0, uint32_t b1) {
    asm volatile("mma.sync.aligned.m16n8k16.row.col.f32.bf16.bf16.f32 {%0,%1,%2,%3}, {%4,%5,%6,%7}, {%8,%9}, {%0,%1,%2,%3};"
        : "+f"(d[0]), "+f"(d[1]), "+f"(d[2]), "+f"(d[3]) : "r"(a0), "r"(a1), "r"(a2), "r"(a3), "r"(b0), "r"(b1));
}
__device__ __forceinline__ void widen_bf(float (&d)[4], uint32_t a0, uint32_t a1, uint32_t b) {
    asm volatile("mma.sync.aligned.m16n8k8.row.col.f32.bf16.bf16.f32 {%0,%1,%2,%3}, {%4,%5}, {%6}, {%7,%7,%7,%7};"
        : "=f"(d[0]), "=f"(d[1]), "=f"(d[2]), "=f"(d[3]) : "r"(a0), "r"(a1), "r"(b), "f"(0.f));
}
__device__ __forceinline__ void widen_h(float (&d)[4], const uint32_t (&a)[2], uint32_t b) {
    asm volatile("mma.sync.aligned.m16n8k8.row.col.f32.f16.f16.f32 {%0,%1,%2,%3}, {%4,%5}, {%6}, {%7,%7,%7,%7};"
        : "=f"(d[0]), "=f"(d[1]), "=f"(d[2]), "=f"(d[3]) : "r"(a[0]), "r"(a[1]), "r"(b), "f"(0.f));
}
__device__ __forceinline__ void widen_add_h(float (&d)[4], const uint32_t (&a)[2], uint32_t b, const float (&c)[4]) {
    asm volatile("mma.sync.aligned.m16n8k8.row.col.f32.f16.f16.f32 {%0,%1,%2,%3}, {%4,%5}, {%6}, {%7,%8,%9,%10};"
        : "=f"(d[0]), "=f"(d[1]), "=f"(d[2]), "=f"(d[3]) : "r"(a[0]), "r"(a[1]), "r"(b), "f"(c[0]), "f"(c[1]), "f"(c[2]), "f"(c[3]));
}
__device__ __forceinline__ void mma_h(uint32_t (&d)[2], const uint32_t (&a)[4], uint32_t b0, uint32_t b1) {
    asm volatile("mma.sync.aligned.m16n8k16.row.col.f16.f16.f16.f16 {%0,%1}, {%2,%3,%4,%5}, {%6,%7}, {%0,%1};"
        : "+r"(d[0]), "+r"(d[1]) : "r"(a[0]), "r"(a[1]), "r"(a[2]), "r"(a[3]), "r"(b0), "r"(b1));
}
__device__ __forceinline__ void mma_h_z(uint32_t& d0, uint32_t& d1, const uint32_t (&a)[4], uint32_t b0, uint32_t b1) {
    asm volatile("mma.sync.aligned.m16n8k16.row.col.f16.f16.f16.f16 {%0,%1}, {%2,%3,%4,%5}, {%6,%7}, {%8,%8};"
        : "=r"(d0), "=r"(d1) : "r"(a[0]), "r"(a[1]), "r"(a[2]), "r"(a[3]), "r"(b0), "r"(b1), "r"(0u));
}
__device__ __forceinline__ void mma_h2(uint32_t& d0, uint32_t& d1, const uint32_t (&a)[4], uint32_t b0, uint32_t b1) {
    asm volatile("mma.sync.aligned.m16n8k16.row.col.f16.f16.f16.f16 {%0,%1}, {%2,%3,%4,%5}, {%6,%7}, {%0,%1};"
        : "+r"(d0), "+r"(d1) : "r"(a[0]), "r"(a[1]), "r"(a[2]), "r"(a[3]), "r"(b0), "r"(b1));
}
__device__ __forceinline__ void mma_h_k8(uint32_t& d0, uint32_t& d1, uint32_t a0, uint32_t a1, uint32_t b) {
    asm volatile("mma.sync.aligned.m16n8k8.row.col.f16.f16.f16.f16 {%0,%1}, {%2,%3}, {%4}, {%0,%1};" : "+r"(d0), "+r"(d1) : "r"(a0), "r"(a1), "r"(b));
}
__device__ __forceinline__ void mma_h_k8_z(uint32_t (&d)[2], uint32_t a0, uint32_t a1, uint32_t b) {
    asm volatile("mma.sync.aligned.m16n8k8.row.col.f16.f16.f16.f16 {%0,%1}, {%2,%3}, {%4}, {%5,%5};" : "=r"(d[0]), "=r"(d[1]) : "r"(a0), "r"(a1), "r"(b), "r"(0u));
}
__device__ __forceinline__ uint32_t pack_bf(float lo, float hi) { uint32_t r; asm("cvt.rn.bf16x2.f32 %0, %1, %2;" : "=r"(r) : "f"(hi), "f"(lo)); return r; }
__device__ __forceinline__ uint32_t pack_h(float lo, float hi) { uint32_t r; asm("cvt.rn.f16x2.f32 %0, %1, %2;" : "=r"(r) : "f"(hi), "f"(lo)); return r; }
__device__ __forceinline__ float bf_lo(uint32_t v) { return __uint_as_float(v << 16); }
__device__ __forceinline__ float bf_hi(uint32_t v) { return __uint_as_float(v & 0xffff0000u); }
__device__ __forceinline__ float bf_round(float x) { return __uint_as_float(pack_bf(0.f, x) & 0xffff0000u); }
__device__ __forceinline__ uint32_t hmul2_bf(uint32_t a, uint32_t b) { uint32_t r; asm("mul.rn.bf16x2 %0, %1, %2;" : "=r"(r) : "r"(a), "r"(b)); return r; }
__device__ __forceinline__ uint32_t hadd2_bf(uint32_t a, uint32_t b) { uint32_t r; asm("add.rn.bf16x2 %0, %1, %2;" : "=r"(r) : "r"(a), "r"(b)); return r; }
__device__ __forceinline__ uint32_t hfma2_bf(uint32_t a, uint32_t b, uint32_t c) { uint32_t r; asm("fma.rn.bf16x2 %0, %1, %2, %3;" : "=r"(r) : "r"(a), "r"(b), "r"(c)); return r; }
__device__ __forceinline__ uint32_t amax2_bf(uint32_t m, uint32_t v) { uint32_t r; asm("max.xorsign.abs.bf16x2 %0, %1, %2;" : "=r"(r) : "r"(m), "r"(v)); return r; }
__device__ __forceinline__ uint32_t amax2_h(uint32_t m, uint32_t v) { uint32_t r; asm("max.xorsign.abs.f16x2 %0, %1, %2;" : "=r"(r) : "r"(m), "r"(v)); return r; }
__device__ __forceinline__ uint32_t hadd(uint32_t a, uint32_t b) { uint32_t r; asm("add.rn.f16x2 %0, %1, %2;" : "=r"(r) : "r"(a), "r"(b)); return r; }
__device__ __forceinline__ uint32_t hsub(uint32_t a, uint32_t b) { uint32_t r; asm("sub.rn.f16x2 %0, %1, %2;" : "=r"(r) : "r"(a), "r"(b)); return r; }
__device__ __forceinline__ uint32_t hmul(uint32_t a, uint32_t b) { uint32_t r; asm("mul.rn.f16x2 %0, %1, %2;" : "=r"(r) : "r"(a), "r"(b)); return r; }
__device__ __forceinline__ uint32_t hfma(uint32_t a, uint32_t b, uint32_t c) { uint32_t r; asm("fma.rn.f16x2 %0, %1, %2, %3;" : "=r"(r) : "r"(a), "r"(b), "r"(c)); return r; }
__device__ __forceinline__ uint32_t hfms(uint32_t a, uint32_t b, uint32_t c) { uint32_t r; asm("{ .reg .b32 t; neg.f16x2 t, %3; fma.rn.f16x2 %0, %1, %2, t; }" : "=r"(r) : "r"(a), "r"(b), "r"(c)); return r; }
__device__ __forceinline__ uint32_t warp_max16(uint32_t m) { return __reduce_max_sync(0xffffffffu, max(m & 0x7fffu, (m >> 16) & 0x7fffu)); }
__device__ __forceinline__ float ex2f(float x) { float r; asm("ex2.approx.ftz.f32 %0, %1;" : "=f"(r) : "f"(x)); return r; }

__device__ __forceinline__ float exp_acc(float x) {
    const float t = x * 1.4426950216293335f;
    const float r = fmaf(x, 1.4426950216293335f, -t) + x * 1.9259629911266175e-8f;
    return ex2f(t) * fmaf(r, 0.6931471805599453f, 1.f);
}
__device__ __forceinline__ float sigmoid_f(float x) { return __fdividef(1.f, 1.f + ex2f(-x * 1.4426950408889634f)); }
__device__ __forceinline__ void cexp(float l2, float th, float& zr, float& zi) {
    const float mag = ex2f(l2);
    const float k = (th * 0.15915494309189535f + 12582912.f) - 12582912.f;
    float r = fmaf(-k, 6.2831854820251465f, th);
    r = fmaf(-k, -1.7484555314695172e-7f, r);
    zr = mag * __cosf(r);
    zi = mag * __sinf(r);
}
struct hc { uint32_t re, im; };
__device__ __forceinline__ hc cmul(const hc& a, const hc& b) { return {hfms(a.re, b.re, hmul(a.im, b.im)), hfma(a.re, b.im, hmul(a.im, b.re))}; }
__device__ __forceinline__ hc cmulc(const hc& a, const hc& b) { return {hfma(a.re, b.re, hmul(a.im, b.im)), hfms(a.im, b.re, hmul(a.re, b.im))}; }
struct fc2 { float r[2], i[2]; };
__device__ __forceinline__ void csq(fc2& z) {
#pragma unroll
    for (int m = 0; m < 2; m++) {
        const float r = fmaf(z.r[m], z.r[m], -(z.i[m] * z.i[m]));
        asm("{ .reg .f32 t; mul.f32 t, %0, %1; mul.f32 %0, t, 0f40000000; }" : "+f"(z.i[m]) : "f"(z.r[m]));
        z.r[m] = r;
    }
}
__device__ __forceinline__ hc pk(const fc2& z) { return {pack_h(z.r[0], z.r[1]), pack_h(z.i[0], z.i[1])}; }
__device__ __forceinline__ void csq_conj(fc2& z) {
#pragma unroll
    for (int m = 0; m < 2; m++) {
        const float r = fmaf(z.r[m], z.r[m], -(z.i[m] * z.i[m]));
        asm("{ .reg .f32 t, n; neg.f32 n, %1; mul.f32 t, %0, n; mul.f32 %0, t, 0f40000000; }" : "+f"(z.i[m]) : "f"(z.r[m]));
        z.r[m] = r;
    }
}

struct Powers { hc C, z1, z2, z4, c8, c16, c32, c64, z128, z256, z512, z1024; };
__device__ __forceinline__ void kg_powers(Powers& q, uint32_t la, uint32_t ai, uint32_t cr, uint32_t ci, float dt, float cf) {
    fc2 z, y;
    const float dtl = -dt * 1.4426950408889634f;
    const uint32_t eb = pack_bf(ex2f(bf_lo(la) * 1.4426950408889634f), ex2f(bf_hi(la) * 1.4426950408889634f));
    const float l2[2] = {bf_lo(eb) * dtl, bf_hi(eb) * dtl}, th[2] = {bf_lo(ai) * dt, bf_hi(ai) * dt};
#pragma unroll
    for (int m = 0; m < 2; m++) { cexp(l2[m], th[m], z.r[m], z.i[m]); cexp(l2[m] * 128.f, th[m] * 128.f, y.r[m], y.i[m]); }
    q.C.re = pack_h(bf_lo(cr) * cf, bf_hi(cr) * cf);
    q.C.im = pack_h(bf_lo(ci) * cf, bf_hi(ci) * cf);
    q.z1 = pk(z); csq(z); q.z128 = pk(y); csq(y);
    q.z2 = pk(z); csq(z); q.z256 = pk(y); csq(y);
    q.z4 = pk(z); csq_conj(z); q.z512 = pk(y); csq(y);
    q.c8 = pk(z); csq(z); q.z1024 = pk(y);
    q.c16 = pk(z); csq(z);
    q.c32 = pk(z); csq(z);
    q.c64 = pk(z);
}
struct Rows { hc ta[8], tb[8], tc[8], pp[8]; };
#define PUT(a0, a1, row, a, b) sts128((((row) & 1) ? (a1) : (a0)) + (row) * 512, (a).re, (a).im, (b).re, (b).im)
template <bool FIRST>
__device__ __forceinline__ void kg_rows(Rows& w, const Powers& q, uint32_t t0, uint32_t t1, uint32_t u0, uint32_t u1, uint32_t zr, uint32_t (&Rl)[2]) {
    w.ta[0] = q.C; w.ta[1] = cmul(q.C, q.z1); w.ta[2] = cmul(q.C, q.z2); w.ta[4] = cmul(q.C, q.z4); w.tb[0] = cmul(q.C, q.z256); w.tb[4] = cmul(q.C, q.z512);
    PUT(t0, t1, 0, w.ta[0], w.tb[0]); PUT(t0, t1, 4, w.ta[4], w.tb[4]);
    w.tb[1] = cmul(w.ta[2], q.z256); w.tb[2] = cmul(w.ta[4], q.z256);
    PUT(t0, t1, 1, w.ta[1], w.tb[1]); PUT(t0, t1, 2, w.ta[2], w.tb[2]);
    w.ta[3] = cmul(w.ta[1], q.z2); w.ta[6] = cmul(w.ta[2], q.z4); w.ta[5] = cmul(w.ta[1], q.z4); w.tb[5] = cmul(w.ta[4], q.z512); w.tb[6] = cmul(w.tb[0], q.z512);
    PUT(t0, t1, 5, w.ta[5], w.tb[5]); PUT(t0, t1, 6, w.ta[6], w.tb[6]);
    w.tb[3] = cmul(w.ta[6], q.z256); w.ta[7] = cmul(w.ta[3], q.z4); w.tb[7] = cmul(w.tb[2], q.z512);
    PUT(t0, t1, 3, w.ta[3], w.tb[3]); PUT(t0, t1, 7, w.ta[7], w.tb[7]);
    PUT(u0, u1, 8, q.c64, q.z128);
    w.pp[0] = hc{0x3C003C00u ^ zr, zr}; w.pp[1] = q.c8; w.pp[2] = q.c16; w.pp[4] = q.c32;
    w.tc[0] = cmul(q.C, q.z1024); w.pp[3] = cmul(q.c8, q.c16); w.pp[5] = cmul(q.c8, q.c32); w.pp[6] = cmul(q.c16, q.c32);
    w.tc[2] = cmul(w.tc[0], q.z128); w.tc[4] = cmul(w.tc[0], q.z256); w.tc[1] = cmul(w.tc[0], q.z512); w.pp[7] = cmul(w.pp[3], q.c32);
    PUT(u0, u1, 0, w.tc[0], w.pp[0]); PUT(u0, u1, 1, w.tc[1], w.pp[1]); PUT(u0, u1, 2, w.tc[2], w.pp[2]); PUT(u0, u1, 4, w.tc[4], w.pp[4]);
    w.tc[6] = cmul(w.tc[2], q.z256); w.tc[3] = cmul(w.tc[2], q.z512); w.tc[5] = cmul(w.tc[4], q.z512);
    PUT(u0, u1, 3, w.tc[3], w.pp[3]); PUT(u0, u1, 5, w.tc[5], w.pp[5]); PUT(u0, u1, 6, w.tc[6], w.pp[6]);
    w.tc[7] = cmul(w.tc[6], q.z512);
    PUT(u0, u1, 7, w.tc[7], w.pp[7]);
    const uint32_t last = hfms(w.tc[0].re, q.z1024.re, hmul(w.tc[0].im, q.z1024.im));
    if (FIRST) mma_h_k8_z(Rl, 0x3C003C00u - zr, 0x3C003C00u + zr, last); else mma_h_k8(Rl[0], Rl[1], 0x3C003C00u - zr, 0x3C003C00u + zr, last);
}
__device__ __forceinline__ void kg_keep(const Rows& w, const Powers& q, uint32_t t0, uint32_t t1, uint32_t u0, uint32_t u1, uint32_t zr) {
}
#undef PUT
template <bool FIRST>
__device__ __forceinline__ void kg_products(uint32_t rt0, uint32_t rt1, uint32_t ru0, uint32_t ru1, uint32_t rc, uint32_t zr,
                                            uint32_t (&Ra)[2][2], uint32_t (&Rb)[2][2], uint32_t (&Rc)[2]) {
    uint4 q1[8], q2[8], cw[8];
#pragma unroll
    for (int ks = 0; ks < 8; ks++) {
        q2[ks] = lds128(((ks & 1) ? ru1 : ru0) + (ks >> 1) * 128); cw[ks] = lds128(rc + ks * 64); q1[ks] = lds128(((ks & 1) ? rt1 : rt0) + (ks >> 1) * 128);
    }
#pragma unroll
    for (int ks = 0; ks < 8; ks++) {
        const hc p0 = {q2[ks].z, q2[ks].w}, u = {cw[ks].x, cw[ks].y}, v = {cw[ks].z, cw[ks].w};
        const hc p1 = cmul(p0, u), p2 = cmulc(p0, v), p3 = cmulc(p1, v);
        const uint32_t qa[4] = {p0.re ^ zr, p1.re, p0.im ^ zr, p1.im}, qb[4] = {p2.re, p3.re, p2.im, p3.im};
        if (FIRST && ks == 0) {
            mma_h_z(Rc[0], Rc[1], qa, q2[ks].x, q2[ks].y); mma_h_z(Ra[0][0], Ra[0][1], qa, q1[ks].x, q1[ks].y); mma_h_z(Rb[0][0], Rb[0][1], qa, q1[ks].z, q1[ks].w);
            mma_h_z(Ra[1][0], Ra[1][1], qb, q1[ks].x, q1[ks].y); mma_h_z(Rb[1][0], Rb[1][1], qb, q1[ks].z, q1[ks].w);
        } else {
            mma_h(Rc, qa, q2[ks].x, q2[ks].y); mma_h(Ra[0], qa, q1[ks].x, q1[ks].y); mma_h(Rb[0], qa, q1[ks].z, q1[ks].w);
            mma_h(Ra[1], qb, q1[ks].x, q1[ks].y); mma_h(Rb[1], qb, q1[ks].z, q1[ks].w);
        }
    }
}
__device__ __forceinline__ void kernel_gen(const uint2& la, const uint2& ai, const uint2& cr, const uint2& ci, float dt, float cf, uint32_t TB, uint32_t UB,
                                           int lane, uint32_t zr, uint32_t (&Ra)[2][2], uint32_t (&Rb)[2][2], uint32_t (&Rc)[2], uint32_t (&Rl)[2]) {
    const int g = lane >> 2, t = lane & 3;
    const uint32_t w0 = lane << 4, w1 = w0 ^ 64, r0 = g * 512 + (((g & 1) << 6) | (t << 4)), r1 = r0 ^ 64;
    const uint32_t t0 = TB + w0, t1 = TB + w1, u0 = UB + w0, u1 = UB + w1;
    Powers p0, p1;
    Rows w;
    kg_powers(p0, la.x, ai.x, cr.x, ci.x, dt, cf);
    kg_rows<true>(w, p0, t0, t1, u0, u1, zr, Rl);
    kg_powers(p1, la.y, ai.y, cr.y, ci.y, dt, cf);
    kg_keep(w, p0, t0, t1, u0, u1, zr);
    __syncwarp();
    kg_products<true>(TB + r0, TB + r1, UB + r0, UB + r1, UB + 4096 + t * 16, zr, Ra, Rb, Rc);
    __syncwarp();
    kg_rows<false>(w, p1, t0, t1, u0, u1, zr, Rl);
    kg_keep(w, p1, t0, t1, u0, u1, zr);
    __syncwarp();
    kg_products<false>(TB + r0, TB + r1, UB + r0, UB + r1, UB + 4096 + t * 16, zr, Ra, Rb, Rc);
    __syncwarp();
}

template <bool FIRST, class Hook>
__device__ __forceinline__ void dense_step(uint32_t (&M)[8][2], uint32_t (&Ye)[8][2], uint32_t (&Yo)[8][2], uint32_t (&X)[8][2],
                                           uint32_t (&F)[8][2], uint32_t (&Bq)[2][4], uint32_t ua, uint32_t ta, uint32_t un, uint32_t zr, Hook hook) {
    uint32_t E[8][2], A[2][4], S[2][4];
#pragma unroll
    for (int jp = 0; jp < 4; jp++) ldsm4(ua + jp * 256, E[2 * jp][0], E[2 * jp][1], E[2 * jp + 1][0], E[2 * jp + 1][1]);
#pragma unroll
    for (int h = 0; h < 2; h++) { A[h][0] = lds32(ta + 1024 * h); A[h][1] = lds32(ta + 1024 * h + 32); A[h][3] = lds32(ta + 1024 * h + 64); A[h][2] = A[h][1] ^ zr; }
    if (FIRST) {
        uint32_t N[8];
        ldsm4(un, N[0], N[1], N[2], N[3]); ldsm4(un + 512, N[4], N[5], N[6], N[7]);
        hook();
        const uint32_t a1 = A[0][0] ^ zr;
#pragma unroll
        for (int J = 0; J < 8; J++) mma_h_k8_z(Ye[J], zr, a1, X[J][1]);
#pragma unroll
        for (int J = 0; J < 8; J++) mma_h_k8_z(Yo[J], zr, a1, N[J]);
    } else {
#pragma unroll
        for (int J = 0; J < 8; J++) mma_h(Ye[J], Bq[0], F[J][0], F[J][1]);
#pragma unroll
        for (int J = 1; J < 8; J++) mma_h(Ye[J], Bq[1], F[J - 1][0], F[J - 1][1]);
    }
    uint32_t G[8][2];
#pragma unroll
    for (int J = 0; J < 8; J++) { G[J][0] = hsub(X[J][0], E[J][0]); G[J][1] = hsub(X[J][1], E[J][1]); }
#pragma unroll
    for (int jp = 0; jp < 4; jp++) ldsm4(ua + 2 * U_PL + jp * 256 - 16, X[2 * jp][0], X[2 * jp][1], X[2 * jp + 1][0], X[2 * jp + 1][1]);
#pragma unroll
    for (int h = 0; h < 2; h++) { Bq[h][1] = lds32(ta + 1024 * h + 96); Bq[h][3] = lds32(ta + 1024 * h + 128); Bq[h][0] = A[h][3] ^ zr; Bq[h][2] = Bq[h][1] ^ zr; }
#pragma unroll
    for (int J = 0; J < 8; J++) mma_h(Yo[J], A[0], G[J][0], G[J][1]);
#pragma unroll
    for (int J = 1; J < 8; J++) mma_h(Yo[J], A[1], G[J - 1][0], G[J - 1][1]);
#pragma unroll
    for (int h = 0; h < 2; h++)
#pragma unroll
        for (int i = 0; i < 4; i++) S[h][i] = hadd(A[h][i], Bq[h][i]);
#pragma unroll
    for (int J = 0; J < 8; J++) { if (FIRST) mma_h_z(M[J][0], M[J][1], S[0], E[J][0], E[J][1]); else mma_h(M[J], S[0], E[J][0], E[J][1]); }
#pragma unroll
    for (int J = 1; J < 8; J++) mma_h(M[J], S[1], E[J - 1][0], E[J - 1][1]);
    if (FIRST) {
        uint32_t A2[4];
        A2[0] = lds32(ta + 2048); A2[1] = lds32(ta + 2048 + 32); A2[3] = lds32(ta + 2048 + 64); A2[2] = A2[1] ^ zr;
#pragma unroll
        for (int J = 2; J < 8; J++) mma_h(Yo[J], A2, G[J - 2][0], G[J - 2][1]);
#pragma unroll
        for (int J = 2; J < 8; J++) mma_h(M[J], A2, E[J - 2][0], E[J - 2][1]);
    }
#pragma unroll
    for (int J = 0; J < 8; J++) { F[J][0] = hsub(X[J][0], E[J][0]); F[J][1] = hsub(X[J][1], E[J][1]); }
}

#define LANE_VARS \
    int tid_; asm volatile("mov.u32 %0, %%tid.x;" : "=r"(tid_)); \
    [[maybe_unused]] const int lane = tid_ & 31, warp = (tid_ >> 5) - MAIN_W0, g = lane >> 2, t = lane & 3, mi = lane >> 3, r = lane & 7; \
    [[maybe_unused]] const uint32_t TB = sb + OFF_TAB + warp * T_CH, UB = sb + OFF_U + warp * U_CH; \
    [[maybe_unused]] const bool lead = (tid_ == 32 * MAIN_W0)

__global__ void __cluster_dims__(2, 1, 1) __launch_bounds__(NTHREADS, 1)
fused_kernel(const Params p, const __grid_constant__ CUtensorMap tm_gu, const __grid_constant__ CUtensorMap tm_down, const __grid_constant__ CUtensorMap tm_x,
             const __grid_constant__ CUtensorMap tm_r) {
    extern __shared__ __align__(1024) unsigned char smem[];
    const uint32_t sb = __shfl_sync(0xffffffffu, smem_u32(smem), 0);
    int tid;
    asm volatile("mov.u32 %0, %%tid.x;" : "=r"(tid));
    const int pw = tid >> 5, lane = tid & 31;
    const int c = blockIdx.x, h = c & 1, pr = c >> 1;
    const uint32_t bars = sb + M_BARS;

    if (c >= 128) {
        if (c != 128) return;
        const unsigned tag = (*(volatile unsigned*)&p.ex->epoch + 1) & 0xffffu;
        const uint32_t idx0 = 2047 - (256 * (tid & 3) + (tid >> 3) + 1024 * ((tid >> 2) & 1));
        const uint32_t list = sb + 128;
#pragma unroll 1
        for (int pass = 0; pass < 2; pass++) {
            if (tid == 0) sts32(sb + 64, 0);
            sts128(list + 16 * tid, 0, 0, 0, 0);
            uint4 a = make_uint4(lane == 0 ? 0x10000u : 0u, 0, 0, 0);
            bool ok = pass == 0;
#pragma unroll 1
            for (int it = 0; it < (1 << 22) && !ok; it++) {
                a = ld_gpu128(&p.ex->r[tid]);
                ok = (((a.x ^ tag) | (a.y ^ tag) | (a.z ^ tag) | (a.w ^ tag)) & 0xffffu) == 0;
            }
            if (!ok) __trap();
            const uint32_t key[4] = {(a.x & 0xffff0000u) | idx0, (a.y & 0xffff0000u) | (idx0 - 64), (a.z & 0xffff0000u) | (idx0 - 128), (a.w & 0xffff0000u) | (idx0 - 192)};
            const uint32_t wm = __reduce_max_sync(0xffffffffu, max(max(key[0], key[1]), max(key[2], key[3])));
            if (lane == 0) sts32(sb + pw * 4, wm);
            __syncthreads();
            const uint2 q = lds64(sb + 8 * (lane & 7));
            const uint32_t thr = __reduce_min_sync(0xffffffffu, max(q.x, q.y));
            if (tid == 0) TSTAMP(0);
            const uint32_t n = (key[0] >= thr) + (key[1] >= thr) + (key[2] >= thr) + (key[3] >= thr);
            if (n) {
                uint32_t pos;
                asm volatile("atom.shared.add.u32 %0, [%1], %2;" : "=r"(pos) : "r"(sb + 64), "r"(n) : "memory");
#pragma unroll
                for (int i = 0; i < 4; i++) if (key[i] >= thr) { sts32(list + 4 * pos, key[i]); pos++; }
            }
            __syncthreads();
            const int ncand = (int)lds32(sb + 64);
            const uint2 l0 = lds64(list + 8 * lane);
#pragma unroll 1
            for (int j = pw; j < ncand; j += 16) {
                const uint32_t mine = lds32(list + 4 * j);
                int rank = __popc(__ballot_sync(0xffffffffu, l0.x > mine)) + __popc(__ballot_sync(0xffffffffu, l0.y > mine));
#pragma unroll 1
                for (int i = 64; i < ncand; i += 32) rank += __popc(__ballot_sync(0xffffffffu, lds32(list + 4 * (i + lane)) > mine));
                if (rank < 8 && lane == 0) asm volatile("st.relaxed.gpu.global.v2.u32 [%0], {%1, %2};" :: "l"(&p.ex->top[rank]), "r"(mine), "r"(pass ? tag : tag ^ 0x8000u) : "memory");
            }
            if (tid == 0) TSTAMP(1);
            __syncthreads();
        }
        if (tid == 0) TSDUMP(3u);
        return;
    }

    if (pw != 12) asm volatile("barrier.cluster.arrive.relaxed.aligned;" ::: "memory");

    if (pw >= MAIN_W0 && pw < MAIN_W0 + 8) {
        const int warp = pw - MAIN_W0;
        const uint32_t po = (8 * c + warp) * 128 + 4 * lane;
        uint2 v_la = ldg64(p.logA + po), v_ai = ldg64(p.Aim + po), v_cr = ldg64(p.Cre + po), v_ci = ldg64(p.Cim + po);
        const uint32_t ldt16 = ldg16(p.logdt + 8 * c + warp);
        [[maybe_unused]] const bool lead = (tid == 32 * MAIN_W0);
        asm volatile("setmaxnreg.inc.sync.aligned.u32 " MAIN_REGS ";");
        [[maybe_unused]] const int d = 8 * c + warp;
        const int g = lane >> 2, t = lane & 3, mi = lane >> 3, r = lane & 7;
        const uint32_t TB = sb + OFF_TAB + warp * T_CH;
        const uint32_t UB = sb + OFF_U + warp * U_CH;
        const uint32_t zr = p.zero;

        uint32_t Ra[2][2], Rb[2][2], Rc[2], Rl[2];
        int esum;
        {
            const float dt = bf_round(exp_acc(__uint_as_float(ldt16 << 16)));
            const uint32_t ec = max(warp_max16(amax2_bf(amax2_bf(v_cr.x, v_cr.y), amax2_bf(v_ci.x, v_ci.y))) >> 7, 6u);
            const float cf = __uint_as_float((__float_as_uint(dt) & 0x7fffffu) | ((260u - ec) << 23));
            esum = (int)ec + (int)(__float_as_uint(dt) >> 23) - 274;
            kernel_gen(v_la, v_ai, v_cr, v_ci, dt, cf, TB, UB, lane, zr, Ra, Rb, Rc, Rl);
        }
        if (lead) TSTAMP(2);
        bar_sync(5, 384);

        uint32_t xr[8][4], utail = 0;
        {
#pragma unroll
            for (int i = 0; i < 4; i++) mbar_wait(bars + 8 * (B_S + i));
            if (lead) TSTAMP(9);
            const int dl = 8 * (r >> 1) + 4 - 2 * mi - (r & 1);
            const uint32_t so = sb + OFF_S + (8 * warp + (dl >> 5)) * 1024 + (dl & 7) * 128 + ((dl >> 3) & 3) * 32 + (((dl & 1) ^ h) << 4);
#pragma unroll
            for (int i = 0; i < 8; i++) ldsm4t(so + i * 1024, xr[i][0], xr[i][1], xr[i][2], xr[i][3]);
            if (lane >= 5 && lane < 8) utail = lds16(sb + OFF_S + 63 * 1024 + 96 + (12 - lane) * 128 + (((lane & 1) ^ h) << 4) + 2 * warp);
            uint32_t mx = utail;
#pragma unroll
            for (int i = 0; i < 8; i++) mx = amax2_bf(amax2_bf(mx, amax2_bf(xr[i][0], xr[i][1])), amax2_bf(xr[i][2], xr[i][3]));
            mx = warp_max16(mx);
            if (lane == 0) { sts32(sb + M_MX + warp * 4, mx); mbar_arrive(bars + 8 * B_MX); }
        }

        uint32_t vb[4], vc[2], kl;
        {
            kl = hadd(Rl[0], __byte_perm(Rl[0], 0, 0x1032));
            kl = hadd(kl, __shfl_xor_sync(0xffffffffu, kl, 1)); kl = hadd(kl, __shfl_xor_sync(0xffffffffu, kl, 2));
            uint32_t mk = amax2_h(amax2_h(amax2_h(Ra[0][0], Ra[0][1]), amax2_h(Ra[1][0], Ra[1][1])), amax2_h(amax2_h(Rb[0][0], Rb[0][1]), amax2_h(Rb[1][0], Rb[1][1])));
            mk = amax2_h(amax2_h(mk, kl), amax2_h(Rc[0], Rc[1]));
            const uint32_t ek = warp_max16(mk) >> 10;
            esum += (int)ek;
            const float fs = __uint_as_float((139u - ek) << 23);
            const uint32_t ks = pack_h(fs, fs);
            sts128(UB + mi * U_PL + r * 16, 0, 0, 0, 0);
            uint32_t va[4];
#pragma unroll
            for (int i = 0; i < 4; i++) { va[i] = hmul(Ra[i >> 1][i & 1], ks); vb[i] = hmul(Rb[i >> 1][i & 1], ks); }
            vc[0] = hmul(Rc[0], ks); vc[1] = hmul(Rc[1], ks); kl = hmul(kl, ks);
            const uint32_t k512 = __shfl_sync(0xffffffffu, vb[0], 2) & 0xffffu, k255 = __shfl_sync(0xffffffffu, va[3], 31);
#pragma unroll
            for (int i = 0; i < 4; i++) {
                const uint32_t pv = __shfl_sync(0xffffffffu, lane == 31 ? (i ? va[i - 1] : 0u) : va[i], lane - 1);
                sts64(TB + 48 + 256 * i + 8 * lane, __byte_perm(pv, va[i], 0x5432), va[i]);
            }
#pragma unroll
            for (int i = 0; i < 4; i++) {
                const uint32_t nx = __shfl_sync(0xffffffffu, lane == 0 ? (i < 3 ? vb[i + (i < 3)] : k512) : vb[i], lane + 1 + 2 * (lane & 1));
                const uint32_t aa = __byte_perm(vb[i], 0, 0x1010);
                sts128_if(t < 2, TB + 1072 + 256 * i + 32 * g + 16 * t, (i == 0 && lane == 0) ? __byte_perm(k255, aa, 0x5432) : aa ^ zr, aa, vb[i] ^ zr, __byte_perm(vb[i], nx, 0x5432));
            }
            const uint32_t k0 = lane == 3 ? k512 : 0u, kk = k0 * 0x10001u;
            sts128_if(lane < 8, TB + 16 * lane + (lane < 3 ? 0 : 2048), kk, kk ^ zr, kk + zr, k0);
        }
        if (lead) TSTAMP(11);

        {
            mbar_wait(bars + 8 * B_MX);
            const uint32_t eu = max(__reduce_max_sync(0xffffffffu, lds32(sb + M_MX + r * 4)) >> 7, 3u);
            esum += (int)eu;
            const uint32_t sc = (257u - eu) << 7;
            const uint32_t idb = (g == 2 * t) ? sc : (g == 2 * t + 1) ? sc << 16 : 0u;
            const uint32_t uo = sb + OFF_U + g * U_CH + t * U_PL + (8 + 8 * warp) * 16;
#pragma unroll
            for (int i = 0; i < 8; i++) {
                float f0[4], f1[4];
                widen_bf(f0, xr[i][0], xr[i][1], idb); widen_bf(f1, xr[i][2], xr[i][3], idb);
                sts128(uo + i * 16, pack_h(f0[0], f0[1]), pack_h(f0[2], f0[3]), pack_h(f1[0], f1[1]), pack_h(f1[2], f1[3]));
            }
            if (lane < 8) sts16(UB + 72 * 16 + lane * 2, pack_h(bf_lo(utail) * bf_lo(sc), 0.f));
            asm volatile("barrier.cluster.wait.acquire.aligned;" ::: "memory");
            if (lane < 2) { const uint32_t o = mapa(sb, lane); st_async4(o + M_SC + (8 * h + warp) * 4, (uint32_t)min(max(esum, 1), 254) << 7, o + M_BARS + 8 * B_SC); }
            if (lead) TSTAMP(10);
            bar_sync(3, 256);
        }
        if (lead) { TSTAMP(3); CSTAMP(27); }

        uint32_t M[8][2], Ye[8][2], Yo[8][2];
        {
            uint32_t X[8][2], F[8][2], Bq[2][4];
            uint32_t ua = UB + ((mi & 1) ? 0 : U_PL) + (8 + 8 * (mi >> 1) + r) * 16, ta = TB + 4 * (1 + g + 2 * t);
#pragma unroll
            for (int jp = 0; jp < 4; jp++) ldsm4(ua + 2 * U_PL + jp * 256, X[2 * jp][0], X[2 * jp][1], X[2 * jp + 1][0], X[2 * jp + 1][1]);
            auto group_tables = [&]() {
#pragma unroll
                for (int i = 0; i < 3; i++) sts128(TB + T_R2 + 16 * lane + 512 * i, 0, 0, 0, 0);
                const uint32_t k1024 = __shfl_sync(0xffffffffu, vc[0], 0) & 0xffffu;
                if (lane == 2) vb[0] &= 0xffff0000u;
                if (lane == 0) vc[0] &= 0xffff0000u;
                if (lane == 4) vc[0] = hsub(vc[0], k1024);
                __syncwarp();
                const uint32_t a1 = TB + T_R2 + T2_S * (g & 3) + 8 * (8 * t - 10 + (g >> 2));
                const uint32_t a0 = TB + T_R2 + T2_S * ((g - 1) & 3) + 8 * (8 * t - 10 + ((g - 1) >> 2)) + 4;
#pragma unroll
                for (int i = 0; i < 4; i++) {
                    sts16_if(t >= 2, a0 + 16 * i, vb[i]); sts16_if(t >= 2, a0 + 16 * i + 10, vb[i]);
                    sts16_if(t >= 2, a1 + 16 * i, vb[i] >> 16); sts16_if(t >= 2, a1 + 16 * i + 10, vb[i] >> 16);
                }
                const uint32_t a = TB + T_R3 + T3_S * (((g - 1) >> 1) & 1) + 8 * (7 + 4 * t + ((g - 1) >> 2)) + 4 * ((g - 1) & 1);
#pragma unroll
                for (int i = 0; i < 2; i++) {
                    sts16(a + 16 * i, vc[i]); sts16(a + 16 * i + 10, vc[i]);
                    sts16(a + 16 * i + 128, vc[i] >> 16); sts16(a + 16 * i + 138, vc[i] >> 16);
                }
                const int q = lane >> 1;
                sts16_if(lane < 8, TB + (q == 0 ? T_R2 + 3 * T2_S + 172 : q == 1 ? T_R2 + 176 : q == 2 ? T_R2 + 180 : T_R3 + T3_S + 308) + 10 * (lane & 1), lane < 6 ? k1024 : kl);
            };
            dense_step<true>(M, Ye, Yo, X, F, Bq, ua, ta, UB + (9 + lane) * 16, zr, group_tables);
#pragma unroll 1
            for (int k = 1; k < 8; k++) {
                ua -= 16; ta += 128;
                dense_step<false>(M, Ye, Yo, X, F, Bq, ua, ta, 0, zr, []() {});
            }
#pragma unroll
            for (int J = 0; J < 8; J++) mma_h(Ye[J], Bq[0], F[J][0], F[J][1]);
#pragma unroll
            for (int J = 1; J < 8; J++) mma_h(Ye[J], Bq[1], F[J - 1][0], F[J - 1][1]);
        }
      {
        LANE_VARS;
        if (lead) { TSTAMP(4); CSTAMP(28); }
        __syncwarp();
        mbar_wait(bars + 8 * B_SC);
        const uint32_t idh = (g == 2 * t) ? 0x3C00u : (g == 2 * t + 1) ? 0x3C000000u : 0u;
        const uint32_t sbr = mapa(sb, h ^ 1);
        const uint32_t yl = TB + lane * 16, yr = sbr + (h ? ALT0 : ALT1) + A_YIN + warp * Y_CH + lane * 16;
        auto finish = [&](int J) {
            float m[4], e[4], o[4];
            widen_h(m, M[J], idh); widen_add_h(e, Ye[J], idh, m); widen_add_h(o, Yo[J], idh, m);
            asm volatile("{ .reg .pred p, q;\n\tsetp.eq.u32 p, %8, %9;\n\tsetp.eq.and.u32 q, %10, 0, p;\n\t"
                         "@p st.shared.v4.u32 [%0], {%4,%5,%6,%7};\n\t"
                         "@!p st.async.weak.shared::cluster.mbarrier::complete_tx::bytes.v4.b32 [%1], {%4,%5,%6,%7}, [%3];\n\t"
                         "bar.warp.sync 0xffffffff;\n\t"
                         "@q mbarrier.arrive.shared::cta.b64 _, [%2];\n\t}"
                         :: "r"(yl + (J & 3) * 512), "r"(yr + (J & 3) * 512), "r"(bars + 8 * (B_Y + (J & 3))), "r"(sbr + M_BARS + 8 * (B_Y + (J & 3))),
                            "r"(pack_bf(e[0], e[2])), "r"(pack_bf(o[0], o[2])), "r"(pack_bf(e[1], e[3])), "r"(pack_bf(o[1], o[3])),
                            "r"(h), "r"(J >> 2), "r"(lane) : "memory");
        };
        finish(0); finish(1);
        {
            const uint32_t a1 = UB + (3 - mi) * U_PL + (8 + r) * 16;
            const uint32_t a2 = UB + ((2 - mi) & 3) * U_PL + (8 + r - (mi == 3)) * 16;
            const uint32_t a3 = UB + (mi < 2 ? 2 - mi : 3) * U_PL + (7 + r) * 16;
            const uint32_t bt = sb + OFF_BAND + 4 * (32 + g + 2 * t);
            {
                const uint32_t f7 = lds32(bt + 768 - 36), g7 = lds32(bt + 768 - 4), f9 = lds32(bt + 1024 - 32), g9 = lds32(bt + 1024), h9 = lds32(bt + 1024 + 32);
                const uint32_t f1 = hmul(lds32(bt - 28), lds16(TB + T_R2 + 176) * 0x10001u);
                const uint32_t B7[4] = {zr, f7, f7 ^ zr, g7}, B9a[4] = {zr + zr, f9, f9 ^ zr, g9}, B9b[4] = {g9 ^ zr, h9, h9 ^ zr, zr * 3}, B1[4] = {zr * 5, f1, f1 ^ zr, zr * 7};
                const uint32_t g7b = g7 ^ zr, z7 = zr * 9;
                const uint32_t tq = TB + T_R3 + 8 * (7 + g - 2 * t);
                uint2 Q0[4], Q1[4], Q2[4];
#pragma unroll
                for (int i = 0; i < 4; i++) { Q0[i] = lds64(tq + 64 * i); Q1[i] = lds64(tq + T3_S + 64 * i); Q2[i] = lds64(tq + T3_S - 8 + 64 * i); }
#pragma unroll
                for (int j = 0; j < 4; j++) {
                    uint32_t c3, c2, c1, c0, d2, d1, d0, dm1, em2, em3, em1, ex;
                    ldsm4(a1 + j * 128, c3, c2, c1, c0); ldsm4(a2 + j * 128, d2, d1, d0, dm1); ldsm4(a3 + j * 128, em2, em3, em1, ex);
                    uint32_t WE[4], WO[4];
                    mma_h_z(WE[0], WE[1], B7, c1, c0); mma_h_z(WO[0], WO[1], B7, c3, c2);
                    mma_h_z(WE[2], WE[3], B9a, d0, dm1); mma_h_z(WO[2], WO[3], B9a, d2, d1);
                    mma_h(Ye[j + 4], B1, d0, dm1); mma_h(Yo[j + 4], B1, d2, d1);
                    mma_h_k8(WE[0], WE[1], g7b, z7, em1); mma_h_k8(WO[0], WO[1], g7b, z7, c1);
                    mma_h2(WE[2], WE[3], B9b, em2, em3); mma_h2(WO[2], WO[3], B9b, d0, dm1);
#pragma unroll
                    for (int i = 0; i < 4 - j; i++) { mma_h(Ye[j + 4 + i], WE, Q0[i].x, Q0[i].y); mma_h(Yo[j + 4 + i], WE, Q1[i].x, Q1[i].y); }
#pragma unroll
                    for (int i = 0; i < 4 - j; i++) { mma_h(Ye[j + 4 + i], WO, Q2[i].x, Q2[i].y); mma_h(Yo[j + 4 + i], WO, Q0[i].x, Q0[i].y); }
                }
            }
            {
                const uint32_t B35[4] = {lds32(bt + 256 - 28), lds32(bt + 512 - 40), lds32(bt + 256 + 4), lds32(bt + 512 - 8)};
                const uint32_t tq = TB + T_R2 + 8 * (6 + g - 2 * t);
                uint2 Q[4][3], QS[2][3];
#pragma unroll
                for (int i = 0; i < 3; i++) {
#pragma unroll
                    for (int s = 0; s < 4; s++) Q[s][i] = lds64(tq + T2_S * s + 64 * i);
#pragma unroll
                    for (int s = 0; s < 2; s++) { QS[s][i].x = hadd(Q[s][i].x, Q[s + 2][i].x); QS[s][i].y = hadd(Q[s][i].y, Q[s + 2][i].y); }
                }
#pragma unroll
                for (int j = 0; j < 6; j++) {
                    uint32_t c3, c2, c1, c0, cm1, cm2, cm3, cm4, d2, d1, d0, dm1, em2, em3;
                    ldsm4(a1 + j * 128, c3, c2, c1, c0); ldsm4(a1 + j * 128 - 16, cm1, cm2, cm3, cm4);
                    ldsm4(a2 + j * 128, d2, d1, d0, dm1); ldsm2(a3 + j * 128, em2, em3);
                    uint32_t H[7][2];
                    mma_h_z(H[3][0], H[3][1], B35, d0, dm1); mma_h_z(H[4][0], H[4][1], B35, c1, c0); mma_h_z(H[2][0], H[2][1], B35, cm1, cm2);
                    mma_h_z(H[5][0], H[5][1], B35, d2, d1); mma_h_z(H[6][0], H[6][1], B35, c3, c2);
                    mma_h_z(H[1][0], H[1][1], B35, em2, em3); mma_h_z(H[0][0], H[0][1], B35, cm3, cm4);
                    const int n = j < 4 ? 3 : 6 - j;
#pragma unroll
                    for (int s = 0; s < 2; s++) {
                        const int o = 3 - s;
                        const uint32_t qe[4] = {H[o][0] ^ zr, H[o + 1][0] ^ zr, H[o][1] ^ zr, H[o + 1][1] ^ zr};
                        const uint32_t qg[4] = {hsub(H[o + 2][0], H[o][0]), hsub(H[o + 3][0], H[o + 1][0]), hsub(H[o + 2][1], H[o][1]), hsub(H[o + 3][1], H[o + 1][1])};
                        const uint32_t qf[4] = {hsub(H[o - 2][0], H[o][0]), hsub(H[o - 1][0], H[o + 1][0]), hsub(H[o - 2][1], H[o][1]), hsub(H[o - 1][1], H[o + 1][1])};
#pragma unroll
                        for (int i = 0; i < n; i++) mma_h(M[j + 2 + i], qe, QS[s][i].x, QS[s][i].y);
#pragma unroll
                        for (int i = 0; i < n; i++) mma_h(Yo[j + 2 + i], qg, Q[s][i].x, Q[s][i].y);
#pragma unroll
                        for (int i = 0; i < n; i++) mma_h(Ye[j + 2 + i], qf, Q[s + 2][i].x, Q[s + 2][i].y);
                    }
                    finish(j + 2);
                }
            }
        }
      }
        {
            LANE_VARS;
            if (lead) { TSTAMP(5); CSTAMP(29); }
            bar_sync(2, 384);
            const uint32_t xo = sb + OFF_S + (32 * h + (g >> 2)) * 1024 + warp * 128 + (g & 3) * 32 + (((t >> 1) ^ (warp & 1)) << 4) + ((t & 1) << 3);
            const uint32_t go = sb + OFF_GP + (8 * warp + g) * 64;
            const uint32_t sel = lds16(sb + M_BMAP + (8 * warp + g) * 2);
            const int ch16 = 4 * (r >> 1) + 2 * (mi & 1) + (r & 1);
            const uint32_t ya = sb + (((ch16 >> 3) == h) ? OFF_TAB + (ch16 & 7) * T_CH : (h ? ALT1 : ALT0) + A_YIN + (ch16 & 7) * Y_CH) + (4 * warp + (mi >> 1)) * 16;
            bf16* op = p.out + (size_t)(1024 * h + 8 * g + warp) * D_ + 16 * pr + 4 * t;
            const uint2 dsk = lds64(sb + M_DSK + 8 * t);
            const uint4 s4 = lds128(sb + M_SC + t * 16);
            const uint32_t s01 = __byte_perm(s4.x, s4.y, 0x5410), s23 = __byte_perm(s4.z, s4.w, 0x5410);
#pragma unroll
            for (int J = 0; J < 4; J++) {
                const uint4 g4 = lds128(go + J * 16);
                const uint32_t gp[4] = {g4.x, g4.y, g4.z, g4.w};
                uint2 xd[4], ex[4];
#pragma unroll
                for (int i = 0; i < 4; i++) {
                    const uint2 x = lds64(xo + (4 * J + i) * 2048);
                    const uint32_t og = __byte_perm(gp[i], 0, 0x3232);
                    ex[i].x = hmul2_bf(og, x.x); ex[i].y = hmul2_bf(og, x.y);
                    xd[i].x = hmul2_bf(x.x, dsk.x); xd[i].y = hmul2_bf(x.y, dsk.y);
                }
                mbar_wait(bars + 8 * (B_Y + J));
                if (J == 3 && lead) TSTAMP(6);
#pragma unroll
                for (int q = 0; q < 2; q++) {
                    uint32_t y[4];
                    ldsm4t(ya + J * 512 + q * 32, y[0], y[1], y[2], y[3]);
#pragma unroll
                    for (int hx = 0; hx < 2; hx++) {
                        const int i = 2 * q + hx;
                        const uint32_t gg = __byte_perm(gp[i], 0, 0x1010);
                        uint2 o;
                        o.x = hadd2_bf(hmul2_bf(gg, hfma2_bf(y[2 * hx], s01, xd[i].x)), ex[i].x);
                        o.y = hadd2_bf(hmul2_bf(gg, hfma2_bf(y[2 * hx + 1], s23, xd[i].y)), ex[i].y);
                        if (!((sel >> (4 * J + i)) & 1u)) *(uint2*)(op + (size_t)(64 * (4 * J + i)) * D_) = o;
                    }
                }
            }
            if (lead) { TSTAMP(7); TSDUMP(0x3c000effu); }
        }
    } else if (pw < 4) {
        const int v = pw, at = tid;
        const int g = lane >> 2, t = lane & 3, mi = lane >> 3, r = lane & 7;
        const uint32_t alt = sb + (h ? ALT1 : ALT0);
        cp16(sb + OFF_GP + tid * 16, p.wr + tid * 8);
        cp16(sb + OFF_GP + 2048 + tid * 16, p.gatew + tid * 8);
        if (tid < 2) cp16(sb + M_DSK + tid * 16, p.Dskip + 16 * pr + 8 * tid);
        const unsigned epoch = *(volatile unsigned*)&p.ex->epoch;
        const unsigned tag = (epoch + 1) & 0xffffu;
        const int ftok = 2 * ((at >> 2) & 3) + (at & 1), fch = (at >> 4) + 8 * ((at >> 1) & 1);
        {
            cp_wait_all();
            bar_sync(7, 160);
            if (at == 0) TSTAMP(21);
            const uint32_t wo = sb + OFF_GP + 512 * v + 64 * ((g >> 1) & 1) + 16 * t + 4 * (g & 1);
            uint32_t w0[4], w1[4];
            uint4 gw[4];
#pragma unroll
            for (int cb = 0; cb < 4; cb++) {
                w0[cb] = lds32(wo + 128 * cb); w1[cb] = lds32(wo + 128 * cb + 8);
                gw[cb] = lds128(sb + OFF_GP + 2048 + 512 * v + 128 * cb + 64 * (g & 1) + 16 * t);
            }
            const uint32_t ro = sb + M_RG + (g >> 1) * 32 + (2 * v + (g & 1)) * 4;
            const uint32_t xo = sb + OFF_RING + X_SLOT * 4096 + (g >> 1) * 2048 + 512 * v + 64 * (g & 1) + 16 * t;
            const uint32_t one0 = 0x3F803F80u ^ p.zero, one1 = 0x3F803F80u + p.zero;
            auto row_sum = [&](uint32_t a) {
                const uint4 x = lds128(a), y = lds128(a + 16);
                return ((__uint_as_float(x.x) + __uint_as_float(x.y)) + (__uint_as_float(x.z) + __uint_as_float(x.w)))
                     + ((__uint_as_float(y.x) + __uint_as_float(y.y)) + (__uint_as_float(y.z) + __uint_as_float(y.w)));
            };
#pragma unroll 1
            for (int i = 0; i < 4; i++) {
                mbar_spin(bars + 8 * (B_X + i));
                uint4 x[4];
#pragma unroll
                for (int cb = 0; cb < 4; cb++) x[cb] = lds128(xo + 8192 * i + 128 * cb);
                float d0[4] = {0.f, 0.f, 0.f, 0.f}, d1[4] = {0.f, 0.f, 0.f, 0.f};
#pragma unroll
                for (int cb = 0; cb < 4; cb++) mma_bf((cb & 1) ? d1 : d0, x[cb].x, x[cb].y, x[cb].z, x[cb].w, w0[cb], w1[cb]);
                if (t == (g & 1)) stsf(ro + 128 * i, (d0[0] + d0[3]) + (d1[0] + d1[3]));
                if (i == 3) {
                    bar_sync(4, 256);
                    if (at < 16) {
                        const uint32_t rb = pack_bf(0.f, row_sum(sb + M_RG + at * 32));
                        st_gpu32((uint32_t*)p.ex->r + 16 * c + at, ((rb ^ (((int)rb >> 31) | 0x80000000u)) & 0xffff0000u) | tag);
                    }
                    if (at == 32) mbar_arrive(bars + 8 * B_XF);
                    if (at == 0) TSTAMP(8);
                }
                float e0[4] = {0.f, 0.f, 0.f, 0.f}, e1[4] = {0.f, 0.f, 0.f, 0.f};
#pragma unroll
                for (int cb = 0; cb < 4; cb++)
                    mma_bf((cb & 1) ? e1 : e0, hmul2_bf(x[cb].x, gw[cb].x), hmul2_bf(x[cb].y, gw[cb].y), hmul2_bf(x[cb].z, gw[cb].z), hmul2_bf(x[cb].w, gw[cb].w), one0, one1);
                if (t == 0) stsf(ro + 512 + 128 * i, (e0[0] + e0[3]) + (e1[0] + e1[3]));
            }
            bar_sync(1, 128);
            if (at < 16) st_gpu32((uint32_t*)p.ex->g + 1024 * h + 16 * (8 * (pr & 7) + (pr >> 3)) + at,
                                  (pack_bf(sigmoid_f(bf_round(row_sum(sb + M_RG + 512 + at * 32))), 0.f) & 0xffffu) | (tag << 16));
            if (at == 0) TSTAMP(23);
        }
        {
            uint32_t top = 0;
            bool ok = false;
            mbar_wait(bars + 8 * B_MX);
#pragma unroll 1
            for (int it = 0; it < (1 << 22); it++) {
                uint32_t tg;
                asm volatile("ld.relaxed.gpu.global.v2.u32 {%0,%1}, [%2];" : "=r"(top), "=r"(tg) : "l"(&p.ex->top[lane & 7]) : "memory");
                ok = __all_sync(0xffffffffu, tg == tag);
                if (ok) break;
                __nanosleep(20);
            }
            if (!ok) __trap();
            if (at == 0) TSTAMP(25);
            const int row = 2047 - (int)(top & 0xffffu);
            if (c < NGU_CTA && (lane >> 1) == v) bulk_load(alt + A_XSEL + lane * XS_ROW, p.u + (size_t)row * D_, 2048, bars + 8 * B_XS);
            uint32_t gv[8];
#pragma unroll 1
            for (int it = 0; it < (1 << 22); it++) {
                const uint4 a = ld_gpu128(&p.ex->g[256 * h + at]), b = ld_gpu128(&p.ex->g[256 * h + 128 + at]);
                gv[0] = a.x; gv[1] = a.y; gv[2] = a.z; gv[3] = a.w; gv[4] = b.x; gv[5] = b.y; gv[6] = b.z; gv[7] = b.w;
                uint32_t bad = 0;
#pragma unroll
                for (int i = 0; i < 8; i++) bad |= gv[i] ^ (tag << 16);
                ok = (bad >> 16) == 0;
                if (ok) break;
                __nanosleep(64);
            }
            if (!ok) __trap();
            if (v == 0 && lane < 8) {
                const uint32_t ord = top >> 16;
                const uint32_t rb = (ord & 0x8000u) ? (ord & 0x7fffu) : (~ord & 0xffffu);
                stsf(sb + M_RSEL + lane * 4, bf_round(sigmoid_f(__uint_as_float(rb << 16))));
                sts32(sb + M_IDX + lane * 4, (uint32_t)row);
                if ((row >> 10) == h) asm volatile("red.shared.or.b32 [%0], %1;" :: "r"(sb + M_BMAP + (row & 7) * 16 + ((row >> 4) & 3) * 4),
                                                   "r"(1u << (((row >> 6) & 15) + 2 * (row & 8))) : "memory");
            }
#pragma unroll
            for (int i = 0; i < 8; i++) gv[i] = (gv[i] & 0xffffu) | (pack_bf(1.f - bf_lo(gv[i]), 0.f) << 16);
            sts128(sb + OFF_GP + at * 16, gv[0], gv[1], gv[2], gv[3]);
            sts128(sb + OFF_GP + (at + 128) * 16, gv[4], gv[5], gv[6], gv[7]);
            if (EPI_AT == 0) bar_arrive(2, 384);
        }
        if (c < NGU_CTA) {
            float dgt[4] = {0.f, 0.f, 0.f, 0.f}, dup[4] = {0.f, 0.f, 0.f, 0.f}, dg2[4] = {0.f, 0.f, 0.f, 0.f}, du2[4] = {0.f, 0.f, 0.f, 0.f};
            const int ct = v & 1, kh = v >> 1;
            const int krow0 = 8 * (mi >> 1) + r;
            const uint32_t off0 = krow0 * 64 + (((2 * ct + (mi & 1)) ^ ((krow0 >> 1) & 3)) << 4);
            const uint32_t ta = sb + OFF_RING + kh * 4096 + off0 + p.swap_gu, tb = ta + 2048 - 2 * p.swap_gu;
            const uint32_t wrap = kh ? 10 : 11;
            const uint32_t xo = alt + A_XSEL + r * XS_ROW + 64 * kh + 16 * mi;
            const uint32_t fb = bars + 8 * kh;
            mbar_spin(bars + 8 * B_XS);
            if (at == 0) TSTAMP(12);
#pragma unroll kGuUnroll
            for (int s = 0; s < 16; s++) {
                uint32_t b[4], a[4][4];
                const uint32_t o = s * 8192 - (s > 10 || (s == 10 && (uint32_t)s >= wrap) ? NSLOT * 4096 : 0);
                mbar_wait(fb + 16 * s);
                ldsm4(xo + 128 * s, b[0], b[1], b[2], b[3]);
                ldsm4t(ta + o, a[0][0], a[0][1], a[0][2], a[0][3]);
                ldsm4t(tb + o, a[1][0], a[1][1], a[1][2], a[1][3]);
                ldsm4t(ta + o + 1024, a[2][0], a[2][1], a[2][2], a[2][3]);
                ldsm4t(tb + o + 1024, a[3][0], a[3][1], a[3][2], a[3][3]);
                mma_bf(dgt, a[0][0], a[0][1], a[0][2], a[0][3], b[0], b[1]);
                mma_bf(dup, a[1][0], a[1][1], a[1][2], a[1][3], b[0], b[1]);
                mma_bf(dg2, a[2][0], a[2][1], a[2][2], a[2][3], b[2], b[3]);
                mma_bf(du2, a[3][0], a[3][1], a[3][2], a[3][3], b[2], b[3]);
                if (lane == 0 && s < B_S - B_EMPTY) mbar_arrive(bars + 8 * (B_EMPTY + s));
            }
#pragma unroll
            for (int i = 0; i < 4; i++) { dgt[i] += dg2[i]; dup[i] += du2[i]; }
            if (at == 0) TSTAMP(13);
            bar_sync(1, 128);
            const uint32_t red = alt + A_XSEL;
            sts128(red + ((v ^ 2) * 32 + lane) * 16, __float_as_uint(kh ? dgt[0] : dgt[2]), __float_as_uint(kh ? dgt[1] : dgt[3]),
                   __float_as_uint(kh ? dup[0] : dup[2]), __float_as_uint(kh ? dup[1] : dup[3]));
            bar_sync(1, 128);
            const uint4 oth = lds128(red + at * 16);
#pragma unroll
            for (int i = 0; i < 2; i++) {
                const float gv = bf_round((kh ? dgt[2 + i] : dgt[i]) + __uint_as_float(i ? oth.y : oth.x));
                const float uv = bf_round((kh ? dup[2 + i] : dup[i]) + __uint_as_float(i ? oth.w : oth.z));
                const float sl = bf_round(gv * sigmoid_f(gv));
                uint32_t hv = pack_bf(sl * uv, 0.f) & 0xffffu;
                hv = (hv == 0x8000u) ? 0x8000u : (hv ^ 0x8000u);
                sts16(red + 4096 + (2 * t + i) * 64 + (g >> 1) * 16 + (2 * ct + kh) * 4 + (g & 1) * 2, hv);
            }
            bar_sync(1, 128);
            if (v == 0) st_gpu128(&p.ex->h[32 * c + lane], lds128(red + 4096 + lane * 16));
        }
        else bar_sync(1, 128);
        if (at == 0) TSTAMP(14);
        if (EPI_AT == 1) bar_arrive(2, 384);
        {
            uint4 hq[14];
            {
                const uint4* hsrc = &p.ex->h[(56 * h + 2 * v) * 32 + lane];
                bool ok = false;
                {
                    const int bi = lane < 14 ? lane : 0;
                    const uint4* pr1 = &p.ex->h[(56 * h + 2 * v + 8 * (bi >> 1) + (bi & 1)) * 32 + 31];
#pragma unroll 1
                    for (int it = 0; it < (1 << 22); it++) {
                        uint32_t w;
                        asm volatile("ld.relaxed.gpu.global.u32 %0, [%1];" : "=r"(w) : "l"(pr1) : "memory");
                        if (__all_sync(0xffffffffu, w != 0)) break;
                        __nanosleep(PSLEEP);
                    }
                }
                if (at == 0) TSTAMP(15);
                if (EPI_AT == 2) bar_arrive(2, 384);
#pragma unroll 1
                for (int it = 0; it < (1 << 22); it++) {
                    uint32_t mn = 0xffffffffu;
#pragma unroll
                    for (int i = 0; i < 14; i++) hq[i] = ld_gpu128(hsrc + (8 * (i >> 1) + (i & 1)) * 32);
#pragma unroll
                    for (int i = 0; i < 14; i++) mn = min(mn, hq[i].x);
                    ok = __all_sync(0xffffffffu, mn != 0);
                    if (ok) break;
                    __nanosleep(20);
                }
                if (!ok) __trap();
            }
            if (at == 0) TSTAMP(16);
            if (EPI_AT == 3) bar_arrive(2, 384);
            float dd[4] = {0.f, 0.f, 0.f, 0.f}, de[4] = {0.f, 0.f, 0.f, 0.f};
            const int krow0 = 64 * (v & 1) + 8 * (mi >> 1) + r;
            const uint32_t ta = sb + OFF_RING + (v >> 1) * 4096 + krow0 * 32 + (((mi & 1) ^ ((krow0 >> 2) & 1)) << 4);
            static_assert((NST_GU + 10) % NSLOT == 0, "stage pairs of the down projection do not straddle the end of the ring");
#pragma unroll
            for (int s = 0; s < 7; s++) {
                mbar_wait(bars + 8 * (B_FULL + NST_GU + 2 * s) + 8 * (v >> 1));
                const uint32_t tile = ta + ((NST_GU + 2 * s) % NSLOT) * 4096;
                uint32_t a[4][4];
#pragma unroll
                for (int j = 0; j < 4; j++) ldsm4t(tile + j * 512, a[j][0], a[j][1], a[j][2], a[j][3]);
                mma_bf(dd, a[0][0], a[0][1], a[0][2], a[0][3], hq[2 * s].x, hq[2 * s].y);
                mma_bf(de, a[1][0], a[1][1], a[1][2], a[1][3], hq[2 * s].z, hq[2 * s].w);
                mma_bf(dd, a[2][0], a[2][1], a[2][2], a[2][3], hq[2 * s + 1].x, hq[2 * s + 1].y);
                mma_bf(de, a[3][0], a[3][1], a[3][2], a[3][3], hq[2 * s + 1].z, hq[2 * s + 1].w);
            }
            if (at == 0) TSTAMP(17);
            mbar_wait(bars + 8 * B_SC);
#pragma unroll
            for (int k = 0; k < 2; k++) {
                const uint32_t o = mapa(sb, k);
                st_async16(o + (k ? ALT1 : ALT0) + A_DP + (128 * h + at) * 16, __float_as_uint(dd[0] + de[0]), __float_as_uint(dd[1] + de[1]),
                           __float_as_uint(dd[2] + de[2]), __float_as_uint(dd[3] + de[3]), o + M_BARS + 8 * B_DP);
            }
            const int row = (int)lds32(sb + M_IDX + ftok * 4);
            const int w = row & 7, jj = (row >> 3) & 7, i = (row >> 6) & 15;
            const float xv = bf_lo(lds16(sb + OFF_S + (row >> 5) * 1024 + w * 128 + (jj & 3) * 32 + (((fch >> 3) ^ (w & 1)) << 4) + (fch & 7) * 2));
            const uint32_t gp = lds32(sb + OFF_GP + (8 * w + jj) * 64 + i * 4);
            const float rs = ldsf(sb + M_RSEL + ftok * 4);
#pragma unroll
            for (int J = 0; J < 4; J++) mbar_wait(bars + 8 * (B_Y + J));
            const float yv = bf_lo(lds16((((fch >> 3) == h) ? sb + OFF_TAB + (fch & 7) * T_CH : alt + A_YIN + (fch & 7) * Y_CH) + (i >> 2) * 512 + (4 * w + (i & 3)) * 16 + jj * 2));
            const float a = bf_round(fmaf(yv, bf_lo(lds32(sb + M_SC + fch * 4)), bf_round(xv * bf_lo(lds16(sb + M_DSK + 2 * fch)))));
            const float ga = bf_round(bf_lo(gp) * a);
            mbar_spin(bars + 8 * B_DP);
            float tot = 0.f;
#pragma unroll
            for (int k = 0; k < 8; k++) tot -= ldsf(alt + A_DP + k * 512 + at * 4);
            if ((row >> 10) == h) {
                const float b = bf_round(xv + bf_round(bf_round(tot) * rs));
                p.out[(size_t)row * D_ + 16 * pr + fch] = __float2bfloat16_rn(ga + bf_round(bf_hi(gp) * b));
            }
        }
        if (at == 0) { TSTAMP(18); TSDUMP(c < NGU_CTA ? 0x02a7f100u : 0x02a7c100u); if (c == 0) *(volatile unsigned*)&p.ex->epoch = epoch + 1; }
    } else {
        asm volatile("setmaxnreg.dec.sync.aligned.u32 " HELP_REGS ";");
        if (pw != 12) {
            if (pw >= 14) {
#pragma unroll
                for (int k = 0; k < 5; k++) {
                    const int w = 1 + 2 * k, e = (tid & 63) - 32;
                    sts32(sb + OFF_BAND + k * 256 + (tid & 63) * 4, ((e >= 0 && e < w) ? 0x3C00u : 0u) | ((e + 1 >= 0 && e + 1 < w) ? 0x3C000000u : 0u));
                }
                if (tid < 14 * 32 + 24) sts128(sb + OFF_S - 384 + lane * 16, 0, 0, 0, 0);
            } else {
                sts32(sb + M_BMAP + lane * 4, 0);
                if (c < NGU_CTA) {
                    st_gpu128(&p.ex->h[32 * c + lane], make_uint4(0, 0, 0, 0));
                    if (ld_gpu128(&p.ex->h[32 * c + lane]).x != 0) __trap();
                }
            }
            bar_arrive(5, 384);
        } else {
            if (lane == 0) {
#pragma unroll
                for (int k = B_S; k < NBAR; k++) mbar_init(bars + 8 * k, (k >= B_Y && k < B_MX) ? 9 : k == B_MX ? 8 : 1);
#pragma unroll
                for (int k = B_S; k < B_XS; k++) mbar_expect(bars + 8 * k, 16384);
                asm volatile("fence.proxy.async.shared::cta;" ::: "memory");
                asm volatile("fence.mbarrier_init.release.cluster;" ::: "memory");
            }
            __syncwarp();
            asm volatile("barrier.cluster.arrive.relaxed.aligned;" ::: "memory");
            auto rows = [&](int i) {
                mbar_expect(bars + 8 * (B_X + i), 8192);
                tma4d(sb + OFF_RING + X_SLOT * 4096 + i * 8192, &tm_r, 0, 0, 16 * h + 4 * i, pr, bars + 8 * (B_X + i));
            };
            if (lane == 0) {
                asm volatile("prefetch.tensormap [%0];" :: "l"(&tm_x) : "memory");
#pragma unroll 1
                for (int i = 0; i < X_LEAD; i++) rows(i);
            }
            __syncwarp();
            bar_arrive(5, 384);
            bar_arrive(7, 160);
            asm volatile("barrier.cluster.wait.acquire.aligned;" ::: "memory");
            if (lane == 0) {
                TSTAMP(20);
#pragma unroll 1
                for (int i = 0; i < 4; i++) {
                    tma4d_both(sb + OFF_S + (4 * h + i) * 8192, &tm_x, 16 * pr, 0, 0, 32 * h + 8 * i, bars + 8 * (B_S + i));
                    if (i + X_LEAD < 4) rows(i + X_LEAD);
                }
                TSTAMP(24);
                asm volatile("prefetch.tensormap [%0];" :: "l"(&tm_gu) : "memory");
                asm volatile("prefetch.tensormap [%0];" :: "l"(&tm_down) : "memory");
#pragma unroll
                for (int k = 0; k < B_S; k++) mbar_init(bars + 8 * k, k < B_EMPTY ? 1 : 4);
#pragma unroll
                for (int k = B_XS; k < B_MX; k++) mbar_expect(bars + 8 * k, k == B_XS ? 16384 : k == B_SC ? 64 : 4096);
                asm volatile("fence.proxy.async.shared::cta;" ::: "memory");
            }
            __syncwarp();
        }
        bar_arrive(4, 256);
        bar_sync(6, 128);
        if (lane != 0) return;
        const int s0 = c < NGU_CTA ? 0 : NST_GU;
        mbar_wait(bars + 8 * (B_S + W_START));
        if (pw == 12) TSTAMP(22);
#pragma unroll 1
        for (int s = s0 + pw - 12; s < NST; s += 4) {
            const uint32_t full = bars + 8 * (B_FULL + s), dst = sb + OFF_RING + (s < NSLOT ? s : s < 2 * NSLOT ? s - NSLOT : s - 2 * NSLOT) * 4096;
            if (s >= X_SLOT) mbar_wait(bars + 8 * ((s >= s0 + NSLOT) ? B_EMPTY + ((s - NSLOT) >> 1) : B_XF));
            mbar_expect(full, 4096);
            if (s < NST_GU) {
                if (s >= DEPTH) mbar_spin(full - 8 * DEPTH);
                tma3d(dst, &tm_gu, 32 * c, 32 * s, 0, full);
            } else {
                if (s >= s0 + DEPTH_D) mbar_spin(full - 8 * DEPTH_D);
                tma2d(dst, &tm_down, 16 * pr, 1792 * h + 128 * (s - NST_GU), full);
            }
        }
        if (pw == 12) { TSTAMP(19); TSDUMP(0x01580000u); }
    }
}

typedef CUresult (*EncodeFn)(CUtensorMap*, CUtensorMapDataType, cuuint32_t, void*, const cuuint64_t*, const cuuint64_t*,
                             const cuuint32_t*, const cuuint32_t*, CUtensorMapInterleave, CUtensorMapSwizzle,
                             CUtensorMapL2promotion, CUtensorMapFloatOOBfill);

void make_map(EncodeFn f, CUtensorMap* m, const void* ptr, int rank, const cuuint64_t* dims, const cuuint64_t* strides, const cuuint32_t* box, CUtensorMapSwizzle sw) {
    const cuuint32_t es[4] = {1, 1, 1, 1};
    f(m, CU_TENSOR_MAP_DATA_TYPE_BFLOAT16, rank, (void*)ptr, dims, strides, box, es, CU_TENSOR_MAP_INTERLEAVE_NONE, sw,
      CU_TENSOR_MAP_L2_PROMOTION_L2_128B, CU_TENSOR_MAP_FLOAT_OOB_FILL_NONE);
}

}

extern "C" void kernel_launch(void* const* d_in, const int* in_sizes, int n_in, void* d_out, int out_size) {
    static EncodeFn enc = nullptr;
    static void* ex = nullptr;
    if (!enc) {
        void* fn = nullptr;
        cudaDriverEntryPointQueryResult qr;
        cudaGetDriverEntryPoint("cuTensorMapEncodeTiled", &fn, cudaEnableDefault, &qr);
        enc = (EncodeFn)fn;
        cudaFuncSetAttribute(fused_kernel, cudaFuncAttributeMaxDynamicSharedMemorySize, SMEM_LAUNCH);
        cudaGetSymbolAddress(&ex, g_ex);
    }
    CUtensorMap tgu, td, tx, tr;
    const char *wg = (const char*)d_in[9], *wu = (const char*)d_in[10];
    const bool swap = wu < wg;
    {
        const cuuint64_t dims[3] = {F_, D_, 2}, str[2] = {F_ * 2, (cuuint64_t)(swap ? wg - wu : wu - wg)};
        const cuuint32_t box[3] = {32, 32, 2};
        make_map(enc, &tgu, swap ? wu : wg, 3, dims, str, box, CU_TENSOR_MAP_SWIZZLE_64B);
    }
    {
        const cuuint64_t dims[2] = {D_, F_}, str[1] = {D_ * 2};
        const cuuint32_t box[2] = {16, 128};
        make_map(enc, &td, d_in[11], 2, dims, str, box, CU_TENSOR_MAP_SWIZZLE_32B);
    }
    {
        const cuuint64_t dims[4] = {D_, 4, 8, L_ / 32}, str[3] = {D_ * 2 * 8, D_ * 2, D_ * 2 * 32};
        const cuuint32_t box[4] = {16, 4, 8, 8};
        make_map(enc, &tx, d_in[0], 4, dims, str, box, CU_TENSOR_MAP_SWIZZLE_32B);
    }
    {
        const cuuint64_t dims[4] = {256, 4, L_ / 64, 64}, str[3] = {512, D_ * 2 * 64, D_ * 2};
        const cuuint32_t box[4] = {256, 4, 4, 1};
        make_map(enc, &tr, d_in[0], 4, dims, str, box, CU_TENSOR_MAP_SWIZZLE_NONE);
    }
    Params p;
    p.u = (const bf16*)d_in[0]; p.logA = (const bf16*)d_in[1]; p.Aim = (const bf16*)d_in[2];
    p.Cre = (const bf16*)d_in[3]; p.Cim = (const bf16*)d_in[4]; p.logdt = (const bf16*)d_in[5];
    p.Dskip = (const bf16*)d_in[6]; p.wr = (const bf16*)d_in[8]; p.gatew = (const bf16*)d_in[12];
    p.out = (bf16*)d_out;
    p.ex = (Exchange*)ex;
    p.zero = 0;
    p.swap_gu = swap ? 2048 : 0;
    fused_kernel<<<NCTA, NTHREADS, SMEM_LAUNCH>>>(p, tgu, td, tx, tr);
}
```

```cpp
#include <cuda_runtime.h>
#include <cuda_bf16.h>
#include <cuda_fp16.h>
#include <cuda.h>
#include <stdint.h>

typedef __nv_bfloat16 bf16;

namespace {

constexpr int L_ = 2048, D_ = 1024, F_ = 3584;
constexpr int NCTA = 130;
constexpr int NTHREADS = 512;
constexpr int MAIN_W0 = 4;
#define DEPTH 10
#define DEPTH_D 5
#define W_START 1
#define PSLEEP 40
#define GU_UNROLL 16
#define KS_UNROLL 4
#define START_MODE 0
#define X_DELAY 0
#define LDX_HINT ""
#define X_BATCH 16
#define EPI_AT 2
#define X_LEAD 1
#define GU_PRE 6
#define GU_BATCH 0
#define DN_PRE 5
#define DEPTH_E DEPTH
#define EARLY 20
#define NPOLL 1
#define X_MODE 0
#define WARM_TLB 0
#define T_W 1600
#define DT_G 158
#define DT_D 172
#define FENCES 16
#define XS_MODE 0
#define REMAP 1
#define PROMO_D CU_TENSOR_MAP_L2_PROMOTION_L2_128B
#define PUB_ATOM 0
#define KEEP_LIVE 0
#define MAIN_REGS "176"
#define HELP_REGS "24"
constexpr int kGuUnroll = GU_UNROLL, kKsUnroll = KS_UNROLL;
constexpr int NGU_CTA = 112;

constexpr int NSLOT    = 21;
constexpr int NST_GU   = 32, NST = 46;
constexpr int OFF_RING = 0;
constexpr int OFF_XSEL = 69632, XS_ROW = 2064;
constexpr int OFF_DP   = OFF_XSEL + 8192;
constexpr int OFF_S    = 87040;
constexpr int ALT0     = OFF_S + 32768, ALT1 = OFF_S - 512;
constexpr int A_YIN    = 32, Y_CH = 2064;
constexpr int A_SLOT   = 16896, ALT_SLOT = 17;
constexpr int U_PL     = 1184;
constexpr int U_CH     = 4752;
constexpr int OFF_U    = 153088;
constexpr int T_CH     = 4112;
constexpr int OFF_TAB  = 191104;
constexpr int T_R2     = 2176, T2_S = 208;
constexpr int T_R3     = 3040, T3_S = 336;
constexpr int OFF_GP   = 224000;
constexpr int OFF_BAND = 228096;
constexpr int OFF_MISC = 229376;
constexpr int M_BARS   = OFF_MISC;
constexpr int M_DSK    = OFF_MISC + 672;
constexpr int M_IDX    = OFF_MISC + 704;
constexpr int M_RSEL   = OFF_MISC + 736;
constexpr int M_BMAP   = OFF_MISC + 768;
constexpr int M_MX     = OFF_MISC + 896;
constexpr int M_SC     = OFF_MISC + 960;
constexpr int M_RG     = OFF_MISC + 1024;
constexpr int SMEM_BYTES = OFF_MISC + 2048;
constexpr int SMEM_LAUNCH = SMEM_BYTES;

constexpr int B_FULL = 0, B_EMPTY = NST, B_S = B_EMPTY + (NST - NSLOT + 1) / 2, B_XS = B_S + 4, B_TD = B_XS + 2, B_SC = B_TD + 1, B_DP = B_SC + 1, B_Y = B_DP + 1, B_MX = B_Y + 4,
              B_TS = B_MX + 1, B_XF = B_TS + 1, B_X = B_XF + 1, NBAR = B_X + 4;
constexpr int X_SLOT = 13;
static_assert(NBAR <= 84, "barrier area");

struct Exchange {
    unsigned epoch, pad[31];
    uint4 h[8 * F_ / 8];
    uint4 r[L_ / 4];
    uint4 g[L_ / 4];
    uint2 top[16];
};
__device__ __align__(128) Exchange g_ex;

struct Params {
    const bf16 *u, *logA, *Aim, *Cre, *Cim, *logdt, *Dskip, *wr, *gatew;
    bf16* out;
    Exchange* ex;
    uint32_t zero;
    uint32_t swap_gu;
};

#define TSTAMP(i) do {} while (0)
#define CSTAMP(i) do {} while (0)
#define TSDUMP(mask) do {} while (0)
#define DBG_PARAMS
#define DBG_ARGS

__device__ __forceinline__ uint32_t smem_u32(const void* p) { return (uint32_t)__cvta_generic_to_shared(p); }
__device__ __forceinline__ void mbar_init(uint32_t b, uint32_t c) { asm volatile("mbarrier.init.shared::cta.b64 [%0], %1;" :: "r"(b), "r"(c) : "memory"); }
__device__ __forceinline__ void mbar_expect(uint32_t b, uint32_t tx) { asm volatile("mbarrier.arrive.expect_tx.shared::cta.b64 _, [%0], %1;" :: "r"(b), "r"(tx) : "memory"); }
__device__ __forceinline__ void mbar_arrive(uint32_t b) { asm volatile("mbarrier.arrive.shared::cta.b64 _, [%0];" :: "r"(b) : "memory"); }
#define WSLEEP "40"
__device__ __forceinline__ void mbar_wait(uint32_t b) {
    asm volatile("{\n\t.reg .pred p, q;\n\t.reg .u32 n;\n\tmov.u32 n, 0;\n"
                 "W%=:\n\tmbarrier.try_wait.parity.shared::cta.b64 p, [%0], 0;\n\t"
                 "@p bra D%=;\n\tnanosleep.u32 " WSLEEP ";\n\tadd.u32 n, n, 1;\n\tsetp.lt.u32 q, n, 4194304;\n\t@q bra W%=;\n"
                 "D%=:\n\t}" :: "r"(b) : "memory");
}
__device__ __forceinline__ void mbar_spin(uint32_t b) {
    asm volatile("{\n\t.reg .pred p, q;\n\t.reg .u32 n;\n\tmov.u32 n, 0;\n"
                 "W%=:\n\tmbarrier.try_wait.parity.shared::cta.b64 p, [%0], 0;\n\t"
                 "@p bra D%=;\n\tadd.u32 n, n, 1;\n\tsetp.lt.u32 q, n, 4194304;\n\t@q bra W%=;\n"
                 "D%=:\n\t}" :: "r"(b) : "memory");
}
template <int N, int STEP>
__device__ __forceinline__ void mbar_wait_n(uint32_t b) {
#pragma unroll 1
    for (int n = 0; n < 4194304; n++) {
        uint32_t ok = 1;
#pragma unroll
        for (int i = 0; i < N; i++) {
            uint32_t d;
            asm volatile("{ .reg .pred p; mbarrier.try_wait.parity.shared::cta.b64 p, [%1], 0; selp.u32 %0, 1, 0, p; }" : "=r"(d) : "r"(b + STEP * i) : "memory");
            ok &= d;
        }
        if (ok) break;
    }
}
__device__ __forceinline__ unsigned ld_epoch(const Exchange* e) { unsigned v; asm volatile("ld.volatile.global.u32 %0, [%1];" : "=r"(v) : "l"(e) : "memory"); return v; }
__device__ __forceinline__ uint32_t now_ns() { uint32_t t; asm volatile("mov.u32 %0, %globaltimer_lo;" : "=r"(t)); return t; }
__device__ __forceinline__ uint32_t mapa(uint32_t addr, uint32_t rank) { uint32_t r; asm("mapa.shared::cluster.u32 %0, %1, %2;" : "=r"(r) : "r"(addr), "r"(rank)); return r; }
__device__ __forceinline__ void bulk_load(uint32_t dst, const void* src, uint32_t bytes, uint32_t bar) {
    asm volatile("cp.async.bulk.shared::cluster.global.mbarrier::complete_tx::bytes [%0], [%1], %2, [%3];" :: "r"(dst), "l"(src), "r"(bytes), "r"(bar) : "memory");
}
__device__ __forceinline__ void bulk_load_both(uint32_t dst, const void* src, uint32_t bytes, uint32_t bar) {
    asm volatile("{ .reg .pred p; elect.sync _|p, 0xffffffff;\n\t@p cp.async.bulk.shared::cluster.global.mbarrier::complete_tx::bytes.multicast::cluster [%0], [%1], %2, [%3], %4; }"
                 :: "r"(dst), "l"(src), "r"(bytes), "r"(bar), "h"((unsigned short)3) : "memory");
}
__device__ __forceinline__ void tma2d(uint32_t dst, const CUtensorMap* tm, int c0, int c1, uint32_t bar) {
    asm volatile("cp.async.bulk.tensor.2d.shared::cluster.global.mbarrier::complete_tx::bytes [%0], [%1, {%3, %4}], [%2];"
        :: "r"(dst), "l"(tm), "r"(bar), "r"(c0), "r"(c1) : "memory");
}
__device__ __forceinline__ void tma3d(uint32_t dst, const CUtensorMap* tm, int c0, int c1, int c2, uint32_t bar) {
    asm volatile("cp.async.bulk.tensor.3d.shared::cluster.global.mbarrier::complete_tx::bytes [%0], [%1, {%3, %4, %5}], [%2];"
        :: "r"(dst), "l"(tm), "r"(bar), "r"(c0), "r"(c1), "r"(c2) : "memory");
}
__device__ __forceinline__ void tma4d(uint32_t dst, const CUtensorMap* tm, int c0, int c1, int c2, int c3, uint32_t bar) {
    asm volatile("cp.async.bulk.tensor.4d.shared::cluster.global.mbarrier::complete_tx::bytes [%0], [%1, {%3, %4, %5, %6}], [%2];"
        :: "r"(dst), "l"(tm), "r"(bar), "r"(c0), "r"(c1), "r"(c2), "r"(c3) : "memory");
}
__device__ __forceinline__ void tma4d_both(uint32_t dst, const CUtensorMap* tm, int c0, int c1, int c2, int c3, uint32_t bar) {
    asm volatile("cp.async.bulk.tensor.4d.shared::cluster.global.mbarrier::complete_tx::bytes.multicast::cluster [%0], [%1, {%3, %4, %5, %6}], [%2], %7;"
        :: "r"(dst), "l"(tm), "r"(bar), "r"(c0), "r"(c1), "r"(c2), "r"(c3), "h"((unsigned short)3) : "memory");
}
__device__ __forceinline__ void st_async16(uint32_t dst, uint32_t x, uint32_t y, uint32_t z, uint32_t w, uint32_t bar) {
    asm volatile("st.async.weak.shared::cluster.mbarrier::complete_tx::bytes.v4.b32 [%0], {%1,%2,%3,%4}, [%5];"
                 :: "r"(dst), "r"(x), "r"(y), "r"(z), "r"(w), "r"(bar) : "memory");
}
__device__ __forceinline__ void st_async4(uint32_t dst, uint32_t v, uint32_t bar) {
    asm volatile("st.async.weak.shared::cluster.mbarrier::complete_tx::bytes.b32 [%0], %1, [%2];" :: "r"(dst), "r"(v), "r"(bar) : "memory");
}
__device__ __forceinline__ void bar_sync(int id, int n) { asm volatile("bar.sync %0, %1;" :: "r"(id), "r"(n) : "memory"); }
__device__ __forceinline__ void bar_arrive(int id, int n) { asm volatile("bar.arrive %0, %1;" :: "r"(id), "r"(n) : "memory"); }
__device__ __forceinline__ void cp16(uint32_t dst, const void* src) { asm volatile("cp.async.cg.shared.global [%0], [%1], 16;" :: "r"(dst), "l"(src) : "memory"); }
__device__ __forceinline__ void cp_wait_all() { asm volatile("cp.async.wait_all;" ::: "memory"); }
__device__ __forceinline__ uint32_t ldg16(const void* p) { uint32_t v; asm volatile("ld.global.nc.u16 %0, [%1];" : "=r"(v) : "l"(p)); return v; }
__device__ __forceinline__ uint2 ldg64(const void* p) { uint2 v; asm volatile("ld.global.nc.v2.u32 {%0,%1}, [%2];" : "=r"(v.x), "=r"(v.y) : "l"(p)); return v; }
__device__ __forceinline__ uint4 ldg128(const void* p) { uint4 v; asm volatile("ld.global.nc" LDX_HINT ".v4.u32 {%0,%1,%2,%3}, [%4];" : "=r"(v.x), "=r"(v.y), "=r"(v.z), "=r"(v.w) : "l"(p)); return v; }
__device__ __forceinline__ uint4 ld_gpu128(const void* p) { uint4 v; asm volatile("ld.relaxed.gpu.global.v4.u32 {%0,%1,%2,%3}, [%4];" : "=r"(v.x), "=r"(v.y), "=r"(v.z), "=r"(v.w) : "l"(p) : "memory"); return v; }
__device__ __forceinline__ void st_gpu32(void* p, uint32_t v) { asm volatile("st.relaxed.gpu.global.u32 [%0], %1;" :: "l"(p), "r"(v) : "memory"); }
__device__ __forceinline__ void st_gpu128(void* p, const uint4& v) { asm volatile("st.relaxed.gpu.global.v4.u32 [%0], {%1,%2,%3,%4};" :: "l"(p), "r"(v.x), "r"(v.y), "r"(v.z), "r"(v.w) : "memory"); }

__device__ __forceinline__ void ldsm4(uint32_t a, uint32_t& r0, uint32_t& r1, uint32_t& r2, uint32_t& r3) {
    asm volatile("ldmatrix.sync.aligned.m8n8.x4.shared.b16 {%0,%1,%2,%3}, [%4];" : "=r"(r0), "=r"(r1), "=r"(r2), "=r"(r3) : "r"(a) : "memory");
}
__device__ __forceinline__ void ldsm2(uint32_t a, uint32_t& r0, uint32_t& r1) {
    asm volatile("ldmatrix.sync.aligned.m8n8.x2.shared.b16 {%0,%1}, [%2];" : "=r"(r0), "=r"(r1) : "r"(a) : "memory");
}
__device__ __forceinline__ void ldsm4t(uint32_t a, uint32_t& r0, uint32_t& r1, uint32_t& r2, uint32_t& r3) {
    asm volatile("ldmatrix.sync.aligned.m8n8.x4.trans.shared.b16 {%0,%1,%2,%3}, [%4];" : "=r"(r0), "=r"(r1), "=r"(r2), "=r"(r3) : "r"(a) : "memory");
}
__device__ __forceinline__ uint32_t lds16(uint32_t a) { uint32_t v; asm volatile("ld.shared.u16 %0, [%1];" : "=r"(v) : "r"(a) : "memory"); return v; }
__device__ __forceinline__ uint32_t lds32(uint32_t a) { uint32_t v; asm volatile("ld.shared.u32 %0, [%1];" : "=r"(v) : "r"(a) : "memory"); return v; }
__device__ __forceinline__ uint2 lds64(uint32_t a) { uint2 v; asm volatile("ld.shared.v2.u32 {%0,%1}, [%2];" : "=r"(v.x), "=r"(v.y) : "r"(a) : "memory"); return v; }
__device__ __forceinline__ uint4 lds128(uint32_t a) { uint4 v; asm volatile("ld.shared.v4.u32 {%0,%1,%2,%3}, [%4];" : "=r"(v.x), "=r"(v.y), "=r"(v.z), "=r"(v.w) : "r"(a) : "memory"); return v; }
__device__ __forceinline__ void sts16(uint32_t a, uint32_t v) { asm volatile("st.shared.u16 [%0], %1;" :: "r"(a), "r"(v) : "memory"); }
__device__ __forceinline__ void sts32(uint32_t a, uint32_t v) { asm volatile("st.shared.u32 [%0], %1;" :: "r"(a), "r"(v) : "memory"); }
__device__ __forceinline__ void sts64(uint32_t a, uint32_t x, uint32_t y) { asm volatile("st.shared.v2.u32 [%0], {%1,%2};" :: "r"(a), "r"(x), "r"(y) : "memory"); }
__device__ __forceinline__ void sts128(uint32_t a, uint32_t x, uint32_t y, uint32_t z, uint32_t w) { asm volatile("st.shared.v4.u32 [%0], {%1,%2,%3,%4};" :: "r"(a), "r"(x), "r"(y), "r"(z), "r"(w) : "memory"); }
__device__ __forceinline__ void sts16_if(bool p, uint32_t a, uint32_t v) { asm volatile("{ .reg .pred q; setp.ne.u32 q, %2, 0; @q st.shared.u16 [%0], %1; }" :: "r"(a), "h"((unsigned short)v), "r"((uint32_t)p) : "memory"); }
__device__ __forceinline__ void sts128_if(bool p, uint32_t a, uint32_t x, uint32_t y, uint32_t z, uint32_t w) {
    asm volatile("{ .reg .pred q; setp.ne.u32 q, %5, 0; @q st.shared.v4.u32 [%0], {%1,%2,%3,%4}; }" :: "r"(a), "r"(x), "r"(y), "r"(z), "r"(w), "r"((uint32_t)p) : "memory");
}
__device__ __forceinline__ void stsf(uint32_t a, float v) { asm volatile("st.shared.f32 [%0], %1;" :: "r"(a), "f"(v) : "memory"); }
__device__ __forceinline__ float ldsf(uint32_t a) { float v; asm volatile("ld.shared.f32 %0, [%1];" : "=f"(v) : "r"(a) : "memory"); return v; }

__device__ __forceinline__ void mma_bf(float (&d)[4], uint32_t a0, uint32_t a1, uint32_t a2, uint32_t a3, uint32_t b0, uint32_t b1) {
    asm volatile("mma.sync.aligned.m16n8k16.row.col.f32.bf16.bf16.f32 {%0,%1,%2,%3}, {%4,%5,%6,%7}, {%8,%9}, {%0,%1,%2,%3};"
        : "+f"(d[0]), "+f"(d[1]), "+f"(d[2]), "+f"(d[3]) : "r"(a0), "r"(a1), "r"(a2), "r"(a3), "r"(b0), "r"(b1));
}
__device__ __forceinline__ void widen_bf(float (&d)[4], uint32_t a0, uint32_t a1, uint32_t b) {
    asm volatile("mma.sync.aligned.m16n8k8.row.col.f32.bf16.bf16.f32 {%0,%1,%2,%3}, {%4,%5}, {%6}, {%7,%7,%7,%7};"
        : "=f"(d[0]), "=f"(d[1]), "=f"(d[2]), "=f"(d[3]) : "r"(a0), "r"(a1), "r"(b), "f"(0.f));
}
__device__ __forceinline__ void widen_h(float (&d)[4], const uint32_t (&a)[2], uint32_t b) {
    asm volatile("mma.sync.aligned.m16n8k8.row.col.f32.f16.f16.f32 {%0,%1,%2,%3}, {%4,%5}, {%6}, {%7,%7,%7,%7};"
        : "=f"(d[0]), "=f"(d[1]), "=f"(d[2]), "=f"(d[3]) : "r"(a[0]), "r"(a[1]), "r"(b), "f"(0.f));
}
__device__ __forceinline__ void widen_add_h(float (&d)[4], const uint32_t (&a)[2], uint32_t b, const float (&c)[4]) {
    asm volatile("mma.sync.aligned.m16n8k8.row.col.f32.f16.f16.f32 {%0,%1,%2,%3}, {%4,%5}, {%6}, {%7,%8,%9,%10};"
        : "=f"(d[0]), "=f"(d[1]), "=f"(d[2]), "=f"(d[3]) : "r"(a[0]), "r"(a[1]), "r"(b), "f"(c[0]), "f"(c[1]), "f"(c[2]), "f"(c[3]));
}
__device__ __forceinline__ void mma_h(uint32_t (&d)[2], const uint32_t (&a)[4], uint32_t b0, uint32_t b1) {
    asm volatile("mma.sync.aligned.m16n8k16.row.col.f16.f16.f16.f16 {%0,%1}, {%2,%3,%4,%5}, {%6,%7}, {%0,%1};"
        : "+r"(d[0]), "+r"(d[1]) : "r"(a[0]), "r"(a[1]), "r"(a[2]), "r"(a[3]), "r"(b0), "r"(b1));
}
__device__ __forceinline__ void mma_h_z(uint32_t& d0, uint32_t& d1, const uint32_t (&a)[4], uint32_t b0, uint32_t b1) {
    asm volatile("mma.sync.aligned.m16n8k16.row.col.f16.f16.f16.f16 {%0,%1}, {%2,%3,%4,%5}, {%6,%7}, {%8,%8};"
        : "=r"(d0), "=r"(d1) : "r"(a[0]), "r"(a[1]), "r"(a[2]), "r"(a[3]), "r"(b0), "r"(b1), "r"(0u));
}
__device__ __forceinline__ void mma_h2(uint32_t& d0, uint32_t& d1, const uint32_t (&a)[4], uint32_t b0, uint32_t b1) {
    asm volatile("mma.sync.aligned.m16n8k16.row.col.f16.f16.f16.f16 {%0,%1}, {%2,%3,%4,%5}, {%6,%7}, {%0,%1};"
        : "+r"(d0), "+r"(d1) : "r"(a[0]), "r"(a[1]), "r"(a[2]), "r"(a[3]), "r"(b0), "r"(b1));
}
__device__ __forceinline__ void mma_h_k8(uint32_t& d0, uint32_t& d1, uint32_t a0, uint32_t a1, uint32_t b) {
    asm volatile("mma.sync.aligned.m16n8k8.row.col.f16.f16.f16.f16 {%0,%1}, {%2,%3}, {%4}, {%0,%1};" : "+r"(d0), "+r"(d1) : "r"(a0), "r"(a1), "r"(b));
}
__device__ __forceinline__ void mma_h_k8_z(uint32_t (&d)[2], uint32_t a0, uint32_t a1, uint32_t b) {
    asm volatile("mma.sync.aligned.m16n8k8.row.col.f16.f16.f16.f16 {%0,%1}, {%2,%3}, {%4}, {%5,%5};" : "=r"(d[0]), "=r"(d[1]) : "r"(a0), "r"(a1), "r"(b), "r"(0u));
}
__device__ __forceinline__ uint32_t pack_bf(float lo, float hi) { uint32_t r; asm("cvt.rn.bf16x2.f32 %0, %1, %2;" : "=r"(r) : "f"(hi), "f"(lo)); return r; }
__device__ __forceinline__ uint32_t pack_h(float lo, float hi) { uint32_t r; asm("cvt.rn.f16x2.f32 %0, %1, %2;" : "=r"(r) : "f"(hi), "f"(lo)); return r; }
__device__ __forceinline__ float bf_lo(uint32_t v) { return __uint_as_float(v << 16); }
__device__ __forceinline__ float bf_hi(uint32_t v) { return __uint_as_float(v & 0xffff0000u); }
__device__ __forceinline__ float bf_round(float x) { return __uint_as_float(pack_bf(0.f, x) & 0xffff0000u); }
__device__ __forceinline__ uint32_t hmul2_bf(uint32_t a, uint32_t b) { uint32_t r; asm("mul.rn.bf16x2 %0, %1, %2;" : "=r"(r) : "r"(a), "r"(b)); return r; }
__device__ __forceinline__ uint32_t hadd2_bf(uint32_t a, uint32_t b) { uint32_t r; asm("add.rn.bf16x2 %0, %1, %2;" : "=r"(r) : "r"(a), "r"(b)); return r; }
__device__ __forceinline__ uint32_t hfma2_bf(uint32_t a, uint32_t b, uint32_t c) { uint32_t r; asm("fma.rn.bf16x2 %0, %1, %2, %3;" : "=r"(r) : "r"(a), "r"(b), "r"(c)); return r; }
__device__ __forceinline__ uint32_t amax2_bf(uint32_t m, uint32_t v) { uint32_t r; asm("max.xorsign.abs.bf16x2 %0, %1, %2;" : "=r"(r) : "r"(m), "r"(v)); return r; }
__device__ __forceinline__ uint32_t amax2_h(uint32_t m, uint32_t v) { uint32_t r; asm("max.xorsign.abs.f16x2 %0, %1, %2;" : "=r"(r) : "r"(m), "r"(v)); return r; }
__device__ __forceinline__ uint32_t hadd(uint32_t a, uint32_t b) { uint32_t r; asm("add.rn.f16x2 %0, %1, %2;" : "=r"(r) : "r"(a), "r"(b)); return r; }
__device__ __forceinline__ uint32_t hsub(uint32_t a, uint32_t b) { uint32_t r; asm("sub.rn.f16x2 %0, %1, %2;" : "=r"(r) : "r"(a), "r"(b)); return r; }
__device__ __forceinline__ uint32_t hsub2(uint32_t a, uint32_t b) { uint32_t r; asm("sub.rn.ftz.f16x2 %0, %1, %2;" : "=r"(r) : "r"(a), "r"(b)); return r; }
__device__ __forceinline__ uint32_t hmul(uint32_t a, uint32_t b) { uint32_t r; asm("mul.rn.f16x2 %0, %1, %2;" : "=r"(r) : "r"(a), "r"(b)); return r; }
__device__ __forceinline__ uint32_t hfma(uint32_t a, uint32_t b, uint32_t c) { uint32_t r; asm("fma.rn.f16x2 %0, %1, %2, %3;" : "=r"(r) : "r"(a), "r"(b), "r"(c)); return r; }
__device__ __forceinline__ uint32_t hfms(uint32_t a, uint32_t b, uint32_t c) { uint32_t r; asm("{ .reg .b32 t; neg.f16x2 t, %3; fma.rn.f16x2 %0, %1, %2, t; }" : "=r"(r) : "r"(a), "r"(b), "r"(c)); return r; }
__device__ __forceinline__ uint32_t warp_max16(uint32_t m) { return __reduce_max_sync(0xffffffffu, max(m & 0x7fffu, (m >> 16) & 0x7fffu)); }
__device__ __forceinline__ float ex2f(float x) { float r; asm("ex2.approx.ftz.f32 %0, %1;" : "=f"(r) : "f"(x)); return r; }

__device__ __forceinline__ float exp_acc(float x) {
    const float t = x * 1.4426950216293335f;
    const float r = fmaf(x, 1.4426950216293335f, -t) + x * 1.9259629911266175e-8f;
    return ex2f(t) * fmaf(r, 0.6931471805599453f, 1.f);
}
__device__ __forceinline__ float sigmoid_f(float x) { return __fdividef(1.f, 1.f + ex2f(-x * 1.4426950408889634f)); }
__device__ __forceinline__ void cexp(float l2, float th, float& zr, float& zi) {
    const float mag = ex2f(l2);
    const float k = (th * 0.15915494309189535f + 12582912.f) - 12582912.f;
    float r = fmaf(-k, 6.2831854820251465f, th);
    r = fmaf(-k, -1.7484555314695172e-7f, r);
    zr = mag * __cosf(r);
    zi = mag * __sinf(r);
}
struct hc { uint32_t re, im; };
__device__ __forceinline__ hc cmul(const hc& a, const hc& b) { return {hfms(a.re, b.re, hmul(a.im, b.im)), hfma(a.re, b.im, hmul(a.im, b.re))}; }
__device__ __forceinline__ hc cmulc(const hc& a, const hc& b) { return {hfma(a.re, b.re, hmul(a.im, b.im)), hfms(a.im, b.re, hmul(a.re, b.im))}; }
struct fc2 { float r[2], i[2]; };
__device__ __forceinline__ void csq(fc2& z) {
#pragma unroll
    for (int m = 0; m < 2; m++) {
        const float r = fmaf(z.r[m], z.r[m], -(z.i[m] * z.i[m]));
        asm("{ .reg .f32 t; mul.f32 t, %0, %1; mul.f32 %0, t, 0f40000000; }" : "+f"(z.i[m]) : "f"(z.r[m]));
        z.r[m] = r;
    }
}
__device__ __forceinline__ hc pk(const fc2& z) { return {pack_h(z.r[0], z.r[1]), pack_h(z.i[0], z.i[1])}; }
__device__ __forceinline__ void csq_conj(fc2& z) {
#pragma unroll
    for (int m = 0; m < 2; m++) {
        const float r = fmaf(z.r[m], z.r[m], -(z.i[m] * z.i[m]));
        asm("{ .reg .f32 t, n; neg.f32 n, %1; mul.f32 t, %0, n; mul.f32 %0, t, 0f40000000; }" : "+f"(z.i[m]) : "f"(z.r[m]));
        z.r[m] = r;
    }
}

struct Powers { hc C, z1, z2, z4, c8, c16, c32, c64, z128, z256, z512, z1024; };
__device__ __forceinline__ void kg_powers(Powers& q, uint32_t la, uint32_t ai, uint32_t cr, uint32_t ci, float dt, float cf) {
    fc2 z, y;
    const float dtl = -dt * 1.4426950408889634f;
    const uint32_t eb = pack_bf(ex2f(bf_lo(la) * 1.4426950408889634f), ex2f(bf_hi(la) * 1.4426950408889634f));
    const float l2[2] = {bf_lo(eb) * dtl, bf_hi(eb) * dtl}, th[2] = {bf_lo(ai) * dt, bf_hi(ai) * dt};
#pragma unroll
    for (int m = 0; m < 2; m++) { cexp(l2[m], th[m], z.r[m], z.i[m]); cexp(l2[m] * 128.f, th[m] * 128.f, y.r[m], y.i[m]); }
    q.C.re = pack_h(bf_lo(cr) * cf, bf_hi(cr) * cf);
    q.C.im = pack_h(bf_lo(ci) * cf, bf_hi(ci) * cf);
    q.z1 = pk(z); csq(z); q.z128 = pk(y); csq(y);
    q.z2 = pk(z); csq(z); q.z256 = pk(y); csq(y);
    q.z4 = pk(z); csq_conj(z); q.z512 = pk(y); csq(y);
    q.c8 = pk(z); csq(z); q.z1024 = pk(y);
    q.c16 = pk(z); csq(z);
    q.c32 = pk(z); csq(z);
    q.c64 = pk(z);
}
struct Rows { hc ta[8], tb[8], tc[8], pp[8]; };
#define PUT(a0, a1, row, a, b) sts128((((row) & 1) ? (a1) : (a0)) + (row) * 512, (a).re, (a).im, (b).re, (b).im)
template <bool FIRST>
__device__ __forceinline__ void kg_rows(Rows& w, const Powers& q, uint32_t t0, uint32_t t1, uint32_t u0, uint32_t u1, uint32_t zr, uint32_t (&Rl)[2]) {
    w.ta[0] = q.C; w.ta[1] = cmul(q.C, q.z1); w.ta[2] = cmul(q.C, q.z2); w.ta[4] = cmul(q.C, q.z4); w.tb[0] = cmul(q.C, q.z256); w.tb[4] = cmul(q.C, q.z512);
    PUT(t0, t1, 0, w.ta[0], w.tb[0]); PUT(t0, t1, 4, w.ta[4], w.tb[4]);
    w.tb[1] = cmul(w.ta[2], q.z256); w.tb[2] = cmul(w.ta[4], q.z256);
    PUT(t0, t1, 1, w.ta[1], w.tb[1]); PUT(t0, t1, 2, w.ta[2], w.tb[2]);
    w.ta[3] = cmul(w.ta[1], q.z2); w.ta[6] = cmul(w.ta[2], q.z4); w.ta[5] = cmul(w.ta[1], q.z4); w.tb[5] = cmul(w.ta[4], q.z512); w.tb[6] = cmul(w.tb[0], q.z512);
    PUT(t0, t1, 5, w.ta[5], w.tb[5]); PUT(t0, t1, 6, w.ta[6], w.tb[6]);
    w.tb[3] = cmul(w.ta[6], q.z256); w.ta[7] = cmul(w.ta[3], q.z4); w.tb[7] = cmul(w.tb[2], q.z512);
    PUT(t0, t1, 3, w.ta[3], w.tb[3]); PUT(t0, t1, 7, w.ta[7], w.tb[7]);
    PUT(u0, u1, 8, q.c64, q.z128);
    w.pp[0] = hc{0x3C003C00u ^ zr, zr}; w.pp[1] = q.c8; w.pp[2] = q.c16; w.pp[4] = q.c32;
    w.tc[0] = cmul(q.C, q.z1024); w.pp[3] = cmul(q.c8, q.c16); w.pp[5] = cmul(q.c8, q.c32); w.pp[6] = cmul(q.c16, q.c32);
    w.tc[2] = cmul(w.tc[0], q.z128); w.tc[4] = cmul(w.tc[0], q.z256); w.tc[1] = cmul(w.tc[0], q.z512); w.pp[7] = cmul(w.pp[3], q.c32);
    PUT(u0, u1, 0, w.tc[0], w.pp[0]); PUT(u0, u1, 1, w.tc[1], w.pp[1]); PUT(u0, u1, 2, w.tc[2], w.pp[2]); PUT(u0, u1, 4, w.tc[4], w.pp[4]);
    w.tc[6] = cmul(w.tc[2], q.z256); w.tc[3] = cmul(w.tc[2], q.z512); w.tc[5] = cmul(w.tc[4], q.z512);
    PUT(u0, u1, 3, w.tc[3], w.pp[3]); PUT(u0, u1, 5, w.tc[5], w.pp[5]); PUT(u0, u1, 6, w.tc[6], w.pp[6]);
    w.tc[7] = cmul(w.tc[6], q.z512);
    PUT(u0, u1, 7, w.tc[7], w.pp[7]);
    const uint32_t last = hfms(w.tc[0].re, q.z1024.re, hmul(w.tc[0].im, q.z1024.im));
    if (FIRST) mma_h_k8_z(Rl, 0x3C003C00u - zr, 0x3C003C00u + zr, last); else mma_h_k8(Rl[0], Rl[1], 0x3C003C00u - zr, 0x3C003C00u + zr, last);
}
__device__ __forceinline__ void kg_keep(const Rows& w, const Powers& q, uint32_t t0, uint32_t t1, uint32_t u0, uint32_t u1, uint32_t zr) {
}
#undef PUT
template <bool FIRST>
__device__ __forceinline__ void kg_products(uint32_t rt0, uint32_t rt1, uint32_t ru0, uint32_t ru1, uint32_t rc, uint32_t zr,
                                            uint32_t (&Ra)[2][2], uint32_t (&Rb)[2][2], uint32_t (&Rc)[2]) {
    uint4 q1[8], q2[8], cw[8];
#pragma unroll
    for (int ks = 0; ks < 8; ks++) {
        q2[ks] = lds128(((ks & 1) ? ru1 : ru0) + (ks >> 1) * 128); cw[ks] = lds128(rc + ks * 64); q1[ks] = lds128(((ks & 1) ? rt1 : rt0) + (ks >> 1) * 128);
    }
#pragma unroll
    for (int ks = 0; ks < 8; ks++) {
        const hc p0 = {q2[ks].z, q2[ks].w}, u = {cw[ks].x, cw[ks].y}, v = {cw[ks].z, cw[ks].w};
        const hc p1 = cmul(p0, u), p2 = cmulc(p0, v), p3 = cmulc(p1, v);
        const uint32_t qa[4] = {p0.re ^ zr, p1.re, p0.im ^ zr, p1.im}, qb[4] = {p2.re, p3.re, p2.im, p3.im};
        if (FIRST && ks == 0) {
            mma_h_z(Rc[0], Rc[1], qa, q2[ks].x, q2[ks].y); mma_h_z(Ra[0][0], Ra[0][1], qa, q1[ks].x, q1[ks].y); mma_h_z(Rb[0][0], Rb[0][1], qa, q1[ks].z, q1[ks].w);
            mma_h_z(Ra[1][0], Ra[1][1], qb, q1[ks].x, q1[ks].y); mma_h_z(Rb[1][0], Rb[1][1], qb, q1[ks].z, q1[ks].w);
        } else {
            mma_h(Rc, qa, q2[ks].x, q2[ks].y); mma_h(Ra[0], qa, q1[ks].x, q1[ks].y); mma_h(Rb[0], qa, q1[ks].z, q1[ks].w);
            mma_h(Ra[1], qb, q1[ks].x, q1[ks].y); mma_h(Rb[1], qb, q1[ks].z, q1[ks].w);
        }
    }
}
__device__ __forceinline__ void kernel_gen(const uint2& la, const uint2& ai, const uint2& cr, const uint2& ci, float dt, float cf, uint32_t TB, uint32_t UB,
                                           int lane, uint32_t zr, uint32_t (&Ra)[2][2], uint32_t (&Rb)[2][2], uint32_t (&Rc)[2], uint32_t (&Rl)[2]) {
    const int g = lane >> 2, t = lane & 3;
    const uint32_t w0 = lane << 4, w1 = w0 ^ 64, r0 = g * 512 + (((g & 1) << 6) | (t << 4)), r1 = r0 ^ 64;
    const uint32_t t0 = TB + w0, t1 = TB + w1, u0 = UB + w0, u1 = UB + w1;
    Powers p0, p1;
    Rows w;
    kg_powers(p0, la.x, ai.x, cr.x, ci.x, dt, cf);
    kg_rows<true>(w, p0, t0, t1, u0, u1, zr, Rl);
    kg_powers(p1, la.y, ai.y, cr.y, ci.y, dt, cf);
    kg_keep(w, p0, t0, t1, u0, u1, zr);
    __syncwarp();
    kg_products<true>(TB + r0, TB + r1, UB + r0, UB + r1, UB + 4096 + t * 16, zr, Ra, Rb, Rc);
    __syncwarp();
    kg_rows<false>(w, p1, t0, t1, u0, u1, zr, Rl);
    kg_keep(w, p1, t0, t1, u0, u1, zr);
    __syncwarp();
    kg_products<false>(TB + r0, TB + r1, UB + r0, UB + r1, UB + 4096 + t * 16, zr, Ra, Rb, Rc);
    __syncwarp();
}

template <int V> struct IC { static constexpr int value = V; };

#define LANE_VARS \
    int tid_; asm volatile("mov.u32 %0, %%tid.x;" : "=r"(tid_)); \
    [[maybe_unused]] const int lane = tid_ & 31, warp = (tid_ >> 5) - MAIN_W0, g = lane >> 2, t = lane & 3, mi = lane >> 3, r = lane & 7; \
    [[maybe_unused]] const uint32_t TB = sb + OFF_TAB + warp * T_CH, UB = sb + OFF_U + warp * U_CH; \
    [[maybe_unused]] const bool lead = (tid_ == 32 * MAIN_W0)

__device__ __forceinline__ void dense_step(uint32_t (&M)[8][2], uint32_t (&Ye)[8][2], uint32_t (&Yo)[8][2], uint32_t (&X)[8][2],
                                           uint32_t (&F)[8][2], uint32_t (&Bq)[2][4], uint32_t ua, uint32_t ta, uint32_t zr) {
    uint32_t E[8][2], A[2][4], S[2][4], G[8][2];
#pragma unroll
    for (int jp = 0; jp < 4; jp++) ldsm4(ua + jp * 256, E[2 * jp][0], E[2 * jp][1], E[2 * jp + 1][0], E[2 * jp + 1][1]);
#pragma unroll
    for (int h = 0; h < 2; h++) { A[h][0] = lds32(ta + 1024 * h); A[h][1] = lds32(ta + 1024 * h + 32); A[h][3] = lds32(ta + 1024 * h + 64); A[h][2] = A[h][1] ^ zr; }
#pragma unroll
    for (int J = 0; J < 8; J++) mma_h(Ye[J], Bq[0], F[J][0], F[J][1]);
#pragma unroll
    for (int J = 1; J < 8; J++) mma_h(Ye[J], Bq[1], F[J - 1][0], F[J - 1][1]);
#pragma unroll
    for (int J = 0; J < 8; J++) { G[J][0] = hsub(X[J][0], E[J][0]); G[J][1] = hsub(X[J][1], E[J][1]); }
#pragma unroll
    for (int jp = 0; jp < 4; jp++) ldsm4(ua + 2 * U_PL + jp * 256 - 16, X[2 * jp][0], X[2 * jp][1], X[2 * jp + 1][0], X[2 * jp + 1][1]);
#pragma unroll
    for (int h = 0; h < 2; h++) { Bq[h][1] = lds32(ta + 1024 * h + 96); Bq[h][3] = lds32(ta + 1024 * h + 128); Bq[h][0] = A[h][3] ^ zr; Bq[h][2] = Bq[h][1] ^ zr; }
#pragma unroll
    for (int J = 0; J < 8; J++) mma_h(Yo[J], A[0], G[J][0], G[J][1]);
#pragma unroll
    for (int J = 1; J < 8; J++) mma_h(Yo[J], A[1], G[J - 1][0], G[J - 1][1]);
#pragma unroll
    for (int h = 0; h < 2; h++)
#pragma unroll
        for (int i = 0; i < 4; i++) S[h][i] = hadd(A[h][i], Bq[h][i]);
#pragma unroll
    for (int J = 0; J < 8; J++) mma_h(M[J], S[0], E[J][0], E[J][1]);
#pragma unroll
    for (int J = 1; J < 8; J++) mma_h(M[J], S[1], E[J - 1][0], E[J - 1][1]);
#pragma unroll
    for (int J = 0; J < 8; J++) { F[J][0] = hsub(X[J][0], E[J][0]); F[J][1] = hsub(X[J][1], E[J][1]); }
}

__device__ __forceinline__ void group_tables(uint32_t TB, int lane) {
    const int g = lane >> 2, t = lane & 3;
    const uint4 b4 = lds128(TB + T_R2 + 16 * lane), c4 = lds128(TB + T_R2 + 512 + 16 * lane);
    uint32_t vb[4] = {b4.x, b4.y, b4.z, b4.w}, vc[2] = {c4.x, c4.y};
    const uint32_t k1024 = __shfl_sync(0xffffffffu, vc[0], 0) & 0xffffu;
#pragma unroll
    for (int i = 0; i < 3; i++) sts128(TB + T_R2 + 16 * lane + 512 * i, 0, 0, 0, 0);
    if (lane == 2) vb[0] &= 0xffff0000u;
    if (lane == 0) vc[0] &= 0xffff0000u;
    if (lane == 4) vc[0] = hsub(vc[0], k1024);
    __syncwarp();
    if (t >= 2) {
        const uint32_t g1 = TB + T_R2 + T2_S * (g & 3) + 8 * (8 * t - 10 + (g >> 2));
        const uint32_t g0 = TB + T_R2 + T2_S * ((g - 1) & 3) + 8 * (8 * t - 10 + ((g - 1) >> 2)) + 4;
#pragma unroll
        for (int i = 0; i < 4; i++) {
            sts16(g0 + 16 * i, vb[i]); sts16(g0 + 16 * i + 10, vb[i]);
            sts16(g1 + 16 * i, vb[i] >> 16); sts16(g1 + 16 * i + 10, vb[i] >> 16);
        }
    }
    const uint32_t g3 = TB + T_R3 + T3_S * (((g - 1) >> 1) & 1) + 8 * (7 + 4 * t + ((g - 1) >> 2)) + 4 * ((g - 1) & 1);
#pragma unroll
    for (int i = 0; i < 2; i++) {
        sts16(g3 + 16 * i, vc[i]); sts16(g3 + 16 * i + 10, vc[i]);
        sts16(g3 + 16 * i + 128, vc[i] >> 16); sts16(g3 + 16 * i + 138, vc[i] >> 16);
    }
    const uint32_t g4 = (uint32_t)(((uint64_t)(T_R3 + T3_S + 308) << 48 | (uint64_t)(T_R2 + 180) << 32 | (T_R2 + 176) << 16 | (T_R2 + 3 * T2_S + 172)) >> (8 * (lane & 6))) & 0xffffu;
    sts16(TB + g4 + 10 * (lane & 1), (lane & 7) < 6 ? k1024 : c4.z);
}

#define FENCE() do { if (zr) asm volatile("exit;"); } while (0)
struct Chunks { uint32_t c3, c2, c1, c0, cm1, cm2, cm3, cm4, d2, d1, d0, dm1, em2, em3; };
__device__ __forceinline__ void convolve(uint32_t sb, int h, uint32_t zr DBG_PARAMS) {
    const uint32_t bars = sb + M_BARS;
    uint32_t M[8][2], Ye[8][2], Yo[8][2], F[8][2], Bq[2][4];
    {
        LANE_VARS;
        uint32_t X[8][2];
        uint32_t ua = UB + ((mi & 1) ? 0 : U_PL) + (8 + 8 * (mi >> 1) + r) * 16, ta = TB + 4 * (1 + g + 2 * t);
        uint32_t A[3][4], S[2][4];
        __syncwarp();
#pragma unroll
        for (int h2 = 0; h2 < 3; h2++) { A[h2][0] = lds32(ta + 1024 * h2); A[h2][1] = lds32(ta + 1024 * h2 + 32); A[h2][3] = lds32(ta + 1024 * h2 + 64); A[h2][2] = A[h2][1] ^ zr; }
#pragma unroll
        for (int h2 = 0; h2 < 2; h2++) {
            Bq[h2][1] = lds32(ta + 1024 * h2 + 96); Bq[h2][3] = lds32(ta + 1024 * h2 + 128); Bq[h2][0] = A[h2][3] ^ zr; Bq[h2][2] = Bq[h2][1] ^ zr;
#pragma unroll
            for (int i = 0; i < 4; i++) S[h2][i] = hadd(A[h2][i], Bq[h2][i]);
        }
        const uint32_t an = A[0][0] ^ zr, un = UB + (9 + lane) * 16;
        if (lead) TSTAMP(10);
        bar_sync(3, 256);
        if (lead) { TSTAMP(3); CSTAMP(27); }
        uint32_t E[8][2], N[8], G[8][2];
#pragma unroll
        for (int jp = 0; jp < 4; jp++) ldsm4(ua + jp * 256, E[2 * jp][0], E[2 * jp][1], E[2 * jp + 1][0], E[2 * jp + 1][1]);
#pragma unroll
        for (int jp = 0; jp < 4; jp++) ldsm4(ua + 2 * U_PL + jp * 256, X[2 * jp][0], X[2 * jp][1], X[2 * jp + 1][0], X[2 * jp + 1][1]);
        ldsm4(un, N[0], N[1], N[2], N[3]); ldsm4(un + 512, N[4], N[5], N[6], N[7]);
#pragma unroll
        for (int J = 0; J < 8; J++) mma_h_z(M[J][0], M[J][1], S[0], E[J][0], E[J][1]);
#pragma unroll
        for (int J = 1; J < 8; J++) mma_h(M[J], S[1], E[J - 1][0], E[J - 1][1]);
#pragma unroll
        for (int J = 2; J < 8; J++) mma_h(M[J], A[2], E[J - 2][0], E[J - 2][1]);
        if (FENCES & 32) FENCE();
#pragma unroll
        for (int J = 0; J < 8; J++) mma_h_k8_z(Ye[J], zr, an, X[J][1]);
#pragma unroll
        for (int J = 0; J < 8; J++) mma_h_k8_z(Yo[J], zr, an, N[J]);
#pragma unroll
        for (int J = 0; J < 8; J++) { G[J][0] = hsub(X[J][0], E[J][0]); G[J][1] = hsub(X[J][1], E[J][1]); }
#pragma unroll
        for (int jp = 0; jp < 4; jp++) ldsm4(ua + 2 * U_PL + jp * 256 - 16, X[2 * jp][0], X[2 * jp][1], X[2 * jp + 1][0], X[2 * jp + 1][1]);
#pragma unroll
        for (int J = 0; J < 8; J++) mma_h(Yo[J], A[0], G[J][0], G[J][1]);
#pragma unroll
        for (int J = 1; J < 8; J++) mma_h(Yo[J], A[1], G[J - 1][0], G[J - 1][1]);
#pragma unroll
        for (int J = 2; J < 8; J++) mma_h(Yo[J], A[2], G[J - 2][0], G[J - 2][1]);
#pragma unroll
        for (int J = 0; J < 8; J++) { F[J][0] = hsub(X[J][0], E[J][0]); F[J][1] = hsub(X[J][1], E[J][1]); }
#pragma unroll 1
        for (int k = 1; k < 8; k++) {
            ua -= 16; ta += 128;
            dense_step(M, Ye, Yo, X, F, Bq, ua, ta, zr);
        }
    }
    mbar_wait_n<2, 8>(bars + 8 * B_TD);
    LANE_VARS;
    if (lead) { TSTAMP(4); CSTAMP(28); }
    __syncwarp();
    const uint32_t idh = (g == 2 * t) ? 0x3C00u : (g == 2 * t + 1) ? 0x3C000000u : 0u;
    const uint32_t sbr = mapa(sb, h ^ 1);
    const uint32_t yl = TB + lane * 16, yr = sbr + (h ? ALT0 : ALT1) + A_YIN + warp * Y_CH + lane * 16;
    uint32_t early[4][4];
    auto finish = [&](int J) {
        float m[4], e[4], o[4];
        widen_h(m, M[J], idh); widen_add_h(e, Ye[J], idh, m); widen_add_h(o, Yo[J], idh, m);
        const uint32_t y[4] = {pack_bf(e[0], e[2]), pack_bf(o[0], o[2]), pack_bf(e[1], e[3]), pack_bf(o[1], o[3])};
        if (J < 4) {
#pragma unroll
            for (int i = 0; i < 4; i++) early[J & 3][i] = y[i];
        } else {
            const uint32_t* ea = early[J & 3];
            st_async16(yr + (J & 3) * 512, h ? ea[0] : y[0], h ? ea[1] : y[1], h ? ea[2] : y[2], h ? ea[3] : y[3], sbr + M_BARS + 8 * (B_Y + (J & 3)));
            sts128(yl + (J & 3) * 512, h ? y[0] : ea[0], h ? y[1] : ea[1], h ? y[2] : ea[2], h ? y[3] : ea[3]);
            __syncwarp();
            if (lane == 0) mbar_arrive(bars + 8 * (B_Y + (J & 3)));
        }
    };
    const uint32_t a1 = UB + (3 - mi) * U_PL + (8 + r) * 16;
    const uint32_t a2 = UB + ((2 - mi) & 3) * U_PL + (8 + r - (mi == 3)) * 16;
    const uint32_t a3 = UB + (2 - (mi & 1)) * U_PL + (7 + r) * 16;
    const uint32_t bt = sb + OFF_BAND + 4 * (32 + g + 2 * t);
    auto load3 = [&](Chunks& u, int j) { ldsm4(a2 + j * 128, u.d2, u.d1, u.d0, u.dm1); ldsm4(a1 + j * 128, u.c3, u.c2, u.c1, u.c0); ldsm2(a3 + j * 128, u.em2, u.em3); };
    auto load2 = [&](Chunks& u, int j) { load3(u, j); ldsm4(a1 + j * 128 - 16, u.cm1, u.cm2, u.cm3, u.cm4); };
    Chunks u;
    uint32_t B35[4];
    uint2 Q[4][3], QS[2][3];
    {
        const uint32_t f7 = lds32(bt + 768 - 36), g7 = lds32(bt + 768 - 4), f9 = lds32(bt + 1024 - 32), g9 = lds32(bt + 1024), h9 = lds32(bt + 1024 + 32);
        const uint32_t f1 = hmul(lds32(bt - 28), lds16(TB + T_R2 + 176) * 0x10001u);
        load3(u, 0);
        const uint32_t tq = TB + T_R3 + 8 * (7 + g - 2 * t);
        uint2 Q0[4], Q1[4], Q2[4];
#pragma unroll
        for (int i = 0; i < 4; i++) { Q0[i] = lds64(tq + 64 * i); Q1[i] = lds64(tq + T3_S + 64 * i); Q2[i] = lds64(tq + T3_S - 8 + 64 * i); }
#pragma unroll
        for (int J = 0; J < 8; J++) mma_h(Ye[J], Bq[0], F[J][0], F[J][1]);
#pragma unroll
        for (int J = 1; J < 8; J++) mma_h(Ye[J], Bq[1], F[J - 1][0], F[J - 1][1]);
        const uint32_t B7[4] = {zr, f7, f7 ^ zr, g7}, B9a[4] = {zr + zr, f9, f9 ^ zr, g9}, B9b[4] = {g9 ^ zr, h9, h9 ^ zr, zr * 3}, B1[4] = {zr * 5, f1, f1 ^ zr, zr * 7};
        const uint32_t g7b = g7 ^ zr, z7 = zr * 9;
        if (FENCES & 1) FENCE();
        uint32_t WE[2][4], WO[2][4];
#pragma unroll
        for (int j = 0; j < 5; j++) {
            uint32_t (&we)[4] = WE[j & 1], (&wo)[4] = WO[j & 1], (&pe)[4] = WE[~j & 1], (&po)[4] = WO[~j & 1];
            if (j == 3) {
                const uint32_t t2 = TB + T_R2 + 8 * (6 + g - 2 * t);
                B35[0] = lds32(bt + 256 - 28); B35[1] = lds32(bt + 512 - 40); B35[2] = lds32(bt + 256 + 4); B35[3] = lds32(bt + 512 - 8);
#pragma unroll
                for (int i = 0; i < 3; i++)
#pragma unroll
                    for (int s = 0; s < 4; s++) Q[s][i] = lds64(t2 + T2_S * s + 64 * i);
            }
            if (j < 4) {
                mma_h_z(we[2], we[3], B9a, u.d0, u.dm1); mma_h_z(wo[2], wo[3], B9a, u.d2, u.d1);
                mma_h_z(we[0], we[1], B7, u.c1, u.c0); mma_h_z(wo[0], wo[1], B7, u.c3, u.c2);
            }
            if (j == 0) { finish(0); finish(1); }
#pragma unroll
            for (int i = 0; i < 5 - j && j > 0; i++) { mma_h(Ye[j + 3 + i], pe, Q0[i].x, Q0[i].y); mma_h(Yo[j + 3 + i], pe, Q1[i].x, Q1[i].y); }
            if (j < 4) {
                mma_h2(we[2], we[3], B9b, u.em2, u.em3); mma_h2(wo[2], wo[3], B9b, u.d0, u.dm1);
                mma_h_k8(we[0], we[1], g7b, z7, u.dm1); mma_h_k8(wo[0], wo[1], g7b, z7, u.c1);
                mma_h(Ye[j + 4], B1, u.d0, u.dm1); mma_h(Yo[j + 4], B1, u.d2, u.d1);
                if (j < 3) load3(u, j + 1); else load2(u, 0);
            }
#pragma unroll
            for (int i = 0; i < 5 - j && j > 0; i++) { mma_h(Ye[j + 3 + i], po, Q2[i].x, Q2[i].y); mma_h(Yo[j + 3 + i], po, Q0[i].x, Q0[i].y); }
            if (j == 3) {
#pragma unroll
                for (int i = 0; i < 3; i++)
#pragma unroll
                    for (int s = 0; s < 2; s++) { QS[s][i].x = hadd(Q[s][i].x, Q[s + 2][i].x); QS[s][i].y = hadd(Q[s][i].y, Q[s + 2][i].y); }
            }
            if (j < 3 ? ((FENCES & 2) || (j == 2 && (FENCES & 4))) : (j == 4 && (FENCES & 8))) FENCE();
        }
    }
    const uint32_t zq = zr + zr;
#pragma unroll
    for (int j = 0; j < 6; j++) {
        uint32_t H[7][2];
        mma_h_z(H[3][0], H[3][1], B35, u.d0, u.dm1); mma_h_z(H[4][0], H[4][1], B35, u.c1, u.c0);
        mma_h_z(H[5][0], H[5][1], B35, u.d2, u.d1); mma_h_z(H[6][0], H[6][1], B35, u.c3, u.c2);
        mma_h_z(H[2][0], H[2][1], B35, u.cm1, u.cm2); mma_h_z(H[1][0], H[1][1], B35, u.em2, u.em3); mma_h_z(H[0][0], H[0][1], B35, u.cm3, u.cm4);
        if (j < 5) load2(u, j + 1);
        if (j > 0) finish(j + 1);
        const int n = j < 4 ? 3 : 6 - j;
#pragma unroll
        for (int s = 0; s < 2; s++) {
            const int o = 3 - s;
            const uint32_t qe[4] = {H[o][0] ^ zr, H[o + 1][0] ^ zq, H[o][1] ^ zr, H[o + 1][1] ^ zq};
            const uint32_t qg[4] = {hsub(H[o + 2][0], H[o][0]), hsub2(H[o + 3][0], H[o + 1][0]), hsub(H[o + 2][1], H[o][1]), hsub2(H[o + 3][1], H[o + 1][1])};
            const uint32_t qf[4] = {hsub(H[o - 2][0], H[o][0]), hsub2(H[o - 1][0], H[o + 1][0]), hsub(H[o - 2][1], H[o][1]), hsub2(H[o - 1][1], H[o + 1][1])};
#pragma unroll
            for (int i = 0; i < n; i++) mma_h(M[j + 2 + i], qe, QS[s][i].x, QS[s][i].y);
#pragma unroll
            for (int i = 0; i < n; i++) mma_h(Yo[j + 2 + i], qg, Q[s][i].x, Q[s][i].y);
#pragma unroll
            for (int i = 0; i < n; i++) mma_h(Ye[j + 2 + i], qf, Q[s + 2][i].x, Q[s + 2][i].y);
        }
        if (j < 5 && (FENCES & 16)) FENCE();
    }
    finish(7);
}

__global__ void __cluster_dims__(2, 1, 1) __launch_bounds__(NTHREADS, 1)
fused_kernel(const Params p, const __grid_constant__ CUtensorMap tm_gu, const __grid_constant__ CUtensorMap tm_down, const __grid_constant__ CUtensorMap tm_x,
             const __grid_constant__ CUtensorMap tm_r) {
    extern __shared__ __align__(1024) unsigned char smem[];
    const uint32_t sb = __shfl_sync(0xffffffffu, smem_u32(smem), 0);
    int tid;
    asm volatile("mov.u32 %0, %%tid.x;" : "=r"(tid));
    const int pw = tid >> 5, lane = tid & 31;
    const int kc = ((blockIdx.x >> 1) + 60) & 63, k7 = ((kc - 32) * 37) >> 8;
    const int h = blockIdx.x & 1;
    const int pr = !REMAP ? (int)(blockIdx.x >> 1) : kc < 32 ? ((kc & 7) << 2) | (kc >> 3) : kc < 60 ? 32 + 4 * (kc - 32 - 7 * k7) + k7 : kc;
    const int c = 2 * pr + h;
    const uint32_t bars = sb + M_BARS;

    if (blockIdx.x >= 128) {
        if (blockIdx.x != 128) return;
        const unsigned tag = (ld_epoch(p.ex) + 1) & 0xffffu;
        const uint32_t idx0 = 2047 - (256 * (tid & 3) + (tid >> 3) + 1024 * ((tid >> 2) & 1));
        const uint32_t list = sb + 128;
#pragma unroll 1
        for (int pass = 0; pass < 2; pass++) {
            if (tid == 0) sts32(sb + 64, 0);
            sts128(list + 16 * tid, 0, 0, 0, 0);
            uint4 a = make_uint4(lane == 0 ? 0x10000u : 0u, 0, 0, 0);
            bool ok = pass == 0;
#pragma unroll 1
            for (int it = 0; it < (1 << 22) && !ok; it++) {
                a = ld_gpu128(&p.ex->r[tid]);
                ok = (((a.x ^ tag) | (a.y ^ tag) | (a.z ^ tag) | (a.w ^ tag)) & 0xffffu) == 0;
            }
            if (!ok) __trap();
            const uint32_t key[4] = {(a.x & 0xffff0000u) | idx0, (a.y & 0xffff0000u) | (idx0 - 64), (a.z & 0xffff0000u) | (idx0 - 128), (a.w & 0xffff0000u) | (idx0 - 192)};
            const uint32_t wm = __reduce_max_sync(0xffffffffu, max(max(key[0], key[1]), max(key[2], key[3])));
            if (lane == 0) sts32(sb + pw * 4, wm);
            __syncthreads();
            const uint2 q = lds64(sb + 8 * (lane & 7));
            const uint32_t thr = __reduce_min_sync(0xffffffffu, max(q.x, q.y));
            if (tid == 0) TSTAMP(0);
            const uint32_t n = (key[0] >= thr) + (key[1] >= thr) + (key[2] >= thr) + (key[3] >= thr);
            if (n) {
                uint32_t pos;
                asm volatile("atom.shared.add.u32 %0, [%1], %2;" : "=r"(pos) : "r"(sb + 64), "r"(n) : "memory");
#pragma unroll
                for (int i = 0; i < 4; i++) if (key[i] >= thr) { sts32(list + 4 * pos, key[i]); pos++; }
            }
            __syncthreads();
            const int ncand = (int)lds32(sb + 64);
            const uint2 l0 = lds64(list + 8 * lane);
#pragma unroll 1
            for (int j = pw; j < ncand; j += 16) {
                const uint32_t mine = lds32(list + 4 * j);
                int rank = __popc(__ballot_sync(0xffffffffu, l0.x > mine)) + __popc(__ballot_sync(0xffffffffu, l0.y > mine));
#pragma unroll 1
                for (int i = 64; i < ncand; i += 32) rank += __popc(__ballot_sync(0xffffffffu, lds32(list + 4 * (i + lane)) > mine));
                if (rank < 8 && lane == 0) {
                    asm volatile("st.relaxed.gpu.global.v2.u32 [%0], {%1, %2};" :: "l"(&p.ex->top[rank]), "r"(mine), "r"(pass ? tag : tag ^ 0x8000u) : "memory");
                }
            }
            if (tid == 0) TSTAMP(1);
            __syncthreads();
        }
        if (tid == 0) TSDUMP(3u);
        return;
    }

    if (pw != 12) asm volatile("barrier.cluster.arrive.relaxed.aligned;" ::: "memory");

    if (pw >= MAIN_W0 && pw < MAIN_W0 + 8) {
        const int warp = pw - MAIN_W0;
        const uint32_t po = (8 * c + warp) * 128 + 4 * lane;
        uint2 v_la = ldg64(p.logA + po), v_ai = ldg64(p.Aim + po), v_cr = ldg64(p.Cre + po), v_ci = ldg64(p.Cim + po);
        const uint32_t ldt16 = ldg16(p.logdt + 8 * c + warp);
        [[maybe_unused]] const bool lead = (tid == 32 * MAIN_W0);
        asm volatile("setmaxnreg.inc.sync.aligned.u32 " MAIN_REGS ";");
        [[maybe_unused]] const int d = 8 * c + warp;
        const int g = lane >> 2, t = lane & 3, mi = lane >> 3, r = lane & 7;
        const uint32_t TB = sb + OFF_TAB + warp * T_CH;
        const uint32_t UB = sb + OFF_U + warp * U_CH;
        const uint32_t zr = p.zero;

        uint32_t Ra[2][2], Rb[2][2], Rc[2], Rl[2];
        int esum;
        {
            const float dt = bf_round(exp_acc(__uint_as_float(ldt16 << 16)));
            const uint32_t ec = max(warp_max16(amax2_bf(amax2_bf(v_cr.x, v_cr.y), amax2_bf(v_ci.x, v_ci.y))) >> 7, 6u);
            const float cf = __uint_as_float((__float_as_uint(dt) & 0x7fffffu) | ((260u - ec) << 23));
            esum = (int)ec + (int)(__float_as_uint(dt) >> 23) - 274;
            kernel_gen(v_la, v_ai, v_cr, v_ci, dt, cf, TB, UB, lane, zr, Ra, Rb, Rc, Rl);
        }
        if (lead) TSTAMP(2);
        bar_sync(5, 384);

        uint32_t xr[8][4], utail = 0;
        {
            mbar_wait_n<4, 8>(bars + 8 * B_S);
            if (lead) TSTAMP(9);
            const int dl = 8 * (r >> 1) + 4 - 2 * mi - (r & 1);
            const uint32_t so = sb + OFF_S + (8 * warp + (dl >> 5)) * 1024 + (dl & 7) * 128 + ((dl >> 3) & 3) * 32 + (((dl & 1) ^ h) << 4);
#pragma unroll
            for (int i = 0; i < 8; i++) ldsm4t(so + i * 1024, xr[i][0], xr[i][1], xr[i][2], xr[i][3]);
            if (lane >= 5 && lane < 8) utail = lds16(sb + OFF_S + 63 * 1024 + 96 + (12 - lane) * 128 + (((lane & 1) ^ h) << 4) + 2 * warp);
            uint32_t mx = utail;
#pragma unroll
            for (int i = 0; i < 8; i++) mx = amax2_bf(amax2_bf(mx, amax2_bf(xr[i][0], xr[i][1])), amax2_bf(xr[i][2], xr[i][3]));
            mx = warp_max16(mx);
            if (lane == 0) { sts32(sb + M_MX + warp * 4, mx); mbar_arrive(bars + 8 * B_MX); }
        }

        {
            uint32_t kl = hadd(Rl[0], __byte_perm(Rl[0], 0, 0x1032));
            kl = hadd(kl, __shfl_xor_sync(0xffffffffu, kl, 1)); kl = hadd(kl, __shfl_xor_sync(0xffffffffu, kl, 2));
            uint32_t mk = amax2_h(amax2_h(amax2_h(Ra[0][0], Ra[0][1]), amax2_h(Ra[1][0], Ra[1][1])), amax2_h(amax2_h(Rb[0][0], Rb[0][1]), amax2_h(Rb[1][0], Rb[1][1])));
            mk = amax2_h(amax2_h(mk, kl), amax2_h(Rc[0], Rc[1]));
            const uint32_t ek = warp_max16(mk) >> 10;
            esum += (int)ek;
            const float fs = __uint_as_float((139u - ek) << 23);
            const uint32_t ks = pack_h(fs, fs);
            sts128(UB + mi * U_PL + r * 16, 0, 0, 0, 0);
            uint32_t va[4], vb[4];
#pragma unroll
            for (int i = 0; i < 4; i++) { va[i] = hmul(Ra[i >> 1][i & 1], ks); vb[i] = hmul(Rb[i >> 1][i & 1], ks); }
            sts128(TB + T_R2 + 16 * lane, vb[0], vb[1], vb[2], vb[3]);
            sts128(TB + T_R2 + 512 + 16 * lane, hmul(Rc[0], ks), hmul(Rc[1], ks), hmul(kl, ks), zr);
            __syncwarp();
            if (lane == 0) mbar_arrive(bars + 8 * B_TS);
            const uint32_t k512 = __shfl_sync(0xffffffffu, vb[0], 2) & 0xffffu, k255 = __shfl_sync(0xffffffffu, va[3], 31);
#pragma unroll
            for (int i = 0; i < 4; i++) {
                const uint32_t pv = __shfl_sync(0xffffffffu, lane == 31 ? (i ? va[i - 1] : 0u) : va[i], lane - 1);
                sts64(TB + 48 + 256 * i + 8 * lane, __byte_perm(pv, va[i], 0x5432), va[i]);
            }
#pragma unroll
            for (int i = 0; i < 4; i++) {
                const uint32_t nx = __shfl_sync(0xffffffffu, lane == 0 ? (i < 3 ? vb[i + (i < 3)] : k512) : vb[i], lane + 1 + 2 * (lane & 1));
                const uint32_t aa = __byte_perm(vb[i], 0, 0x1010);
                sts128_if(t < 2, TB + 1072 + 256 * i + 32 * g + 16 * t, (i == 0 && lane == 0) ? __byte_perm(k255, aa, 0x5432) : aa ^ zr, aa, vb[i] ^ zr, __byte_perm(vb[i], nx, 0x5432));
            }
            const uint32_t k0 = lane == 3 ? k512 : 0u, kk = k0 * 0x10001u;
            sts128_if(lane < 8, TB + 16 * lane + (lane < 3 ? 0 : 2048), kk, kk ^ zr, kk + zr, k0);
        }
        if (lead) TSTAMP(11);

        {
            mbar_wait(bars + 8 * B_MX);
            const uint32_t eu = max(__reduce_max_sync(0xffffffffu, lds32(sb + M_MX + r * 4)) >> 7, 3u);
            esum += (int)eu;
            const uint32_t sc = (257u - eu) << 7;
            const uint32_t idb = (g == 2 * t) ? sc : (g == 2 * t + 1) ? sc << 16 : 0u;
            const uint32_t uo = sb + OFF_U + g * U_CH + t * U_PL + (8 + 8 * warp) * 16;
#pragma unroll
            for (int i = 0; i < 8; i++) {
                float f0[4], f1[4];
                widen_bf(f0, xr[i][0], xr[i][1], idb); widen_bf(f1, xr[i][2], xr[i][3], idb);
                sts128(uo + i * 16, pack_h(f0[0], f0[1]), pack_h(f0[2], f0[3]), pack_h(f1[0], f1[1]), pack_h(f1[2], f1[3]));
            }
            if (lane < 8) sts16(UB + 72 * 16 + lane * 2, pack_h(bf_lo(utail) * bf_lo(sc), 0.f));
            asm volatile("barrier.cluster.wait.acquire.aligned;" ::: "memory");
            if (lane < 2) { const uint32_t o = mapa(sb, lane); st_async4(o + M_SC + (8 * h + warp) * 4, (uint32_t)min(max(esum, 1), 254) << 7, o + M_BARS + 8 * B_SC); }
        }

        convolve(sb, h, zr DBG_ARGS);

        {
            LANE_VARS;
            if (lead) { TSTAMP(5); CSTAMP(29); }
            bar_sync(2, 384);
            const uint32_t xo = sb + OFF_S + (32 * h + (g >> 2)) * 1024 + warp * 128 + (g & 3) * 32 + (((t >> 1) ^ (warp & 1)) << 4) + ((t & 1) << 3);
            const uint32_t go = sb + OFF_GP + (8 * warp + g) * 64;
            const uint32_t sel = lds16(sb + M_BMAP + (8 * warp + g) * 2);
            const int ch16 = 4 * (r >> 1) + 2 * (mi & 1) + (r & 1);
            const uint32_t ya = sb + (((ch16 >> 3) == h) ? OFF_TAB + (ch16 & 7) * T_CH : (h ? ALT1 : ALT0) + A_YIN + (ch16 & 7) * Y_CH) + (4 * warp + (mi >> 1)) * 16;
            bf16* op = p.out + (size_t)(1024 * h + 8 * g + warp) * D_ + 16 * pr + 4 * t;
            const uint2 dsk = lds64(sb + M_DSK + 8 * t);
            const uint4 s4 = lds128(sb + M_SC + t * 16);
            const uint32_t s01 = __byte_perm(s4.x, s4.y, 0x5410), s23 = __byte_perm(s4.z, s4.w, 0x5410);
#pragma unroll
            for (int J = 0; J < 4; J++) {
                const uint4 g4 = lds128(go + J * 16);
                const uint32_t gp[4] = {g4.x, g4.y, g4.z, g4.w};
                uint2 xd[4], ex[4];
#pragma unroll
                for (int i = 0; i < 4; i++) {
                    const uint2 x = lds64(xo + (4 * J + i) * 2048);
                    const uint32_t og = __byte_perm(gp[i], 0, 0x3232);
                    ex[i].x = hmul2_bf(og, x.x); ex[i].y = hmul2_bf(og, x.y);
                    xd[i].x = hmul2_bf(x.x, dsk.x); xd[i].y = hmul2_bf(x.y, dsk.y);
                }
                mbar_wait(bars + 8 * (B_Y + J));
                if (J == 3 && lead) TSTAMP(6);
#pragma unroll
                for (int q = 0; q < 2; q++) {
                    uint32_t y[4];
                    ldsm4t(ya + J * 512 + q * 32, y[0], y[1], y[2], y[3]);
#pragma unroll
                    for (int hx = 0; hx < 2; hx++) {
                        const int i = 2 * q + hx;
                        const uint32_t gg = __byte_perm(gp[i], 0, 0x1010);
                        uint2 o;
                        o.x = hadd2_bf(hmul2_bf(gg, hfma2_bf(y[2 * hx], s01, xd[i].x)), ex[i].x);
                        o.y = hadd2_bf(hmul2_bf(gg, hfma2_bf(y[2 * hx + 1], s23, xd[i].y)), ex[i].y);
                        if (!((sel >> (4 * J + i)) & 1u)) *(uint2*)(op + (size_t)(64 * (4 * J + i)) * D_) = o;
                    }
                }
            }
            if (lead) { TSTAMP(7); TSDUMP(0x3c000effu); }
        }
    } else if (pw < 4) {
        const int v = pw, at = tid;
        const int g = lane >> 2, t = lane & 3, mi = lane >> 3, r = lane & 7;
        const uint32_t alt = sb + (h ? ALT1 : ALT0), dalt = (h ? ALT1 : ALT0) + A_SLOT - ALT_SLOT * 4096;
        cp16(sb + OFF_GP + tid * 16, p.wr + tid * 8);
        cp16(sb + OFF_GP + 2048 + tid * 16, p.gatew + tid * 8);
        if (tid < 2) cp16(sb + M_DSK + tid * 16, p.Dskip + 16 * pr + 8 * tid);
        const unsigned epoch = ld_epoch(p.ex);
        const unsigned tag = (epoch + 1) & 0xffffu;
        const int ftok = 2 * ((at >> 2) & 3) + (at & 1), fch = (at >> 4) + 8 * ((at >> 1) & 1);
        {
            cp_wait_all();
            bar_sync(7, 160);
            const uint32_t wo = sb + OFF_GP + 512 * v + 64 * ((g >> 1) & 1) + 16 * t + 4 * (g & 1);
            uint32_t w0[4], w1[4];
            uint4 gw[4];
#pragma unroll
            for (int cb = 0; cb < 4; cb++) {
                w0[cb] = lds32(wo + 128 * cb); w1[cb] = lds32(wo + 128 * cb + 8);
                gw[cb] = lds128(sb + OFF_GP + 2048 + 512 * v + 128 * cb + 64 * (g & 1) + 16 * t);
            }
            const uint32_t ro = sb + M_RG + (g >> 1) * 32 + (2 * v + (g & 1)) * 4;
            const uint32_t xo = sb + OFF_RING + X_SLOT * 4096 + (g >> 1) * 2048 + 512 * v + 64 * (g & 1) + 16 * t;
            const uint32_t one0 = 0x3F803F80u ^ p.zero, one1 = 0x3F803F80u + p.zero;
            auto row_sum = [&](uint32_t a) {
                const uint4 x = lds128(a), y = lds128(a + 16);
                return ((__uint_as_float(x.x) + __uint_as_float(x.y)) + (__uint_as_float(x.z) + __uint_as_float(x.w)))
                     + ((__uint_as_float(y.x) + __uint_as_float(y.y)) + (__uint_as_float(y.z) + __uint_as_float(y.w)));
            };
#pragma unroll 1
            for (int i = 0; i < 4; i++) {
                mbar_spin(bars + 8 * (B_X + i));
                uint4 x[4];
#pragma unroll
                for (int cb = 0; cb < 4; cb++) x[cb] = lds128(xo + 8192 * i + 128 * cb);
                float d0[4] = {0.f, 0.f, 0.f, 0.f}, d1[4] = {0.f, 0.f, 0.f, 0.f};
#pragma unroll
                for (int cb = 0; cb < 4; cb++) mma_bf((cb & 1) ? d1 : d0, x[cb].x, x[cb].y, x[cb].z, x[cb].w, w0[cb], w1[cb]);
                if (t == (g & 1)) stsf(ro + 128 * i, (d0[0] + d0[3]) + (d1[0] + d1[3]));
                if (i == 3) {
                    bar_sync(4, 256);
                    if (at < 16) {
                        const uint32_t rb = pack_bf(0.f, row_sum(sb + M_RG + at * 32));
                        st_gpu32((uint32_t*)p.ex->r + 16 * c + at, ((rb ^ (((int)rb >> 31) | 0x80000000u)) & 0xffff0000u) | tag);
                    }
                    if (at == 32) mbar_arrive(bars + 8 * B_XF);
                    if (at == 0) TSTAMP(8);
                }
                float e0[4] = {0.f, 0.f, 0.f, 0.f}, e1[4] = {0.f, 0.f, 0.f, 0.f};
#pragma unroll
                for (int cb = 0; cb < 4; cb++)
                    mma_bf((cb & 1) ? e1 : e0, hmul2_bf(x[cb].x, gw[cb].x), hmul2_bf(x[cb].y, gw[cb].y), hmul2_bf(x[cb].z, gw[cb].z), hmul2_bf(x[cb].w, gw[cb].w), one0, one1);
                if (t == 0) stsf(ro + 512 + 128 * i, (e0[0] + e0[3]) + (e1[0] + e1[3]));
            }
            bar_sync(1, 128);
            if (at < 16) st_gpu32((uint32_t*)p.ex->g + 1024 * h + 16 * (8 * (pr & 7) + (pr >> 3)) + at,
                                  (pack_bf(sigmoid_f(bf_round(row_sum(sb + M_RG + 512 + at * 32))), 0.f) & 0xffffu) | (tag << 16));
            if (at == 0) TSTAMP(23);
        }
        mbar_wait(bars + 8 * B_TS);
#pragma unroll 1
        for (int i = 0; i < 2; i++) group_tables(sb + OFF_TAB + (v + 4 * i) * T_CH, lane);
        __syncwarp();
        if (lane == 0) mbar_arrive(bars + 8 * B_TD);
        const int ct = v & 1, kh = v >> 1;
        uint32_t wa[GU_PRE][4][4];
        uint32_t ta, tb;
        {
            const int krow0 = 8 * (mi >> 1) + r;
            const uint32_t off0 = krow0 * 64 + (((2 * ct + (mi & 1)) ^ ((krow0 >> 1) & 3)) << 4);
            ta = sb + OFF_RING + kh * 4096 + off0 + p.swap_gu; tb = ta + 2048 - 2 * p.swap_gu;
        }
        auto gu_load = [&](uint32_t (&a)[4][4], int s) {
            const uint32_t o = s * 8192 + (s > 10 ? -NSLOT * 4096 : s == 10 ? (kh ? -NSLOT * 4096 : dalt) : s == 9 ? dalt : s == 8 ? (kh ? dalt : 0) : 0);
            ldsm4t(ta + o, a[0][0], a[0][1], a[0][2], a[0][3]);
            ldsm4t(tb + o, a[1][0], a[1][1], a[1][2], a[1][3]);
            ldsm4t(ta + o + 1024, a[2][0], a[2][1], a[2][2], a[2][3]);
            ldsm4t(tb + o + 1024, a[3][0], a[3][1], a[3][2], a[3][3]);
        };
        auto gu_release = [&](const uint32_t (&a)[4][4], int s) {
            if (s < B_S - B_EMPTY && lane == 0) mbar_arrive(bars + 8 * (B_EMPTY + s) + (a[0][0] & a[1][0] & a[2][0] & a[3][0] & p.zero));
        };
        if (c < NGU_CTA) {
#pragma unroll
            for (int s = 0; s < GU_PRE; s++) { mbar_wait(bars + 8 * kh + 16 * s); gu_load(wa[s], s); gu_release(wa[s], s); }
        }
        if (c < NGU_CTA) {
            float dgt[4] = {0.f, 0.f, 0.f, 0.f}, dup[4] = {0.f, 0.f, 0.f, 0.f}, dg2[4] = {0.f, 0.f, 0.f, 0.f}, du2[4] = {0.f, 0.f, 0.f, 0.f};
            const uint32_t xo = sb + OFF_XSEL + r * XS_ROW + 64 * kh + 16 * mi;
            auto gu_mma = [&](const uint32_t (&a)[4][4], const uint32_t (&b)[4]) {
                mma_bf(dgt, a[0][0], a[0][1], a[0][2], a[0][3], b[0], b[1]);
                mma_bf(dup, a[1][0], a[1][1], a[1][2], a[1][3], b[0], b[1]);
                mma_bf(dg2, a[2][0], a[2][1], a[2][2], a[2][3], b[2], b[3]);
                mma_bf(du2, a[3][0], a[3][1], a[3][2], a[3][3], b[2], b[3]);
            };
            auto gu_batch = [&](auto S0, auto N) {
                constexpr int s0 = decltype(S0)::value, n = decltype(N)::value;
                uint32_t b[n][4];
                mbar_wait_n<n, 16>(bars + 8 * kh + 16 * s0);
#pragma unroll
                for (int i = 0; i < n; i++) { ldsm4(xo + 128 * (s0 + i), b[i][0], b[i][1], b[i][2], b[i][3]); gu_load(wa[i], s0 + i); }
#pragma unroll
                for (int i = 0; i < n; i++) gu_mma(wa[i], b[i]);
#pragma unroll
                for (int i = 0; i < n; i++) gu_release(wa[n - 1], s0 + i);
            };
            mbar_spin(bars + 8 * B_XS);
            if (at == 0) TSTAMP(12);
#pragma unroll
            for (int s = 0; s < GU_PRE; s++) { uint32_t b[4]; ldsm4(xo + 128 * s, b[0], b[1], b[2], b[3]); gu_mma(wa[s], b); }
            static_assert(GU_PRE == 6, "batches below");
            gu_batch(IC<6>(), IC<2>());
            mbar_spin(bars + 8 * (B_XS + 1));
            gu_batch(IC<8>(), IC<4>()); gu_batch(IC<12>(), IC<3>()); gu_batch(IC<15>(), IC<1>());
#pragma unroll
            for (int i = 0; i < 4; i++) { dgt[i] += dg2[i]; dup[i] += du2[i]; }
            if (at == 0) TSTAMP(13);
            bar_sync(1, 128);
            const uint32_t red = sb + OFF_XSEL;
            sts128(red + ((v ^ 2) * 32 + lane) * 16, __float_as_uint(kh ? dgt[0] : dgt[2]), __float_as_uint(kh ? dgt[1] : dgt[3]),
                   __float_as_uint(kh ? dup[0] : dup[2]), __float_as_uint(kh ? dup[1] : dup[3]));
            bar_sync(1, 128);
            const uint4 oth = lds128(red + at * 16);
#pragma unroll
            for (int i = 0; i < 2; i++) {
                const float gv = bf_round((kh ? dgt[2 + i] : dgt[i]) + __uint_as_float(i ? oth.y : oth.x));
                const float uv = bf_round((kh ? dup[2 + i] : dup[i]) + __uint_as_float(i ? oth.w : oth.z));
                const float sl = bf_round(gv * sigmoid_f(gv));
                uint32_t hv = pack_bf(sl * uv, 0.f) & 0xffffu;
                hv = (hv == 0x8000u) ? 0x8000u : (hv ^ 0x8000u);
                sts16(red + 4096 + (2 * t + i) * 64 + (g >> 1) * 16 + (2 * ct + kh) * 4 + (g & 1) * 2, hv);
            }
            bar_sync(1, 128);
            if (v == 0) st_gpu128(&p.ex->h[32 * c + lane], lds128(red + 4096 + lane * 16));
        }
        else mbar_wait(bars + 8 * (B_XS + 1));
        if (at == 0) TSTAMP(14);
        {
            uint32_t gv[8];
            bool ok = false;
#pragma unroll 1
            for (int it = 0; it < (1 << 22); it++) {
                const uint4 a = ld_gpu128(&p.ex->g[256 * h + at]), b = ld_gpu128(&p.ex->g[256 * h + 128 + at]);
                gv[0] = a.x; gv[1] = a.y; gv[2] = a.z; gv[3] = a.w; gv[4] = b.x; gv[5] = b.y; gv[6] = b.z; gv[7] = b.w;
                uint32_t bad = 0;
#pragma unroll
                for (int i = 0; i < 8; i++) bad |= gv[i] ^ (tag << 16);
                ok = (bad >> 16) == 0;
                if (ok) break;
                __nanosleep(64);
            }
            if (!ok) __trap();
#pragma unroll
            for (int i = 0; i < 8; i++) gv[i] = (gv[i] & 0xffffu) | (pack_bf(1.f - bf_lo(gv[i]), 0.f) << 16);
            sts128(sb + OFF_GP + at * 16, gv[0], gv[1], gv[2], gv[3]);
            sts128(sb + OFF_GP + (at + 128) * 16, gv[4], gv[5], gv[6], gv[7]);
            bar_sync(1, 128);
        }
        if (EPI_AT == 1) bar_arrive(2, 384);
        {
            uint4 hq[14];
            {
                const uint4* hsrc = &p.ex->h[(56 * h + 2 * v) * 32 + lane];
                bool ok = false;
                {
                    const int bi = lane < 14 ? lane : 0;
                    const uint4* pr1 = &p.ex->h[(56 * h + 2 * v + 8 * (bi >> 1) + (bi & 1)) * 32 + 31];
#pragma unroll 1
                    for (int it = 0; it < (1 << 22); it++) {
                        uint32_t w;
                        asm volatile("ld.relaxed.gpu.global.u32 %0, [%1];" : "=r"(w) : "l"(pr1) : "memory");
                        if (__all_sync(0xffffffffu, w != 0)) break;
                        __nanosleep(PSLEEP);
                    }
                }
                if (at == 0) TSTAMP(15);
                if (EPI_AT == 2) bar_arrive(2, 384);
#pragma unroll 1
                for (int it = 0; it < (1 << 22); it++) {
                    uint32_t mn = 0xffffffffu;
#pragma unroll
                    for (int i = 0; i < 14; i++) hq[i] = ld_gpu128(hsrc + (8 * (i >> 1) + (i & 1)) * 32);
                    mbar_wait(bars + 8 * B_SC);
                    mbar_wait_n<DN_PRE, 16>(bars + 8 * (B_FULL + NST_GU) + 8 * (v >> 1));
#pragma unroll
                    for (int i = 0; i < 14; i++) mn = min(mn, hq[i].x);
                    ok = __all_sync(0xffffffffu, mn != 0);
                    if (ok) break;
                    __nanosleep(20);
                }
                if (!ok) __trap();
            }
            if (at == 0) TSTAMP(16);
            if (EPI_AT == 3) bar_arrive(2, 384);
            float dd[4][4];
#pragma unroll
            for (int j = 0; j < 4; j++) { dd[j][0] = dd[j][1] = dd[j][2] = dd[j][3] = 0.f; }
            const int krow0 = 64 * (v & 1) + 8 * (mi >> 1) + r;
            const uint32_t td = sb + OFF_RING + (v >> 1) * 4096 + krow0 * 32 + (((mi & 1) ^ ((krow0 >> 2) & 1)) << 4);
            static_assert((NST_GU + 10) % NSLOT == 0, "stage pairs of the down projection do not straddle the end of the ring");
#pragma unroll
            for (int s = 0; s < 7; s++) {
                if (s >= DN_PRE) mbar_spin(bars + 8 * (B_FULL + NST_GU + 2 * s) + 8 * (v >> 1));
                const uint32_t tile = td + ((NST_GU + 2 * s) % NSLOT) * 4096 + ((NST_GU + 2 * s) % NSLOT >= ALT_SLOT ? dalt : 0);
                uint32_t a[4][4];
#pragma unroll
                for (int j = 0; j < 4; j++) ldsm4t(tile + j * 512, a[j][0], a[j][1], a[j][2], a[j][3]);
                mma_bf(dd[0], a[0][0], a[0][1], a[0][2], a[0][3], hq[2 * s].x, hq[2 * s].y);
                mma_bf(dd[1], a[1][0], a[1][1], a[1][2], a[1][3], hq[2 * s].z, hq[2 * s].w);
                mma_bf(dd[2], a[2][0], a[2][1], a[2][2], a[2][3], hq[2 * s + 1].x, hq[2 * s + 1].y);
                mma_bf(dd[3], a[3][0], a[3][1], a[3][2], a[3][3], hq[2 * s + 1].z, hq[2 * s + 1].w);
            }
            uint32_t ds[4];
#pragma unroll
            for (int j = 0; j < 4; j++) ds[j] = __float_as_uint((dd[0][j] + dd[1][j]) + (dd[2][j] + dd[3][j]));
            if (at == 0) TSTAMP(17);
#pragma unroll
            for (int k = 0; k < 2; k++) {
                const uint32_t o = mapa(sb, k);
                st_async16(o + OFF_DP + (128 * h + at) * 16, ds[0], ds[1], ds[2], ds[3], o + M_BARS + 8 * B_DP);
            }
            const int row = (int)lds32(sb + M_IDX + ftok * 4);
            const int w = row & 7, jj = (row >> 3) & 7, i = (row >> 6) & 15;
            const float xv = bf_lo(lds16(sb + OFF_S + (row >> 5) * 1024 + w * 128 + (jj & 3) * 32 + (((fch >> 3) ^ (w & 1)) << 4) + (fch & 7) * 2));
            const uint32_t gp = lds32(sb + OFF_GP + (8 * w + jj) * 64 + i * 4);
            const float rs = bf_round(sigmoid_f(ldsf(sb + M_RSEL + ftok * 4)));
            mbar_wait_n<4, 8>(bars + 8 * B_Y);
            const float yv = bf_lo(lds16((((fch >> 3) == h) ? sb + OFF_TAB + (fch & 7) * T_CH : alt + A_YIN + (fch & 7) * Y_CH) + (i >> 2) * 512 + (4 * w + (i & 3)) * 16 + jj * 2));
            const float a = bf_round(fmaf(yv, bf_lo(lds32(sb + M_SC + fch * 4)), bf_round(xv * bf_lo(lds16(sb + M_DSK + 2 * fch)))));
            const float ga = bf_round(bf_lo(gp) * a);
            mbar_spin(bars + 8 * B_DP);
            float tot = 0.f;
#pragma unroll
            for (int k = 0; k < 8; k++) tot -= ldsf(sb + OFF_DP + k * 512 + at * 4);
            if ((row >> 10) == h) {
                const float b = bf_round(xv + bf_round(bf_round(tot) * rs));
                p.out[(size_t)row * D_ + 16 * pr + fch] = __float2bfloat16_rn(ga + bf_round(bf_hi(gp) * b));
            }
        }
        if (at == 0) { TSTAMP(18); TSDUMP(c < NGU_CTA ? 0x0087f100u : 0x0087c100u); if (c == 0) *(volatile unsigned*)&p.ex->epoch = epoch + 1; }
    } else {
        const uint32_t t_start = now_ns();
        asm volatile("setmaxnreg.dec.sync.aligned.u32 " HELP_REGS ";");
        if (pw != 12) {
            if (pw >= 14) {
#pragma unroll
                for (int k = 0; k < 5; k++) {
                    const int w = 1 + 2 * k, e = (tid & 63) - 32;
                    sts32(sb + OFF_BAND + k * 256 + (tid & 63) * 4, ((e >= 0 && e < w) ? 0x3C00u : 0u) | ((e + 1 >= 0 && e + 1 < w) ? 0x3C000000u : 0u));
                }
                if (tid < 14 * 32 + 24) sts128(sb + OFF_S - 384 + lane * 16, 0, 0, 0, 0);
            } else {
                sts32(sb + M_BMAP + lane * 4, 0);
                if (c < NGU_CTA) {
                    st_gpu128(&p.ex->h[32 * c + lane], make_uint4(0, 0, 0, 0));
                    if (ld_gpu128(&p.ex->h[32 * c + lane]).x != 0) __trap();
                }
            }
            bar_arrive(5, 384);
        } else {
            if (lane == 0) {
#pragma unroll
                for (int k = B_S; k < NBAR; k++) mbar_init(bars + 8 * k, (k >= B_Y && k < B_MX) ? 9 : (k == B_MX || k == B_TS) ? 8 : k == B_TD ? 4 : k == B_XS + 1 ? 2 : 1);
#pragma unroll
                for (int k = B_S; k < B_XS; k++) mbar_expect(bars + 8 * k, 16384);
                asm volatile("fence.proxy.async.shared::cta;" ::: "memory");
                asm volatile("fence.mbarrier_init.release.cluster;" ::: "memory");
            }
            __syncwarp();
            asm volatile("barrier.cluster.arrive.relaxed.aligned;" ::: "memory");
            auto rows = [&](int i) {
                if (X_MODE == 1) return;
                mbar_expect(bars + 8 * (B_X + i), 8192);
                tma4d(sb + OFF_RING + X_SLOT * 4096 + i * 8192, &tm_r, 0, 0, 16 * h + 4 * i, pr, bars + 8 * (B_X + i));
            };
            if (lane == 0) {
                asm volatile("prefetch.tensormap [%0];" :: "l"(&tm_x) : "memory");
#pragma unroll 1
                for (int i = 0; i < X_LEAD; i++) rows(i);
            }
            __syncwarp();
            bar_arrive(5, 384);
            bar_arrive(7, 160);
            asm volatile("barrier.cluster.wait.acquire.aligned;" ::: "memory");
            if (lane == 0) {
                TSTAMP(20);
#pragma unroll 1
                for (int i = 0; i < 4; i++) {
                    tma4d_both(sb + OFF_S + (4 * h + i) * 8192, &tm_x, 16 * pr, 0, 0, 32 * h + 8 * i, bars + 8 * (B_S + i));
                    if (i + X_LEAD < 4) rows(i + X_LEAD);
                }
                TSTAMP(24);
                asm volatile("prefetch.tensormap [%0];" :: "l"(&tm_gu) : "memory");
                asm volatile("prefetch.tensormap [%0];" :: "l"(&tm_down) : "memory");
#pragma unroll
                for (int k = 0; k < B_S; k++) mbar_init(bars + 8 * k, k < B_EMPTY ? 1 : 4);
#pragma unroll
                for (int k = B_XS; k < B_MX; k++) if (k != B_TD) mbar_expect(bars + 8 * k, k < B_TD ? (c < NGU_CTA ? 8192 : 0) : k == B_SC ? 64 : 4096);
                asm volatile("fence.proxy.async.shared::cta;" ::: "memory");
            }
            __syncwarp();
        }
        bar_arrive(4, 256);
        bar_sync(6, 128);
        if (pw == 15) {
            const unsigned tag = (ld_epoch(p.ex) + 1) & 0xffffu;
            const int tok = lane & 7;
            uint32_t top = 0;
            bool ok = false;
            mbar_wait(bars + 8 * B_XF);
#pragma unroll 1
            for (int it = 0; it < (1 << 22); it++) {
                uint32_t tg;
                asm volatile("ld.relaxed.gpu.global.v2.u32 {%0,%1}, [%2];" : "=r"(top), "=r"(tg) : "l"(&p.ex->top[tok]) : "memory");
                ok = __all_sync(0xffffffffu, tg == tag);
                if (ok) break;
            }
            if (!ok) __trap();
            if (lane == 0) TSTAMP(25);
            const int row = 2047 - (int)(top & 0xffffu);
            if (c < NGU_CTA) {
#pragma unroll
                for (int k = 0; k < 8; k++) {
                    const int tk = 4 * h + ((k + pr) & 3), hf = k >> 2;
                    bulk_load_both(sb + OFF_XSEL + tk * XS_ROW + 1024 * hf, p.u + (size_t)__shfl_sync(0xffffffffu, row, tk) * D_ + 512 * hf, 1024, bars + 8 * (B_XS + hf));
                }
            }
            if (lane == 0) TSTAMP(21);
            if (lane < 8) {
                const uint32_t ord = top >> 16;
                sts32(sb + M_RSEL + tok * 4, ((ord & 0x8000u) ? (ord & 0x7fffu) : (~ord & 0xffffu)) << 16);
                sts32(sb + M_IDX + tok * 4, (uint32_t)row);
                if ((row >> 10) == h) asm volatile("red.shared.or.b32 [%0], %1;" :: "r"(sb + M_BMAP + (row & 7) * 16 + ((row >> 4) & 3) * 4),
                                                   "r"(1u << (((row >> 6) & 15) + 2 * (row & 8))) : "memory");
            }
            __syncwarp();
            if (lane == 0) { mbar_arrive(bars + 8 * (B_XS + 1)); TSDUMP(0x02200000u); }
            return;
        }
        if (lane != 0) return;
        const int s0 = c < NGU_CTA ? 0 : NST_GU;
        if (T_W == 0) mbar_wait(bars + 8 * (B_S + W_START));
        if (pw == 12) TSTAMP(22);
#pragma unroll 1
        for (int s = s0 + pw - 12; s < NST; s += 3) {
            const int slot = s < NSLOT ? s : s < 2 * NSLOT ? s - NSLOT : s - 2 * NSLOT;
            const uint32_t full = bars + 8 * (B_FULL + s), dst = sb + OFF_RING + slot * 4096 + (slot >= ALT_SLOT ? (h ? ALT1 : ALT0) + A_SLOT - ALT_SLOT * 4096 : 0);
            if (s >= X_SLOT) mbar_wait(bars + 8 * ((s >= s0 + NSLOT) ? B_EMPTY + ((s - NSLOT) >> 1) : slot >= ALT_SLOT ? B_MX : B_XF));
            mbar_expect(full, 4096);
            if (T_W > 0) {
                const uint32_t due = T_W + DT_G * s + (s > NST_GU ? (DT_D - DT_G) * (s - NST_GU) : 0);
#pragma unroll 1
                for (int n = 0; n < 100000; n++) {
                    const int left = (int)(due - (now_ns() - t_start));
                    if (left <= 0) break;
                    __nanosleep(left > 100 ? left >> 1 : 20);
                }
            }
            if (s < NST_GU) {
                if (s >= DEPTH_E) mbar_spin(full - 8 * (s < EARLY ? DEPTH_E : DEPTH));
                tma3d(dst, &tm_gu, 32 * c, 32 * s, 0, full);
            } else {
                if (s >= s0 + DEPTH_D) mbar_spin(full - 8 * DEPTH_D);

                tma2d(dst, &tm_down, 16 * pr, 1792 * h + 128 * (s - NST_GU), full);
            }
        }
        if (pw == 12) TSDUMP(0x01500000u);
    }
}

typedef CUresult (*EncodeFn)(CUtensorMap*, CUtensorMapDataType, cuuint32_t, void*, const cuuint64_t*, const cuuint64_t*,
                             const cuuint32_t*, const cuuint32_t*, CUtensorMapInterleave, CUtensorMapSwizzle,
                             CUtensorMapL2promotion, CUtensorMapFloatOOBfill);

void make_map(EncodeFn f, CUtensorMap* m, const void* ptr, int rank, const cuuint64_t* dims, const cuuint64_t* strides, const cuuint32_t* box, CUtensorMapSwizzle sw,
              CUtensorMapL2promotion promo = CU_TENSOR_MAP_L2_PROMOTION_L2_128B) {
    const cuuint32_t es[4] = {1, 1, 1, 1};
    f(m, CU_TENSOR_MAP_DATA_TYPE_BFLOAT16, rank, (void*)ptr, dims, strides, box, es, CU_TENSOR_MAP_INTERLEAVE_NONE, sw,
      promo, CU_TENSOR_MAP_FLOAT_OOB_FILL_NONE);
}

}

extern "C" void kernel_launch(void* const* d_in, const int* in_sizes, int n_in, void* d_out, int out_size) {
    static EncodeFn enc = nullptr;
    static void* ex = nullptr;
    if (!enc) {
        void* fn = nullptr;
        cudaDriverEntryPointQueryResult qr;
        cudaGetDriverEntryPoint("cuTensorMapEncodeTiled", &fn, cudaEnableDefault, &qr);
        enc = (EncodeFn)fn;
        cudaFuncSetAttribute(fused_kernel, cudaFuncAttributeMaxDynamicSharedMemorySize, SMEM_LAUNCH);
        cudaGetSymbolAddress(&ex, g_ex);
    }
    CUtensorMap tgu, td, tx, tr;
    const char *wg = (const char*)d_in[9], *wu = (const char*)d_in[10];
    const bool swap = wu < wg;
    {
        const cuuint64_t dims[3] = {F_, D_, 2}, str[2] = {F_ * 2, (cuuint64_t)(swap ? wg - wu : wu - wg)};
        const cuuint32_t box[3] = {32, 32, 2};
        make_map(enc, &tgu, swap ? wu : wg, 3, dims, str, box, CU_TENSOR_MAP_SWIZZLE_64B);
    }
    {
        const cuuint64_t dims[2] = {D_, F_}, str[1] = {D_ * 2};
        const cuuint32_t box[2] = {16, 128};
        make_map(enc, &td, d_in[11], 2, dims, str, box, CU_TENSOR_MAP_SWIZZLE_32B, PROMO_D);
    }
    {
        const cuuint64_t dims[4] = {D_, 4, 8, L_ / 32}, str[3] = {D_ * 2 * 8, D_ * 2, D_ * 2 * 32};
        const cuuint32_t box[4] = {16, 4, 8, 8};
        make_map(enc, &tx, d_in[0], 4, dims, str, box, CU_TENSOR_MAP_SWIZZLE_32B);
    }
    {
        const cuuint64_t dims[4] = {256, 4, L_ / 64, 64}, str[3] = {512, D_ * 2 * 64, D_ * 2};
        const cuuint32_t box[4] = {256, 4, 4, 1};
        make_map(enc, &tr, d_in[0], 4, dims, str, box, CU_TENSOR_MAP_SWIZZLE_NONE);
    }
    Params p;
    p.u = (const bf16*)d_in[0]; p.logA = (const bf16*)d_in[1]; p.Aim = (const bf16*)d_in[2];
    p.Cre = (const bf16*)d_in[3]; p.Cim = (const bf16*)d_in[4]; p.logdt = (const bf16*)d_in[5];
    p.Dskip = (const bf16*)d_in[6]; p.wr = (const bf16*)d_in[8]; p.gatew = (const bf16*)d_in[12];
    p.out = (bf16*)d_out;
    p.ex = (Exchange*)ex;
    p.zero = 0;
    p.swap_gu = swap ? 2048 : 0;
    fused_kernel<<<NCTA, NTHREADS, SMEM_LAUNCH>>>(p, tgu, td, tx, tr);
}
```

```cpp
#include <cuda_runtime.h>
#include <cuda_bf16.h>
#include <cuda_fp16.h>
#include <cuda.h>
#include <stdint.h>

typedef __nv_bfloat16 bf16;

namespace {

constexpr int L_ = 2048, D_ = 1024, F_ = 3584;
constexpr int NCTA = 130;
constexpr int NTHREADS = 512;
constexpr int MAIN_W0 = 4;
#define DEPTH 10
#define DEPTH_D 5
#define W_START 1
#define PSLEEP 40
#define GU_UNROLL 16
#define KS_UNROLL 4
#define START_MODE 0
#define X_DELAY 0
#define LDX_HINT ""
#define X_BATCH 16
#define EPI_AT 0
#define X_LEAD 1
#define GU_PRE 6
#define GU_BATCH 0
#define DN_PRE 5
#define DEPTH_E DEPTH
#define EARLY 20
#define NPOLL 1
#define X_MODE 0
#define WARM_TLB 0
#define T_W 1600
#define DT_G 158
#define DT_D 172
#define FENCES 16
#define XS_MODE 0
#define REMAP 1
#define PROMO_D CU_TENSOR_MAP_L2_PROMOTION_L2_128B
#define PUB_ATOM 0
#define KG_LOOP 0
#define RG_LOOP 0
#define W_SQ 2
#define H_WAIT 2
#define KEEP_LIVE 0
#define MAIN_REGS "176"
#define HELP_REGS "24"
constexpr int NGU_CTA = 112;

constexpr int NSLOT    = 21;
constexpr int NST_GU   = 32, NST = 46;
constexpr int OFF_RING = 0;
constexpr int OFF_XSEL = 69632, XS_ROW = 2064;
constexpr int OFF_DP   = OFF_XSEL + 8192;
constexpr int OFF_S    = 87040;
constexpr int ALT0     = OFF_S + 32768, ALT1 = OFF_S - 512;
constexpr int A_YIN    = 32, Y_CH = 2064;
constexpr int A_SLOT   = 16896, ALT_SLOT = 17;
constexpr int U_PL     = 1184;
constexpr int U_CH     = 4752;
constexpr int OFF_U    = 153088;
constexpr int T_CH     = 4112;
constexpr int OFF_TAB  = 191104;
constexpr int T_R2     = 2176, T2_S = 208;
constexpr int T_R3     = 3040, T3_S = 336;
constexpr int OFF_GP   = 224000;
constexpr int OFF_BAND = 228096;
constexpr int OFF_MISC = 229376;
constexpr int M_BARS   = OFF_MISC;
constexpr int M_DSK    = OFF_MISC + 672;
constexpr int M_IDX    = OFF_MISC + 704;
constexpr int M_RSEL   = OFF_MISC + 736;
constexpr int M_BMAP   = OFF_MISC + 768;
constexpr int M_MX     = OFF_MISC + 896;
constexpr int M_SC     = OFF_MISC + 960;
constexpr int M_RG     = OFF_MISC + 1024;
constexpr int SMEM_BYTES = OFF_MISC + 3072;

constexpr int B_FULL = 0, B_EMPTY = NST, B_S = B_EMPTY + (NST - NSLOT + 1) / 2, B_XS = B_S + 4, B_TD = B_XS + 2, B_SC = B_TD + 1, B_G = B_SC + 1, B_DP = B_G + 1, B_Y = B_DP + 1,
              B_KD = B_Y + 4, B_U = B_KD + 1, B_TS = B_U + 1, B_XF = B_TS + 1, B_X = B_XF + 1, NBAR = B_X + 4;
constexpr int X_SLOT = 13;
static_assert(NBAR <= 84, "barrier area");

struct Exchange {
    unsigned epoch, pad[31];
    uint4 h[8 * F_ / 8];
    uint4 r[L_ / 4];
    uint4 g[L_ / 4];
    uint2 top[16];
};
__device__ __align__(128) Exchange g_ex;

struct Params {
    const bf16 *u, *logA, *Aim, *Cre, *Cim, *logdt, *Dskip, *wr, *gatew;
    bf16* out;
    Exchange* ex;
    uint32_t zero;
    uint32_t swap_gu;
};

#define TSTAMP(i) do {} while (0)
#define CSTAMP(i) do {} while (0)
#define TSDUMP(mask) do {} while (0)
#define DBG_PARAMS
#define DBG_ARGS

__device__ __forceinline__ uint32_t smem_u32(const void* p) { return (uint32_t)__cvta_generic_to_shared(p); }
__device__ __forceinline__ void mbar_init(uint32_t b, uint32_t c) { asm volatile("mbarrier.init.shared::cta.b64 [%0], %1;" :: "r"(b), "r"(c) : "memory"); }
__device__ __forceinline__ void mbar_expect(uint32_t b, uint32_t tx) { asm volatile("mbarrier.arrive.expect_tx.shared::cta.b64 _, [%0], %1;" :: "r"(b), "r"(tx) : "memory"); }
__device__ __forceinline__ void mbar_arrive(uint32_t b) { asm volatile("mbarrier.arrive.shared::cta.b64 _, [%0];" :: "r"(b) : "memory"); }
#define WSLEEP "40"
__device__ __forceinline__ void mbar_wait(uint32_t b) {
    asm volatile("{\n\t.reg .pred p, q;\n\t.reg .u32 n;\n\tmov.u32 n, 0;\n"
                 "W%=:\n\tmbarrier.try_wait.parity.shared::cta.b64 p, [%0], 0;\n\t"
                 "@p bra D%=;\n\tnanosleep.u32 " WSLEEP ";\n\tadd.u32 n, n, 1;\n\tsetp.lt.u32 q, n, 4194304;\n\t@q bra W%=;\n"
                 "D%=:\n\t}" :: "r"(b) : "memory");
}
__device__ __forceinline__ void mbar_spin(uint32_t b) {
    asm volatile("{\n\t.reg .pred p, q;\n\t.reg .u32 n;\n\tmov.u32 n, 0;\n"
                 "W%=:\n\tmbarrier.try_wait.parity.shared::cta.b64 p, [%0], 0;\n\t"
                 "@p bra D%=;\n\tadd.u32 n, n, 1;\n\tsetp.lt.u32 q, n, 4194304;\n\t@q bra W%=;\n"
                 "D%=:\n\t}" :: "r"(b) : "memory");
}
template <int N, int STEP>
__device__ __forceinline__ void mbar_wait_n(uint32_t b) {
#pragma unroll 1
    for (int n = 0; n < 4194304; n++) {
        uint32_t ok = 1;
#pragma unroll
        for (int i = 0; i < N; i++) {
            uint32_t d;
            asm volatile("{ .reg .pred p; mbarrier.try_wait.parity.shared::cta.b64 p, [%1], 0; selp.u32 %0, 1, 0, p; }" : "=r"(d) : "r"(b + STEP * i) : "memory");
            ok &= d;
        }
        if (ok) break;
    }
}
__device__ __forceinline__ unsigned ld_epoch(const Exchange* e) { unsigned v; asm volatile("ld.volatile.global.u32 %0, [%1];" : "=r"(v) : "l"(e) : "memory"); return v; }
__device__ __forceinline__ uint32_t now_ns() { uint32_t t; asm volatile("mov.u32 %0, %globaltimer_lo;" : "=r"(t)); return t; }
__device__ __forceinline__ uint32_t mapa(uint32_t addr, uint32_t rank) { uint32_t r; asm("mapa.shared::cluster.u32 %0, %1, %2;" : "=r"(r) : "r"(addr), "r"(rank)); return r; }
__device__ __forceinline__ void bulk_load(uint32_t dst, const void* src, uint32_t bytes, uint32_t bar) {
    asm volatile("cp.async.bulk.shared::cluster.global.mbarrier::complete_tx::bytes [%0], [%1], %2, [%3];" :: "r"(dst), "l"(src), "r"(bytes), "r"(bar) : "memory");
}
__device__ __forceinline__ void bulk_load_both(uint32_t dst, const void* src, uint32_t bytes, uint32_t bar) {
    asm volatile("{ .reg .pred p; elect.sync _|p, 0xffffffff;\n\t@p cp.async.bulk.shared::cluster.global.mbarrier::complete_tx::bytes.multicast::cluster [%0], [%1], %2, [%3], %4; }"
                 :: "r"(dst), "l"(src), "r"(bytes), "r"(bar), "h"((unsigned short)3) : "memory");
}
__device__ __forceinline__ void tma2d(uint32_t dst, const CUtensorMap* tm, int c0, int c1, uint32_t bar) {
    asm volatile("cp.async.bulk.tensor.2d.shared::cluster.global.mbarrier::complete_tx::bytes [%0], [%1, {%3, %4}], [%2];"
        :: "r"(dst), "l"(tm), "r"(bar), "r"(c0), "r"(c1) : "memory");
}
__device__ __forceinline__ void tma3d(uint32_t dst, const CUtensorMap* tm, int c0, int c1, int c2, uint32_t bar) {
    asm volatile("cp.async.bulk.tensor.3d.shared::cluster.global.mbarrier::complete_tx::bytes [%0], [%1, {%3, %4, %5}], [%2];"
        :: "r"(dst), "l"(tm), "r"(bar), "r"(c0), "r"(c1), "r"(c2) : "memory");
}
__device__ __forceinline__ void tma4d(uint32_t dst, const CUtensorMap* tm, int c0, int c1, int c2, int c3, uint32_t bar) {
    asm volatile("cp.async.bulk.tensor.4d.shared::cluster.global.mbarrier::complete_tx::bytes [%0], [%1, {%3, %4, %5, %6}], [%2];"
        :: "r"(dst), "l"(tm), "r"(bar), "r"(c0), "r"(c1), "r"(c2), "r"(c3) : "memory");
}
__device__ __forceinline__ void tma4d_both(uint32_t dst, const CUtensorMap* tm, int c0, int c1, int c2, int c3, uint32_t bar) {
    asm volatile("cp.async.bulk.tensor.4d.shared::cluster.global.mbarrier::complete_tx::bytes.multicast::cluster [%0], [%1, {%3, %4, %5, %6}], [%2], %7;"
        :: "r"(dst), "l"(tm), "r"(bar), "r"(c0), "r"(c1), "r"(c2), "r"(c3), "h"((unsigned short)3) : "memory");
}
__device__ __forceinline__ void st_async16(uint32_t dst, uint32_t x, uint32_t y, uint32_t z, uint32_t w, uint32_t bar) {
    asm volatile("st.async.weak.shared::cluster.mbarrier::complete_tx::bytes.v4.b32 [%0], {%1,%2,%3,%4}, [%5];"
                 :: "r"(dst), "r"(x), "r"(y), "r"(z), "r"(w), "r"(bar) : "memory");
}
__device__ __forceinline__ void st_async4(uint32_t dst, uint32_t v, uint32_t bar) {
    asm volatile("st.async.weak.shared::cluster.mbarrier::complete_tx::bytes.b32 [%0], %1, [%2];" :: "r"(dst), "r"(v), "r"(bar) : "memory");
}
__device__ __forceinline__ void bar_sync(int id, int n) { asm volatile("bar.sync %0, %1;" :: "r"(id), "r"(n) : "memory"); }
__device__ __forceinline__ void bar_arrive(int id, int n) { asm volatile("bar.arrive %0, %1;" :: "r"(id), "r"(n) : "memory"); }
__device__ __forceinline__ void cp16(uint32_t dst, const void* src) { asm volatile("cp.async.cg.shared.global [%0], [%1], 16;" :: "r"(dst), "l"(src) : "memory"); }
__device__ __forceinline__ void cp_wait_all() { asm volatile("cp.async.wait_all;" ::: "memory"); }
__device__ __forceinline__ uint32_t ldg16(const void* p) { uint32_t v; asm volatile("ld.global.nc.u16 %0, [%1];" : "=r"(v) : "l"(p)); return v; }
__device__ __forceinline__ uint2 ldg64(const void* p) { uint2 v; asm volatile("ld.global.nc.v2.u32 {%0,%1}, [%2];" : "=r"(v.x), "=r"(v.y) : "l"(p)); return v; }
__device__ __forceinline__ uint4 ldg128(const void* p) { uint4 v; asm volatile("ld.global.nc" LDX_HINT ".v4.u32 {%0,%1,%2,%3}, [%4];" : "=r"(v.x), "=r"(v.y), "=r"(v.z), "=r"(v.w) : "l"(p)); return v; }
__device__ __forceinline__ uint4 ld_gpu128(const void* p) { uint4 v; asm volatile("ld.relaxed.gpu.global.v4.u32 {%0,%1,%2,%3}, [%4];" : "=r"(v.x), "=r"(v.y), "=r"(v.z), "=r"(v.w) : "l"(p) : "memory"); return v; }
__device__ __forceinline__ void st_gpu32(void* p, uint32_t v) { asm volatile("st.relaxed.gpu.global.u32 [%0], %1;" :: "l"(p), "r"(v) : "memory"); }
__device__ __forceinline__ void st_gpu128(void* p, const uint4& v) { asm volatile("st.relaxed.gpu.global.v4.u32 [%0], {%1,%2,%3,%4};" :: "l"(p), "r"(v.x), "r"(v.y), "r"(v.z), "r"(v.w) : "memory"); }

__device__ __forceinline__ void ldsm4(uint32_t a, uint32_t& r0, uint32_t& r1, uint32_t& r2, uint32_t& r3) {
    asm volatile("ldmatrix.sync.aligned.m8n8.x4.shared.b16 {%0,%1,%2,%3}, [%4];" : "=r"(r0), "=r"(r1), "=r"(r2), "=r"(r3) : "r"(a) : "memory");
}
__device__ __forceinline__ void ldsm2(uint32_t a, uint32_t& r0, uint32_t& r1) {
    asm volatile("ldmatrix.sync.aligned.m8n8.x2.shared.b16 {%0,%1}, [%2];" : "=r"(r0), "=r"(r1) : "r"(a) : "memory");
}
__device__ __forceinline__ void ldsm4t(uint32_t a, uint32_t& r0, uint32_t& r1, uint32_t& r2, uint32_t& r3) {
    asm volatile("ldmatrix.sync.aligned.m8n8.x4.trans.shared.b16 {%0,%1,%2,%3}, [%4];" : "=r"(r0), "=r"(r1), "=r"(r2), "=r"(r3) : "r"(a) : "memory");
}
__device__ __forceinline__ uint32_t lds16(uint32_t a) { uint32_t v; asm volatile("ld.shared.u16 %0, [%1];" : "=r"(v) : "r"(a) : "memory"); return v; }
__device__ __forceinline__ uint32_t lds32(uint32_t a) { uint32_t v; asm volatile("ld.shared.u32 %0, [%1];" : "=r"(v) : "r"(a) : "memory"); return v; }
__device__ __forceinline__ uint2 lds64(uint32_t a) { uint2 v; asm volatile("ld.shared.v2.u32 {%0,%1}, [%2];" : "=r"(v.x), "=r"(v.y) : "r"(a) : "memory"); return v; }
__device__ __forceinline__ uint4 lds128(uint32_t a) { uint4 v; asm volatile("ld.shared.v4.u32 {%0,%1,%2,%3}, [%4];" : "=r"(v.x), "=r"(v.y), "=r"(v.z), "=r"(v.w) : "r"(a) : "memory"); return v; }
__device__ __forceinline__ void sts16(uint32_t a, uint32_t v) { asm volatile("st.shared.u16 [%0], %1;" :: "r"(a), "r"(v) : "memory"); }
__device__ __forceinline__ void sts32(uint32_t a, uint32_t v) { asm volatile("st.shared.u32 [%0], %1;" :: "r"(a), "r"(v) : "memory"); }
__device__ __forceinline__ void sts64(uint32_t a, uint32_t x, uint32_t y) { asm volatile("st.shared.v2.u32 [%0], {%1,%2};" :: "r"(a), "r"(x), "r"(y) : "memory"); }
__device__ __forceinline__ void sts128(uint32_t a, uint32_t x, uint32_t y, uint32_t z, uint32_t w) { asm volatile("st.shared.v4.u32 [%0], {%1,%2,%3,%4};" :: "r"(a), "r"(x), "r"(y), "r"(z), "r"(w) : "memory"); }
__device__ __forceinline__ void sts16_if(bool p, uint32_t a, uint32_t v) { asm volatile("{ .reg .pred q; setp.ne.u32 q, %2, 0; @q st.shared.u16 [%0], %1; }" :: "r"(a), "h"((unsigned short)v), "r"((uint32_t)p) : "memory"); }
__device__ __forceinline__ void sts128_if(bool p, uint32_t a, uint32_t x, uint32_t y, uint32_t z, uint32_t w) {
    asm volatile("{ .reg .pred q; setp.ne.u32 q, %5, 0; @q st.shared.v4.u32 [%0], {%1,%2,%3,%4}; }" :: "r"(a), "r"(x), "r"(y), "r"(z), "r"(w), "r"((uint32_t)p) : "memory");
}
__device__ __forceinline__ void stsf(uint32_t a, float v) { asm volatile("st.shared.f32 [%0], %1;" :: "r"(a), "f"(v) : "memory"); }
__device__ __forceinline__ float ldsf(uint32_t a) { float v; asm volatile("ld.shared.f32 %0, [%1];" : "=f"(v) : "r"(a) : "memory"); return v; }

__device__ __forceinline__ void mma_bf(float (&d)[4], uint32_t a0, uint32_t a1, uint32_t a2, uint32_t a3, uint32_t b0, uint32_t b1) {
    asm volatile("mma.sync.aligned.m16n8k16.row.col.f32.bf16.bf16.f32 {%0,%1,%2,%3}, {%4,%5,%6,%7}, {%8,%9}, {%0,%1,%2,%3};"
        : "+f"(d[0]), "+f"(d[1]), "+f"(d[2]), "+f"(d[3]) : "r"(a0), "r"(a1), "r"(a2), "r"(a3), "r"(b0), "r"(b1));
}
__device__ __forceinline__ void widen_bf(float (&d)[4], uint32_t a0, uint32_t a1, uint32_t b) {
    asm volatile("mma.sync.aligned.m16n8k8.row.col.f32.bf16.bf16.f32 {%0,%1,%2,%3}, {%4,%5}, {%6}, {%7,%7,%7,%7};"
        : "=f"(d[0]), "=f"(d[1]), "=f"(d[2]), "=f"(d[3]) : "r"(a0), "r"(a1), "r"(b), "f"(0.f));
}
__device__ __forceinline__ void widen_h(float (&d)[4], const uint32_t (&a)[2], uint32_t b) {
    asm volatile("mma.sync.aligned.m16n8k8.row.col.f32.f16.f16.f32 {%0,%1,%2,%3}, {%4,%5}, {%6}, {%7,%7,%7,%7};"
        : "=f"(d[0]), "=f"(d[1]), "=f"(d[2]), "=f"(d[3]) : "r"(a[0]), "r"(a[1]), "r"(b), "f"(0.f));
}
__device__ __forceinline__ void widen_add_h(float (&d)[4], const uint32_t (&a)[2], uint32_t b, const float (&c)[4]) {
    asm volatile("mma.sync.aligned.m16n8k8.row.col.f32.f16.f16.f32 {%0,%1,%2,%3}, {%4,%5}, {%6}, {%7,%8,%9,%10};"
        : "=f"(d[0]), "=f"(d[1]), "=f"(d[2]), "=f"(d[3]) : "r"(a[0]), "r"(a[1]), "r"(b), "f"(c[0]), "f"(c[1]), "f"(c[2]), "f"(c[3]));
}
__device__ __forceinline__ void mma_h(uint32_t (&d)[2], const uint32_t (&a)[4], uint32_t b0, uint32_t b1) {
    asm volatile("mma.sync.aligned.m16n8k16.row.col.f16.f16.f16.f16 {%0,%1}, {%2,%3,%4,%5}, {%6,%7}, {%0,%1};"
        : "+r"(d[0]), "+r"(d[1]) : "r"(a[0]), "r"(a[1]), "r"(a[2]), "r"(a[3]), "r"(b0), "r"(b1));
}
__device__ __forceinline__ void mma_h_z(uint32_t& d0, uint32_t& d1, const uint32_t (&a)[4], uint32_t b0, uint32_t b1) {
    asm volatile("mma.sync.aligned.m16n8k16.row.col.f16.f16.f16.f16 {%0,%1}, {%2,%3,%4,%5}, {%6,%7}, {%8,%8};"
        : "=r"(d0), "=r"(d1) : "r"(a[0]), "r"(a[1]), "r"(a[2]), "r"(a[3]), "r"(b0), "r"(b1), "r"(0u));
}
__device__ __forceinline__ void mma_h2(uint32_t& d0, uint32_t& d1, const uint32_t (&a)[4], uint32_t b0, uint32_t b1) {
    asm volatile("mma.sync.aligned.m16n8k16.row.col.f16.f16.f16.f16 {%0,%1}, {%2,%3,%4,%5}, {%6,%7}, {%0,%1};"
        : "+r"(d0), "+r"(d1) : "r"(a[0]), "r"(a[1]), "r"(a[2]), "r"(a[3]), "r"(b0), "r"(b1));
}
__device__ __forceinline__ void mma_h_k8(uint32_t& d0, uint32_t& d1, uint32_t a0, uint32_t a1, uint32_t b) {
    asm volatile("mma.sync.aligned.m16n8k8.row.col.f16.f16.f16.f16 {%0,%1}, {%2,%3}, {%4}, {%0,%1};" : "+r"(d0), "+r"(d1) : "r"(a0), "r"(a1), "r"(b));
}
__device__ __forceinline__ void mma_h_k8_z(uint32_t (&d)[2], uint32_t a0, uint32_t a1, uint32_t b) {
    asm volatile("mma.sync.aligned.m16n8k8.row.col.f16.f16.f16.f16 {%0,%1}, {%2,%3}, {%4}, {%5,%5};" : "=r"(d[0]), "=r"(d[1]) : "r"(a0), "r"(a1), "r"(b), "r"(0u));
}
__device__ __forceinline__ uint32_t pack_bf(float lo, float hi) { uint32_t r; asm("cvt.rn.bf16x2.f32 %0, %1, %2;" : "=r"(r) : "f"(hi), "f"(lo)); return r; }
__device__ __forceinline__ uint32_t pack_h(float lo, float hi) { uint32_t r; asm("cvt.rn.f16x2.f32 %0, %1, %2;" : "=r"(r) : "f"(hi), "f"(lo)); return r; }
__device__ __forceinline__ float bf_lo(uint32_t v) { return __uint_as_float(v << 16); }
__device__ __forceinline__ float bf_hi(uint32_t v) { return __uint_as_float(v & 0xffff0000u); }
__device__ __forceinline__ float bf_round(float x) { return __uint_as_float(pack_bf(0.f, x) & 0xffff0000u); }
__device__ __forceinline__ uint32_t hmul2_bf(uint32_t a, uint32_t b) { uint32_t r; asm("mul.rn.bf16x2 %0, %1, %2;" : "=r"(r) : "r"(a), "r"(b)); return r; }
__device__ __forceinline__ uint32_t hadd2_bf(uint32_t a, uint32_t b) { uint32_t r; asm("add.rn.bf16x2 %0, %1, %2;" : "=r"(r) : "r"(a), "r"(b)); return r; }
__device__ __forceinline__ uint32_t hfma2_bf(uint32_t a, uint32_t b, uint32_t c) { uint32_t r; asm("fma.rn.bf16x2 %0, %1, %2, %3;" : "=r"(r) : "r"(a), "r"(b), "r"(c)); return r; }
__device__ __forceinline__ uint32_t amax2_bf(uint32_t m, uint32_t v) { uint32_t r; asm("max.xorsign.abs.bf16x2 %0, %1, %2;" : "=r"(r) : "r"(m), "r"(v)); return r; }
__device__ __forceinline__ uint32_t amax2_h(uint32_t m, uint32_t v) { uint32_t r; asm("max.xorsign.abs.f16x2 %0, %1, %2;" : "=r"(r) : "r"(m), "r"(v)); return r; }
__device__ __forceinline__ uint32_t hadd(uint32_t a, uint32_t b) { uint32_t r; asm("add.rn.f16x2 %0, %1, %2;" : "=r"(r) : "r"(a), "r"(b)); return r; }
__device__ __forceinline__ uint32_t hsub(uint32_t a, uint32_t b) { uint32_t r; asm("sub.rn.f16x2 %0, %1, %2;" : "=r"(r) : "r"(a), "r"(b)); return r; }
__device__ __forceinline__ uint32_t hsub2(uint32_t a, uint32_t b) { uint32_t r; asm("sub.rn.ftz.f16x2 %0, %1, %2;" : "=r"(r) : "r"(a), "r"(b)); return r; }
__device__ __forceinline__ uint32_t hmul(uint32_t a, uint32_t b) { uint32_t r; asm("mul.rn.f16x2 %0, %1, %2;" : "=r"(r) : "r"(a), "r"(b)); return r; }
__device__ __forceinline__ uint32_t hfma(uint32_t a, uint32_t b, uint32_t c) { uint32_t r; asm("fma.rn.f16x2 %0, %1, %2, %3;" : "=r"(r) : "r"(a), "r"(b), "r"(c)); return r; }
__device__ __forceinline__ uint32_t hfms(uint32_t a, uint32_t b, uint32_t c) { uint32_t r; asm("{ .reg .b32 t; neg.f16x2 t, %3; fma.rn.f16x2 %0, %1, %2, t; }" : "=r"(r) : "r"(a), "r"(b), "r"(c)); return r; }
__device__ __forceinline__ uint32_t warp_max16(uint32_t m) { return __reduce_max_sync(0xffffffffu, max(m & 0x7fffu, (m >> 16) & 0x7fffu)); }
__device__ __forceinline__ float ex2f(float x) { float r; asm("ex2.approx.ftz.f32 %0, %1;" : "=f"(r) : "f"(x)); return r; }

__device__ __forceinline__ float exp_acc(float x) {
    const float t = x * 1.4426950216293335f;
    const float r = fmaf(x, 1.4426950216293335f, -t) + x * 1.9259629911266175e-8f;
    return ex2f(t) * fmaf(r, 0.6931471805599453f, 1.f);
}
__device__ __forceinline__ float sigmoid_f(float x) { return __fdividef(1.f, 1.f + ex2f(-x * 1.4426950408889634f)); }
__device__ __forceinline__ void cexp(float l2, float th, float& zr, float& zi) {
    const float mag = ex2f(l2);
    const float k = (th * 0.15915494309189535f + 12582912.f) - 12582912.f;
    float r = fmaf(-k, 6.2831854820251465f, th);
    r = fmaf(-k, -1.7484555314695172e-7f, r);
    zr = mag * __cosf(r);
    zi = mag * __sinf(r);
}
struct hc { uint32_t re, im; };
__device__ __forceinline__ hc cmul(const hc& a, const hc& b) { return {hfms(a.re, b.re, hmul(a.im, b.im)), hfma(a.re, b.im, hmul(a.im, b.re))}; }
__device__ __forceinline__ hc cmulc(const hc& a, const hc& b) { return {hfma(a.re, b.re, hmul(a.im, b.im)), hfms(a.im, b.re, hmul(a.re, b.im))}; }
struct fc2 { float r[2], i[2]; };
__device__ __forceinline__ void csq(fc2& z) {
#pragma unroll
    for (int m = 0; m < 2; m++) {
        const float r = fmaf(z.r[m], z.r[m], -(z.i[m] * z.i[m]));
        asm("{ .reg .f32 t; mul.f32 t, %0, %1; mul.f32 %0, t, 0f40000000; }" : "+f"(z.i[m]) : "f"(z.r[m]));
        z.r[m] = r;
    }
}
__device__ __forceinline__ hc pk(const fc2& z) { return {pack_h(z.r[0], z.r[1]), pack_h(z.i[0], z.i[1])}; }
__device__ __forceinline__ void csq_conj(fc2& z) {
#pragma unroll
    for (int m = 0; m < 2; m++) {
        const float r = fmaf(z.r[m], z.r[m], -(z.i[m] * z.i[m]));
        asm("{ .reg .f32 t, n; neg.f32 n, %1; mul.f32 t, %0, n; mul.f32 %0, t, 0f40000000; }" : "+f"(z.i[m]) : "f"(z.r[m]));
        z.r[m] = r;
    }
}

struct Powers { hc C, z1, z2, z4, c8, c16, c32, c64, z128, z256, z512, z1024; };
__device__ __forceinline__ void kg_powers(Powers& q, uint32_t la, uint32_t ai, uint32_t cr, uint32_t ci, float dt, float cf) {
    fc2 z, y;
    const float dtl = -dt * 1.4426950408889634f;
    const uint32_t eb = pack_bf(ex2f(bf_lo(la) * 1.4426950408889634f), ex2f(bf_hi(la) * 1.4426950408889634f));
    const float l2[2] = {bf_lo(eb) * dtl, bf_hi(eb) * dtl}, th[2] = {bf_lo(ai) * dt, bf_hi(ai) * dt};
#pragma unroll
    for (int m = 0; m < 2; m++) { cexp(l2[m], th[m], z.r[m], z.i[m]); cexp(l2[m] * 128.f, th[m] * 128.f, y.r[m], y.i[m]); }
    q.C.re = pack_h(bf_lo(cr) * cf, bf_hi(cr) * cf);
    q.C.im = pack_h(bf_lo(ci) * cf, bf_hi(ci) * cf);
    q.z1 = pk(z); csq(z); q.z128 = pk(y); csq(y);
    q.z2 = pk(z); csq(z); q.z256 = pk(y); csq(y);
    q.z4 = pk(z); csq_conj(z); q.z512 = pk(y); csq(y);
    q.c8 = pk(z); csq(z); q.z1024 = pk(y);
    q.c16 = pk(z); csq(z);
    q.c32 = pk(z); csq(z);
    q.c64 = pk(z);
}
struct Rows { hc ta[8], tb[8], tc[8], pp[8]; };
#define PUT(a0, a1, row, a, b) sts128((((row) & 1) ? (a1) : (a0)) + (row) * 512, (a).re, (a).im, (b).re, (b).im)
template <bool FIRST>
__device__ __forceinline__ void kg_rows(Rows& w, const Powers& q, uint32_t t0, uint32_t t1, uint32_t u0, uint32_t u1, uint32_t uc, uint32_t zr, uint32_t (&Rl)[2]) {
    w.ta[0] = q.C; w.ta[1] = cmul(q.C, q.z1); w.ta[2] = cmul(q.C, q.z2); w.ta[4] = cmul(q.C, q.z4); w.tb[0] = cmul(q.C, q.z256); w.tb[4] = cmul(q.C, q.z512);
    PUT(t0, t1, 0, w.ta[0], w.tb[0]); PUT(t0, t1, 4, w.ta[4], w.tb[4]);
    w.tb[1] = cmul(w.ta[2], q.z256); w.tb[2] = cmul(w.ta[4], q.z256);
    PUT(t0, t1, 1, w.ta[1], w.tb[1]); PUT(t0, t1, 2, w.ta[2], w.tb[2]);
    w.ta[3] = cmul(w.ta[1], q.z2); w.ta[6] = cmul(w.ta[2], q.z4); w.ta[5] = cmul(w.ta[1], q.z4); w.tb[5] = cmul(w.ta[4], q.z512); w.tb[6] = cmul(w.tb[0], q.z512);
    PUT(t0, t1, 5, w.ta[5], w.tb[5]); PUT(t0, t1, 6, w.ta[6], w.tb[6]);
    w.tb[3] = cmul(w.ta[6], q.z256); w.ta[7] = cmul(w.ta[3], q.z4); w.tb[7] = cmul(w.tb[2], q.z512);
    PUT(t0, t1, 3, w.ta[3], w.tb[3]); PUT(t0, t1, 7, w.ta[7], w.tb[7]);
    sts64(uc, q.c64.re, q.c64.im);
    w.pp[0] = hc{0x3C003C00u ^ zr, zr}; w.pp[1] = q.c8; w.pp[2] = q.c16; w.pp[4] = q.c32;
    w.tc[0] = cmul(q.C, q.z1024); w.pp[3] = cmul(q.c8, q.c16); w.pp[5] = cmul(q.c8, q.c32); w.pp[6] = cmul(q.c16, q.c32);
    w.tc[2] = cmul(w.tc[0], q.z128); w.tc[4] = cmul(w.tc[0], q.z256); w.tc[1] = cmul(w.tc[0], q.z512); w.pp[7] = cmul(w.pp[3], q.c32);
    PUT(u0, u1, 0, w.tc[0], w.pp[0]); PUT(u0, u1, 1, w.tc[1], w.pp[1]); PUT(u0, u1, 2, w.tc[2], w.pp[2]); PUT(u0, u1, 4, w.tc[4], w.pp[4]);
    w.tc[6] = cmul(w.tc[2], q.z256); w.tc[3] = cmul(w.tc[2], q.z512); w.tc[5] = cmul(w.tc[4], q.z512);
    PUT(u0, u1, 3, w.tc[3], w.pp[3]); PUT(u0, u1, 5, w.tc[5], w.pp[5]); PUT(u0, u1, 6, w.tc[6], w.pp[6]);
    w.tc[7] = cmul(w.tc[6], q.z512);
    PUT(u0, u1, 7, w.tc[7], w.pp[7]);
    const uint32_t last = hfms(w.tc[0].re, q.z1024.re, hmul(w.tc[0].im, q.z1024.im));
    if (FIRST) mma_h_k8_z(Rl, 0x3C003C00u - zr, 0x3C003C00u + zr, last); else mma_h_k8(Rl[0], Rl[1], 0x3C003C00u - zr, 0x3C003C00u + zr, last);
}
__device__ __forceinline__ void kg_keep(const Rows& w, const Powers& q, uint32_t t0, uint32_t t1, uint32_t u0, uint32_t u1, uint32_t zr) {
}
#undef PUT
template <bool FIRST>
__device__ __forceinline__ void kg_products(uint32_t rt0, uint32_t rt1, uint32_t ru0, uint32_t ru1, uint32_t rc, uint32_t zr,
                                            uint32_t (&Ra)[2][2], uint32_t (&Rb)[2][2], uint32_t (&Rc)[2]) {
    uint4 q1[8], q2[8], cw[8];
#pragma unroll
    for (int ks = 0; ks < 8; ks++) {
        q2[ks] = lds128(((ks & 1) ? ru1 : ru0) + (ks >> 1) * 128); if (!W_SQ) cw[ks] = lds128(rc + ks * 64); else if (!(ks & 1)) cw[ks] = lds128(rc + ks * 32); q1[ks] = lds128(((ks & 1) ? rt1 : rt0) + (ks >> 1) * 128);
    }
#pragma unroll
    for (int ks = 0; ks < 8; ks++) {
        const hc p0 = {q2[ks].z, q2[ks].w}, u = (ks & 1) ? hc{cw[ks & 6].z, cw[ks & 6].w} : hc{cw[ks].x, cw[ks].y};
        const hc p1 = cmul(p0, u), p2 = cmul(p1, u), p3 = cmul(p2, u);
        const uint32_t qa[4] = {p0.re ^ zr, p1.re, p0.im ^ zr, p1.im}, qb[4] = {p2.re, p3.re, p2.im, p3.im};
        if (FIRST && ks == 0) {
            mma_h_z(Rc[0], Rc[1], qa, q2[ks].x, q2[ks].y); mma_h_z(Ra[0][0], Ra[0][1], qa, q1[ks].x, q1[ks].y); mma_h_z(Rb[0][0], Rb[0][1], qa, q1[ks].z, q1[ks].w);
            mma_h_z(Ra[1][0], Ra[1][1], qb, q1[ks].x, q1[ks].y); mma_h_z(Rb[1][0], Rb[1][1], qb, q1[ks].z, q1[ks].w);
        } else {
            mma_h(Rc, qa, q2[ks].x, q2[ks].y); mma_h(Ra[0], qa, q1[ks].x, q1[ks].y); mma_h(Rb[0], qa, q1[ks].z, q1[ks].w);
            mma_h(Ra[1], qb, q1[ks].x, q1[ks].y); mma_h(Rb[1], qb, q1[ks].z, q1[ks].w);
        }
    }
}
__device__ __forceinline__ void kernel_gen(const uint2& la, const uint2& ai, const uint2& cr, const uint2& ci, float dt, float cf, uint32_t TB, uint32_t UB,
                                           int lane, uint32_t zr, uint32_t (&Ra)[2][2], uint32_t (&Rb)[2][2], uint32_t (&Rc)[2], uint32_t (&Rl)[2]) {
    const int g = lane >> 2, t = lane & 3;
    const uint32_t w0 = lane << 4, w1 = w0 ^ 64, r0 = g * 512 + (((g & 1) << 6) | (t << 4)), r1 = r0 ^ 64;
    const uint32_t t0 = TB + w0, t1 = TB + w1, u0 = UB + w0, u1 = UB + w1;
    [[maybe_unused]] const uint32_t uc = UB + 4096 + (lane >> 3) * 64 + t * 16 + (lane & 4) * 2;
    Powers p0, p1;
    Rows w;
    kg_powers(p0, la.x, ai.x, cr.x, ci.x, dt, cf);
    kg_rows<true>(w, p0, t0, t1, u0, u1, uc, zr, Rl);
    kg_powers(p1, la.y, ai.y, cr.y, ci.y, dt, cf);
    kg_keep(w, p0, t0, t1, u0, u1, zr);
    __syncwarp();
    kg_products<true>(TB + r0, TB + r1, UB + r0, UB + r1, UB + 4096 + t * 16, zr, Ra, Rb, Rc);
    __syncwarp();
    kg_rows<false>(w, p1, t0, t1, u0, u1, uc, zr, Rl);
    kg_keep(w, p1, t0, t1, u0, u1, zr);
    __syncwarp();
    kg_products<false>(TB + r0, TB + r1, UB + r0, UB + r1, UB + 4096 + t * 16, zr, Ra, Rb, Rc);
    __syncwarp();
}

template <int V> struct IC { static constexpr int value = V; };

#define LANE_VARS \
    int tid_; asm volatile("mov.u32 %0, %%tid.x;" : "=r"(tid_)); \
    [[maybe_unused]] const int lane = tid_ & 31, warp = (tid_ >> 5) - MAIN_W0, g = lane >> 2, t = lane & 3, mi = lane >> 3, r = lane & 7; \
    [[maybe_unused]] const uint32_t TB = sb + OFF_TAB + warp * T_CH, UB = sb + OFF_U + warp * U_CH; \
    [[maybe_unused]] const bool lead = (tid_ == 32 * MAIN_W0)

__device__ __forceinline__ void dense_step(uint32_t (&M)[8][2], uint32_t (&Ye)[8][2], uint32_t (&Yo)[8][2], uint32_t (&X)[8][2],
                                           uint32_t (&F)[8][2], uint32_t (&Bq)[2][4], uint32_t ua, uint32_t ta, uint32_t zr) {
    uint32_t E[8][2], A[2][4], S[2][4], G[8][2];
#pragma unroll
    for (int jp = 0; jp < 4; jp++) ldsm4(ua + jp * 256, E[2 * jp][0], E[2 * jp][1], E[2 * jp + 1][0], E[2 * jp + 1][1]);
#pragma unroll
    for (int h = 0; h < 2; h++) { A[h][0] = lds32(ta + 1024 * h); A[h][1] = lds32(ta + 1024 * h + 32); A[h][3] = lds32(ta + 1024 * h + 64); A[h][2] = A[h][1] ^ zr; }
#pragma unroll
    for (int J = 0; J < 8; J++) mma_h(Ye[J], Bq[0], F[J][0], F[J][1]);
#pragma unroll
    for (int J = 1; J < 8; J++) mma_h(Ye[J], Bq[1], F[J - 1][0], F[J - 1][1]);
#pragma unroll
    for (int J = 0; J < 8; J++) { G[J][0] = hsub(X[J][0], E[J][0]); G[J][1] = hsub(X[J][1], E[J][1]); }
#pragma unroll
    for (int jp = 0; jp < 4; jp++) ldsm4(ua + 2 * U_PL + jp * 256 - 16, X[2 * jp][0], X[2 * jp][1], X[2 * jp + 1][0], X[2 * jp + 1][1]);
#pragma unroll
    for (int h = 0; h < 2; h++) { Bq[h][1] = lds32(ta + 1024 * h + 96); Bq[h][3] = lds32(ta + 1024 * h + 128); Bq[h][0] = A[h][3] ^ zr; Bq[h][2] = Bq[h][1] ^ zr; }
#pragma unroll
    for (int J = 0; J < 8; J++) mma_h(Yo[J], A[0], G[J][0], G[J][1]);
#pragma unroll
    for (int J = 1; J < 8; J++) mma_h(Yo[J], A[1], G[J - 1][0], G[J - 1][1]);
#pragma unroll
    for (int h = 0; h < 2; h++)
#pragma unroll
        for (int i = 0; i < 4; i++) S[h][i] = hadd(A[h][i], Bq[h][i]);
#pragma unroll
    for (int J = 0; J < 8; J++) mma_h(M[J], S[0], E[J][0], E[J][1]);
#pragma unroll
    for (int J = 1; J < 8; J++) mma_h(M[J], S[1], E[J - 1][0], E[J - 1][1]);
#pragma unroll
    for (int J = 0; J < 8; J++) { F[J][0] = hsub(X[J][0], E[J][0]); F[J][1] = hsub(X[J][1], E[J][1]); }
}

__device__ __forceinline__ int group_tables(uint32_t TB, int lane) {
    const int g = lane >> 2, t = lane & 3;
    const uint4 b4 = lds128(TB + T_R2 + 16 * lane), c4 = lds128(TB + T_R2 + 512 + 16 * lane);
    uint32_t vb[4] = {b4.x, b4.y, b4.z, b4.w}, vc[2] = {c4.x, c4.y};
    const uint32_t k1024 = __shfl_sync(0xffffffffu, vc[0], 0) & 0xffffu;
    uint32_t kl = hadd(c4.z, __byte_perm(c4.z, 0, 0x1032));
    kl = hadd(kl, __shfl_xor_sync(0xffffffffu, kl, 1)); kl = hadd(kl, __shfl_xor_sync(0xffffffffu, kl, 2));
#pragma unroll
    for (int i = 0; i < 3; i++) sts128(TB + T_R2 + 16 * lane + 512 * i, 0, 0, 0, 0);
    if (lane == 2) vb[0] &= 0xffff0000u;
    if (lane == 0) vc[0] &= 0xffff0000u;
    if (lane == 4) vc[0] = hsub(vc[0], k1024);
    __syncwarp();
    if (t >= 2) {
        const uint32_t g1 = TB + T_R2 + T2_S * (g & 3) + 8 * (8 * t - 10 + (g >> 2));
        const uint32_t g0 = TB + T_R2 + T2_S * ((g - 1) & 3) + 8 * (8 * t - 10 + ((g - 1) >> 2)) + 4;
#pragma unroll
        for (int i = 0; i < 4; i++) {
            sts16(g0 + 16 * i, vb[i]); sts16(g0 + 16 * i + 10, vb[i]);
            sts16(g1 + 16 * i, vb[i] >> 16); sts16(g1 + 16 * i + 10, vb[i] >> 16);
        }
    }
    const uint32_t g3 = TB + T_R3 + T3_S * (((g - 1) >> 1) & 1) + 8 * (7 + 4 * t + ((g - 1) >> 2)) + 4 * ((g - 1) & 1);
#pragma unroll
    for (int i = 0; i < 2; i++) {
        sts16(g3 + 16 * i, vc[i]); sts16(g3 + 16 * i + 10, vc[i]);
        sts16(g3 + 16 * i + 128, vc[i] >> 16); sts16(g3 + 16 * i + 138, vc[i] >> 16);
    }
    const uint32_t g4 = (uint32_t)(((uint64_t)(T_R3 + T3_S + 308) << 48 | (uint64_t)(T_R2 + 180) << 32 | (T_R2 + 176) << 16 | (T_R2 + 3 * T2_S + 172)) >> (8 * (lane & 6))) & 0xffffu;
    sts16(TB + g4 + 10 * (lane & 1), (lane & 7) < 6 ? k1024 : kl);
    return (int)c4.w;
}

#define FENCE() do { if (zr) asm volatile("exit;"); } while (0)
struct Chunks { uint32_t c3, c2, c1, c0, cm1, cm2, cm3, cm4, d2, d1, d0, dm1, em2, em3; };
__device__ __forceinline__ void convolve(uint32_t sb, int h, uint32_t zr DBG_PARAMS) {
    const uint32_t bars = sb + M_BARS;
    uint32_t M[8][2], Ye[8][2], Yo[8][2], F[8][2], Bq[2][4];
    {
        LANE_VARS;
        uint32_t X[8][2];
        uint32_t ua = UB + ((mi & 1) ? 0 : U_PL) + (8 + 8 * (mi >> 1) + r) * 16, ta = TB + 4 * (1 + g + 2 * t);
        uint32_t A[3][4], S[2][4];
        __syncwarp();
#pragma unroll
        for (int h2 = 0; h2 < 3; h2++) { A[h2][0] = lds32(ta + 1024 * h2); A[h2][1] = lds32(ta + 1024 * h2 + 32); A[h2][3] = lds32(ta + 1024 * h2 + 64); A[h2][2] = A[h2][1] ^ zr; }
#pragma unroll
        for (int h2 = 0; h2 < 2; h2++) {
            Bq[h2][1] = lds32(ta + 1024 * h2 + 96); Bq[h2][3] = lds32(ta + 1024 * h2 + 128); Bq[h2][0] = A[h2][3] ^ zr; Bq[h2][2] = Bq[h2][1] ^ zr;
#pragma unroll
            for (int i = 0; i < 4; i++) S[h2][i] = hadd(A[h2][i], Bq[h2][i]);
        }
        const uint32_t an = A[0][0] ^ zr, un = UB + (9 + lane) * 16;
        if (lead) TSTAMP(10);
        mbar_spin(bars + 8 * B_U);
        if (lead) { TSTAMP(3); CSTAMP(27); }
        uint32_t E[8][2], N[8], G[8][2];
#pragma unroll
        for (int jp = 0; jp < 4; jp++) ldsm4(ua + jp * 256, E[2 * jp][0], E[2 * jp][1], E[2 * jp + 1][0], E[2 * jp + 1][1]);
#pragma unroll
        for (int jp = 0; jp < 4; jp++) ldsm4(ua + 2 * U_PL + jp * 256, X[2 * jp][0], X[2 * jp][1], X[2 * jp + 1][0], X[2 * jp + 1][1]);
        ldsm4(un, N[0], N[1], N[2], N[3]); ldsm4(un + 512, N[4], N[5], N[6], N[7]);
#pragma unroll
        for (int J = 0; J < 8; J++) mma_h_z(M[J][0], M[J][1], S[0], E[J][0], E[J][1]);
#pragma unroll
        for (int J = 1; J < 8; J++) mma_h(M[J], S[1], E[J - 1][0], E[J - 1][1]);
#pragma unroll
        for (int J = 2; J < 8; J++) mma_h(M[J], A[2], E[J - 2][0], E[J - 2][1]);
        if (FENCES & 32) FENCE();
#pragma unroll
        for (int J = 0; J < 8; J++) mma_h_k8_z(Ye[J], zr, an, X[J][1]);
#pragma unroll
        for (int J = 0; J < 8; J++) mma_h_k8_z(Yo[J], zr, an, N[J]);
#pragma unroll
        for (int J = 0; J < 8; J++) { G[J][0] = hsub(X[J][0], E[J][0]); G[J][1] = hsub(X[J][1], E[J][1]); }
#pragma unroll
        for (int jp = 0; jp < 4; jp++) ldsm4(ua + 2 * U_PL + jp * 256 - 16, X[2 * jp][0], X[2 * jp][1], X[2 * jp + 1][0], X[2 * jp + 1][1]);
#pragma unroll
        for (int J = 0; J < 8; J++) mma_h(Yo[J], A[0], G[J][0], G[J][1]);
#pragma unroll
        for (int J = 1; J < 8; J++) mma_h(Yo[J], A[1], G[J - 1][0], G[J - 1][1]);
#pragma unroll
        for (int J = 2; J < 8; J++) mma_h(Yo[J], A[2], G[J - 2][0], G[J - 2][1]);
#pragma unroll
        for (int J = 0; J < 8; J++) { F[J][0] = hsub(X[J][0], E[J][0]); F[J][1] = hsub(X[J][1], E[J][1]); }
#pragma unroll 1
        for (int k = 1; k < 8; k++) {
            ua -= 16; ta += 128;
            dense_step(M, Ye, Yo, X, F, Bq, ua, ta, zr);
        }
    }
    mbar_wait_n<2, 8>(bars + 8 * B_TD);
    LANE_VARS;
    if (lead) { TSTAMP(4); CSTAMP(28); }
    __syncwarp();
    const uint32_t idh = (g == 2 * t) ? 0x3C00u : (g == 2 * t + 1) ? 0x3C000000u : 0u;
    const uint32_t sbr = mapa(sb, h ^ 1);
    const uint32_t yl = TB + lane * 16, yr = sbr + (h ? ALT0 : ALT1) + A_YIN + warp * Y_CH + lane * 16;
    uint32_t early[4][4];
    auto finish = [&](int J) {
        float m[4], e[4], o[4];
        widen_h(m, M[J], idh); widen_add_h(e, Ye[J], idh, m); widen_add_h(o, Yo[J], idh, m);
        const uint32_t y[4] = {pack_bf(e[0], e[2]), pack_bf(o[0], o[2]), pack_bf(e[1], e[3]), pack_bf(o[1], o[3])};
        if (J < 4) {
#pragma unroll
            for (int i = 0; i < 4; i++) early[J & 3][i] = y[i];
        } else {
            const uint32_t* ea = early[J & 3];
            st_async16(yr + (J & 3) * 512, h ? ea[0] : y[0], h ? ea[1] : y[1], h ? ea[2] : y[2], h ? ea[3] : y[3], sbr + M_BARS + 8 * (B_Y + (J & 3)));
            sts128(yl + (J & 3) * 512, h ? y[0] : ea[0], h ? y[1] : ea[1], h ? y[2] : ea[2], h ? y[3] : ea[3]);
            __syncwarp();
            if (lane == 0) mbar_arrive(bars + 8 * (B_Y + (J & 3)));
        }
    };
    const uint32_t a1 = UB + (3 - mi) * U_PL + (8 + r) * 16;
    const uint32_t a2 = UB + ((2 - mi) & 3) * U_PL + (8 + r - (mi == 3)) * 16;
    const uint32_t a3 = UB + (2 - (mi & 1)) * U_PL + (7 + r) * 16;
    const uint32_t bt = sb + OFF_BAND + 4 * (32 + g + 2 * t);
    auto load3 = [&](Chunks& u, int j) { ldsm4(a2 + j * 128, u.d2, u.d1, u.d0, u.dm1); ldsm4(a1 + j * 128, u.c3, u.c2, u.c1, u.c0); ldsm2(a3 + j * 128, u.em2, u.em3); };
    auto load2 = [&](Chunks& u, int j) { load3(u, j); ldsm4(a1 + j * 128 - 16, u.cm1, u.cm2, u.cm3, u.cm4); };
    Chunks u;
    uint32_t B35[4];
    uint2 Q[4][3], QS[2][3];
    {
        const uint32_t f7 = lds32(bt + 768 - 36), g7 = lds32(bt + 768 - 4), f9 = lds32(bt + 1024 - 32), g9 = lds32(bt + 1024), h9 = lds32(bt + 1024 + 32);
        const uint32_t f1 = hmul(lds32(bt - 28), lds16(TB + T_R2 + 176) * 0x10001u);
        load3(u, 0);
        const uint32_t tq = TB + T_R3 + 8 * (7 + g - 2 * t);
        uint2 Q0[4], Q1[4], Q2[4];
#pragma unroll
        for (int i = 0; i < 4; i++) { Q0[i] = lds64(tq + 64 * i); Q1[i] = lds64(tq + T3_S + 64 * i); Q2[i] = lds64(tq + T3_S - 8 + 64 * i); }
#pragma unroll
        for (int J = 0; J < 8; J++) mma_h(Ye[J], Bq[0], F[J][0], F[J][1]);
#pragma unroll
        for (int J = 1; J < 8; J++) mma_h(Ye[J], Bq[1], F[J - 1][0], F[J - 1][1]);
        const uint32_t B7[4] = {zr, f7, f7 ^ zr, g7}, B9a[4] = {zr + zr, f9, f9 ^ zr, g9}, B9b[4] = {g9 ^ zr, h9, h9 ^ zr, zr * 3}, B1[4] = {zr * 5, f1, f1 ^ zr, zr * 7};
        const uint32_t g7b = g7 ^ zr, z7 = zr * 9;
        if (FENCES & 1) FENCE();
        uint32_t WE[2][4], WO[2][4];
#pragma unroll
        for (int j = 0; j < 5; j++) {
            uint32_t (&we)[4] = WE[j & 1], (&wo)[4] = WO[j & 1], (&pe)[4] = WE[~j & 1], (&po)[4] = WO[~j & 1];
            if (j == 3) {
                const uint32_t t2 = TB + T_R2 + 8 * (6 + g - 2 * t);
                B35[0] = lds32(bt + 256 - 28); B35[1] = lds32(bt + 512 - 40); B35[2] = lds32(bt + 256 + 4); B35[3] = lds32(bt + 512 - 8);
#pragma unroll
                for (int i = 0; i < 3; i++)
#pragma unroll
                    for (int s = 0; s < 4; s++) Q[s][i] = lds64(t2 + T2_S * s + 64 * i);
            }
            if (j < 4) {
                mma_h_z(we[2], we[3], B9a, u.d0, u.dm1); mma_h_z(wo[2], wo[3], B9a, u.d2, u.d1);
                mma_h_z(we[0], we[1], B7, u.c1, u.c0); mma_h_z(wo[0], wo[1], B7, u.c3, u.c2);
            }
            if (j == 0) { finish(0); finish(1); }
#pragma unroll
            for (int i = 0; i < 5 - j && j > 0; i++) { mma_h(Ye[j + 3 + i], pe, Q0[i].x, Q0[i].y); mma_h(Yo[j + 3 + i], pe, Q1[i].x, Q1[i].y); }
            if (j < 4) {
                mma_h2(we[2], we[3], B9b, u.em2, u.em3); mma_h2(wo[2], wo[3], B9b, u.d0, u.dm1);
                mma_h_k8(we[0], we[1], g7b, z7, u.dm1); mma_h_k8(wo[0], wo[1], g7b, z7, u.c1);
                mma_h(Ye[j + 4], B1, u.d0, u.dm1); mma_h(Yo[j + 4], B1, u.d2, u.d1);
                if (j < 3) load3(u, j + 1); else load2(u, 0);
            }
#pragma unroll
            for (int i = 0; i < 5 - j && j > 0; i++) { mma_h(Ye[j + 3 + i], po, Q2[i].x, Q2[i].y); mma_h(Yo[j + 3 + i], po, Q0[i].x, Q0[i].y); }
            if (j == 3) {
#pragma unroll
                for (int i = 0; i < 3; i++)
#pragma unroll
                    for (int s = 0; s < 2; s++) { QS[s][i].x = hadd(Q[s][i].x, Q[s + 2][i].x); QS[s][i].y = hadd(Q[s][i].y, Q[s + 2][i].y); }
            }
            if (j < 3 ? ((FENCES & 2) || (j == 2 && (FENCES & 4))) : (j == 4 && (FENCES & 8))) FENCE();
        }
    }
    const uint32_t zq = zr + zr;
#pragma unroll
    for (int j = 0; j < 6; j++) {
        uint32_t H[7][2];
        mma_h_z(H[3][0], H[3][1], B35, u.d0, u.dm1); mma_h_z(H[4][0], H[4][1], B35, u.c1, u.c0);
        mma_h_z(H[5][0], H[5][1], B35, u.d2, u.d1); mma_h_z(H[6][0], H[6][1], B35, u.c3, u.c2);
        mma_h_z(H[2][0], H[2][1], B35, u.cm1, u.cm2); mma_h_z(H[1][0], H[1][1], B35, u.em2, u.em3); mma_h_z(H[0][0], H[0][1], B35, u.cm3, u.cm4);
        if (j < 5) load2(u, j + 1);
        if (j > 0) finish(j + 1);
        const int n = j < 4 ? 3 : 6 - j;
#pragma unroll
        for (int s = 0; s < 2; s++) {
            const int o = 3 - s;
            const uint32_t qe[4] = {H[o][0] ^ zr, H[o + 1][0] ^ zq, H[o][1] ^ zr, H[o + 1][1] ^ zq};
            const uint32_t qg[4] = {hsub(H[o + 2][0], H[o][0]), hsub2(H[o + 3][0], H[o + 1][0]), hsub(H[o + 2][1], H[o][1]), hsub2(H[o + 3][1], H[o + 1][1])};
            const uint32_t qf[4] = {hsub(H[o - 2][0], H[o][0]), hsub2(H[o - 1][0], H[o + 1][0]), hsub(H[o - 2][1], H[o][1]), hsub2(H[o - 1][1], H[o + 1][1])};
#pragma unroll
            for (int i = 0; i < n; i++) mma_h(M[j + 2 + i], qe, QS[s][i].x, QS[s][i].y);
#pragma unroll
            for (int i = 0; i < n; i++) mma_h(Yo[j + 2 + i], qg, Q[s][i].x, Q[s][i].y);
#pragma unroll
            for (int i = 0; i < n; i++) mma_h(Ye[j + 2 + i], qf, Q[s + 2][i].x, Q[s + 2][i].y);
        }
        if (j < 5 && (FENCES & 16)) FENCE();
    }
    finish(7);
}

__global__ void __cluster_dims__(2, 1, 1) __launch_bounds__(NTHREADS, 1)
fused_kernel(const Params p, const __grid_constant__ CUtensorMap tm_gu, const __grid_constant__ CUtensorMap tm_down, const __grid_constant__ CUtensorMap tm_x,
             const __grid_constant__ CUtensorMap tm_r, const __grid_constant__ CUtensorMap tm_o) {
    extern __shared__ __align__(1024) unsigned char smem[];
    const uint32_t sb = __shfl_sync(0xffffffffu, smem_u32(smem), 0);
    int tid;
    asm volatile("mov.u32 %0, %%tid.x;" : "=r"(tid));
    const int pw = tid >> 5, lane = tid & 31;
    const int kc = ((blockIdx.x >> 1) + 60) & 63, k7 = ((kc - 32) * 37) >> 8;
    const int h = blockIdx.x & 1;
    const int pr = !REMAP ? (int)(blockIdx.x >> 1) : kc < 32 ? ((kc & 7) << 2) | (kc >> 3) : kc < 60 ? 32 + 4 * (kc - 32 - 7 * k7) + k7 : kc;
    const int c = 2 * pr + h;
    const uint32_t bars = sb + M_BARS;

    if (blockIdx.x >= 128) {
        if (blockIdx.x != 128) return;
        const unsigned tag = (ld_epoch(p.ex) + 1) & 0xffffu;
        const uint32_t idx0 = 2047 - (256 * (tid & 3) + (tid >> 3) + 1024 * ((tid >> 2) & 1));
        const uint32_t list = sb + 128;
#pragma unroll 1
        for (int pass = 0; pass < 2; pass++) {
            if (tid == 0) sts32(sb + 64, 0);
            sts128(list + 16 * tid, 0, 0, 0, 0);
            uint4 a = make_uint4(lane == 0 ? 0x10000u : 0u, 0, 0, 0);
            bool ok = pass == 0;
#pragma unroll 1
            for (int it = 0; it < (1 << 22) && !ok; it++) {
                a = ld_gpu128(&p.ex->r[tid]);
                ok = (((a.x ^ tag) | (a.y ^ tag) | (a.z ^ tag) | (a.w ^ tag)) & 0xffffu) == 0;
            }
            if (!ok) __trap();
            const uint32_t key[4] = {(a.x & 0xffff0000u) | idx0, (a.y & 0xffff0000u) | (idx0 - 64), (a.z & 0xffff0000u) | (idx0 - 128), (a.w & 0xffff0000u) | (idx0 - 192)};
            const uint32_t wm = __reduce_max_sync(0xffffffffu, max(max(key[0], key[1]), max(key[2], key[3])));
            if (lane == 0) sts32(sb + pw * 4, wm);
            __syncthreads();
            const uint2 q = lds64(sb + 8 * (lane & 7));
            const uint32_t thr = __reduce_min_sync(0xffffffffu, max(q.x, q.y));
            if (tid == 0) TSTAMP(0);
            const uint32_t n = (key[0] >= thr) + (key[1] >= thr) + (key[2] >= thr) + (key[3] >= thr);
            if (n) {
                uint32_t pos;
                asm volatile("atom.shared.add.u32 %0, [%1], %2;" : "=r"(pos) : "r"(sb + 64), "r"(n) : "memory");
#pragma unroll
                for (int i = 0; i < 4; i++) if (key[i] >= thr) { sts32(list + 4 * pos, key[i]); pos++; }
            }
            __syncthreads();
            const int ncand = (int)lds32(sb + 64);
            const uint2 l0 = lds64(list + 8 * lane);
#pragma unroll 1
            for (int j = pw; j < ncand; j += 16) {
                const uint32_t mine = lds32(list + 4 * j);
                int rank = __popc(__ballot_sync(0xffffffffu, l0.x > mine)) + __popc(__ballot_sync(0xffffffffu, l0.y > mine));
#pragma unroll 1
                for (int i = 64; i < ncand; i += 32) rank += __popc(__ballot_sync(0xffffffffu, lds32(list + 4 * (i + lane)) > mine));
                if (rank < 8 && lane == 0) {
                    asm volatile("st.relaxed.gpu.global.v2.u32 [%0], {%1, %2};" :: "l"(&p.ex->top[rank]), "r"(mine), "r"(pass ? tag : tag ^ 0x8000u) : "memory");
                }
            }
            if (tid == 0) TSTAMP(1);
            __syncthreads();
        }
        if (tid == 0) TSDUMP(3u);
        return;
    }

    if (pw != 12) asm volatile("barrier.cluster.arrive.relaxed.aligned;" ::: "memory");

    if (pw >= MAIN_W0 && pw < MAIN_W0 + 8) {
        const int warp = pw - MAIN_W0;
        const uint32_t po = (8 * c + warp) * 128 + 4 * lane;
        uint2 v_la = ldg64(p.logA + po), v_ai = ldg64(p.Aim + po), v_cr = ldg64(p.Cre + po), v_ci = ldg64(p.Cim + po);
        const uint32_t ldt16 = ldg16(p.logdt + 8 * c + warp);
        [[maybe_unused]] const bool lead = (tid == 32 * MAIN_W0);
        asm volatile("setmaxnreg.inc.sync.aligned.u32 " MAIN_REGS ";");
        [[maybe_unused]] const int d = 8 * c + warp;
        const int g = lane >> 2, t = lane & 3, mi = lane >> 3, r = lane & 7;
        const uint32_t TB = sb + OFF_TAB + warp * T_CH;
        const uint32_t UB = sb + OFF_U + warp * U_CH;
        const uint32_t zr = p.zero;

        uint32_t Ra[2][2], Rb[2][2], Rc[2], Rl[2];
        int esum;
        {
            const float dt = bf_round(exp_acc(__uint_as_float(ldt16 << 16)));
            const uint32_t ec = max(warp_max16(amax2_bf(amax2_bf(v_cr.x, v_cr.y), amax2_bf(v_ci.x, v_ci.y))) >> 7, 6u);
            const float cf = __uint_as_float((__float_as_uint(dt) & 0x7fffffu) | ((260u - ec) << 23));
            esum = (int)ec + (int)(__float_as_uint(dt) >> 23) - 274;
            kernel_gen(v_la, v_ai, v_cr, v_ci, dt, cf, TB, UB, lane, zr, Ra, Rb, Rc, Rl);
        }
        asm volatile("barrier.cluster.wait.acquire.aligned;" ::: "memory");
        if (lane == 0) mbar_arrive(bars + 8 * B_KD + (Rc[0] & zr));
        if (lead) TSTAMP(2);

        {
            uint32_t mk = amax2_h(amax2_h(amax2_h(Ra[0][0], Ra[0][1]), amax2_h(Ra[1][0], Ra[1][1])), amax2_h(amax2_h(Rb[0][0], Rb[0][1]), amax2_h(Rb[1][0], Rb[1][1])));
            mk = amax2_h(amax2_h(mk, hmul(Rl[0], 0x34003400u)), amax2_h(Rc[0], Rc[1]));
            const uint32_t ek = warp_max16(mk) >> 10;
            const float fs = __uint_as_float((139u - ek) << 23);
            const uint32_t ks = pack_h(fs, fs);
            uint32_t va[4], vb[4];
#pragma unroll
            for (int i = 0; i < 4; i++) { va[i] = hmul(Ra[i >> 1][i & 1], ks); vb[i] = hmul(Rb[i >> 1][i & 1], ks); }
            const uint32_t k512 = __shfl_sync(0xffffffffu, vb[0], 2) & 0xffffu, k255 = __shfl_sync(0xffffffffu, va[3], 31);
#pragma unroll
            for (int i = 0; i < 4; i++) {
                const uint32_t pv = __shfl_sync(0xffffffffu, lane == 31 ? (i ? va[i - 1] : 0u) : va[i], lane - 1);
                sts64(TB + 48 + 256 * i + 8 * lane, __byte_perm(pv, va[i], 0x5432), va[i]);
            }
#pragma unroll
            for (int i = 0; i < 4; i++) {
                const uint32_t nx = __shfl_sync(0xffffffffu, lane == 0 ? (i < 3 ? vb[i + (i < 3)] : k512) : vb[i], lane + 1 + 2 * (lane & 1));
                const uint32_t aa = __byte_perm(vb[i], 0, 0x1010);
                sts128_if(t < 2, TB + 1072 + 256 * i + 32 * g + 16 * t, (i == 0 && lane == 0) ? __byte_perm(k255, aa, 0x5432) : aa ^ zr, aa, vb[i] ^ zr, __byte_perm(vb[i], nx, 0x5432));
            }
            const uint32_t k0 = lane == 3 ? k512 : 0u, kk = k0 * 0x10001u;
            sts128_if(lane < 8, TB + 16 * lane + (lane < 3 ? 0 : 2048), kk, kk ^ zr, kk + zr, k0);
            esum += (int)ek;
            sts128(TB + T_R2 + 16 * lane, vb[0], vb[1], vb[2], vb[3]);
            sts128(TB + T_R2 + 512 + 16 * lane, hmul(Rc[0], ks), hmul(Rc[1], ks), hmul(Rl[0], ks), (uint32_t)esum);
            __syncwarp();
            if (lane == 0) mbar_arrive(bars + 8 * B_TS);
        }
        if (lead) TSTAMP(11);

        convolve(sb, h, zr DBG_ARGS);

        {
            LANE_VARS;
            if (lead) { TSTAMP(5); CSTAMP(29); }
            mbar_spin(bars + 8 * B_G);
            const uint32_t xo = sb + OFF_S + (32 * h + (g >> 2)) * 1024 + warp * 128 + (g & 3) * 32 + (((t >> 1) ^ (warp & 1)) << 4) + ((t & 1) << 3);
            const uint32_t go = sb + OFF_GP + (8 * warp + g) * 64;
            const uint32_t sel = lds16(sb + M_BMAP + (8 * warp + g) * 2);
            const int ch16 = 4 * (r >> 1) + 2 * (mi & 1) + (r & 1);
            const uint32_t ya = sb + (((ch16 >> 3) == h) ? OFF_TAB + (ch16 & 7) * T_CH : (h ? ALT1 : ALT0) + A_YIN + (ch16 & 7) * Y_CH) + (4 * warp + (mi >> 1)) * 16;
            const uint32_t ob = (UB + 127) & ~127u;
            const uint32_t obu = __shfl_sync(0xffffffffu, ob, 0), wu = __shfl_sync(0xffffffffu, warp, 0);
            const uint2 dsk = lds64(sb + M_DSK + 8 * t);
            const uint4 s4 = lds128(sb + M_SC + t * 16);
            const uint32_t s01 = __byte_perm(s4.x, s4.y, 0x5410), s23 = __byte_perm(s4.z, s4.w, 0x5410);
            auto put = [&](int J) {
                if (__any_sync(0xffffffffu, (sel >> (4 * J)) & 15u)) {
                    bf16* op = p.out + (size_t)(1024 * h + 256 * J + 8 * g + warp) * D_ + 16 * pr + 4 * t;
#pragma unroll 1
                    for (int i = 0; i < 4; i++) {
                        const uint2 o = lds64(ob + (4 * J + i) * 256 + lane * 8);
                        if (!((sel >> (4 * J + i)) & 1u)) *(uint2*)(op + (size_t)(64 * i) * D_) = o;
                    }
                } else {
                    asm volatile("fence.proxy.async.shared::cta;" ::: "memory");
                    __syncwarp();
                    asm volatile("{ .reg .pred p; elect.sync _|p, 0xffffffff;\n\t@p cp.async.bulk.tensor.3d.global.shared::cta.bulk_group [%0, {%2, %3, %4}], [%1]; }"
                                 :: "l"(&tm_o), "r"(obu + J * 1024), "r"(16 * pr), "r"(128 * h + 32 * J), "r"(wu) : "memory");
                }
            };
#pragma unroll
            for (int J = 0; J < 4; J++) {
                const uint4 g4 = lds128(go + J * 16);
                const uint32_t gp[4] = {g4.x, g4.y, g4.z, g4.w};
                uint2 xd[4], ex[4];
#pragma unroll
                for (int i = 0; i < 4; i++) {
                    const uint2 x = lds64(xo + (4 * J + i) * 2048);
                    const uint32_t og = __byte_perm(gp[i], 0, 0x3232);
                    ex[i].x = hmul2_bf(og, x.x); ex[i].y = hmul2_bf(og, x.y);
                    xd[i].x = hmul2_bf(x.x, dsk.x); xd[i].y = hmul2_bf(x.y, dsk.y);
                }
                mbar_wait(bars + 8 * (B_Y + J));
                if (J == 3 && lead) TSTAMP(6);
#pragma unroll
                for (int q = 0; q < 2; q++) {
                    uint32_t y[4];
                    ldsm4t(ya + J * 512 + q * 32, y[0], y[1], y[2], y[3]);
#pragma unroll
                    for (int hx = 0; hx < 2; hx++) {
                        const int i = 2 * q + hx;
                        const uint32_t gg = __byte_perm(gp[i], 0, 0x1010);
                        uint2 o;
                        o.x = hadd2_bf(hmul2_bf(gg, hfma2_bf(y[2 * hx], s01, xd[i].x)), ex[i].x);
                        o.y = hadd2_bf(hmul2_bf(gg, hfma2_bf(y[2 * hx + 1], s23, xd[i].y)), ex[i].y);
                        sts64(ob + (4 * J + i) * 256 + lane * 8, o.x, o.y);
                    }
                }
                if (EPI_AT == 0) put(J);
            }
            if (EPI_AT > 0) {
                bar_sync(2, 384);
#pragma unroll 1
                for (int J = 0; J < 4; J++) put(J);
            }
            asm volatile("cp.async.bulk.commit_group;" ::: "memory");
            asm volatile("cp.async.bulk.wait_group.read 0;" ::: "memory");
            if (lead) { TSTAMP(7); TSDUMP(0x3c000cffu); }
        }
    } else if (pw < 4) {
        const int v = pw, at = tid;
        const int g = lane >> 2, t = lane & 3, mi = lane >> 3, r = lane & 7;
        const uint32_t alt = sb + (h ? ALT1 : ALT0), dalt = (h ? ALT1 : ALT0) + A_SLOT - ALT_SLOT * 4096;
        cp16(sb + OFF_GP + tid * 16, p.wr + tid * 8);
        cp16(sb + OFF_GP + 2048 + tid * 16, p.gatew + tid * 8);
        if (tid < 2) cp16(sb + M_DSK + tid * 16, p.Dskip + 16 * pr + 8 * tid);
        const unsigned epoch = ld_epoch(p.ex);
        if (tid < 24) sts128(sb + OFF_S - 384 + tid * 16, 0, 0, 0, 0);
        const unsigned tag = (epoch + 1) & 0xffffu;
        const int ftok = 2 * ((at >> 2) & 3) + (at & 1), fch = (at >> 4) + 8 * ((at >> 1) & 1);
        uint32_t eu;
        {
            cp_wait_all();
            bar_sync(7, 160);
            const uint32_t wo = sb + OFF_GP + 512 * v + 64 * ((g >> 1) & 1) + 16 * t + 4 * (g & 1);
            uint32_t w0[4], w1[4];
#pragma unroll
            for (int cb = 0; cb < 4; cb++) { w0[cb] = lds32(wo + 128 * cb); w1[cb] = lds32(wo + 128 * cb + 8); }
            const uint32_t go = sb + OFF_GP + 2048 + 512 * v + 64 * (g & 1) + 16 * t;
            const uint32_t ro = sb + M_RG + (g >> 1) * 32 + (2 * v + (g & 1)) * 4;
            const uint32_t xo = sb + OFF_RING + X_SLOT * 4096 + (g >> 1) * 2048 + 512 * v + 64 * (g & 1) + 16 * t;
            const uint32_t one0 = 0x3F803F80u ^ p.zero, one1 = 0x3F803F80u + p.zero;
            auto row_sum = [&](uint32_t a) {
                const uint4 x = lds128(a), y = lds128(a + 16);
                return ((__uint_as_float(x.x) + __uint_as_float(x.y)) + (__uint_as_float(x.z) + __uint_as_float(x.w)))
                     + ((__uint_as_float(y.x) + __uint_as_float(y.y)) + (__uint_as_float(y.z) + __uint_as_float(y.w)));
            };
            const int n0 = 32 * (v >> 1) + 4 * (v & 1), dl = 8 * (r >> 1) + 4 - 2 * mi - (r & 1);
            const uint32_t so = sb + OFF_S + (n0 + (dl >> 5)) * 1024 + (dl & 7) * 128 + ((dl >> 3) & 3) * 32 + (((dl & 1) ^ h) << 4);
            uint32_t xr[16][4], mx = 0, idb = 0;
            auto slice = [&](int k) { ldsm4t(so + (8 * (k >> 2) + (k & 3)) * 1024, xr[k][0], xr[k][1], xr[k][2], xr[k][3]); };
            auto to_half = [&](uint32_t (&q)[4]) {
                float f0[4], f1[4];
                widen_bf(f0, q[0], q[1], idb); widen_bf(f1, q[2], q[3], idb);
                q[0] = pack_h(f0[0], f0[1]); q[1] = pack_h(f0[2], f0[3]); q[2] = pack_h(f1[0], f1[1]); q[3] = pack_h(f1[2], f1[3]);
            };
            auto track = [&](int k) { mx = amax2_bf(amax2_bf(mx, amax2_bf(xr[k][0], xr[k][1])), amax2_bf(xr[k][2], xr[k][3])); };
            auto cta_exp = [&](uint32_t slot) {
                const uint4 m4 = lds128(slot);
                return max(max(m4.x, m4.y), max(m4.z, m4.w)) >> 7;
            };
            auto set_scale = [&]() { const uint32_t sc = (257u - eu) << 7; idb = (g == 2 * t) ? sc : (g == 2 * t + 1) ? sc << 16 : 0u; };
            uint4 x[4], gw[4];
#pragma unroll
            for (int cb = 0; cb < 4; cb++) gw[cb] = lds128(go + 128 * cb);
            auto gate = [&](int i) {
                float e0[4] = {0.f, 0.f, 0.f, 0.f}, e1[4] = {0.f, 0.f, 0.f, 0.f};
#pragma unroll
                for (int cb = 0; cb < 4; cb++)
                    mma_bf((cb & 1) ? e1 : e0, hmul2_bf(x[cb].x, gw[cb].x), hmul2_bf(x[cb].y, gw[cb].y), hmul2_bf(x[cb].z, gw[cb].z), hmul2_bf(x[cb].w, gw[cb].w), one0, one1);
                if (t == 0) stsf(ro + 512 + 128 * i, (e0[0] + e0[3]) + (e1[0] + e1[3]));
            };
#pragma unroll
            for (int i = 0; i < 4; i++) {
                if (i == 0) mbar_spin(bars + 8 * B_X); else mbar_wait_n<2, 8 * (B_X - B_S + 1)>(bars + 8 * (B_S + i - 1));
#pragma unroll
                for (int cb = 0; cb < 4; cb++) x[cb] = lds128(xo + 8192 * i + 128 * cb);
#pragma unroll
                for (int k = max(4 * i - 4, 1); k < 4 * i; k++) slice(k);
                float d0[4] = {0.f, 0.f, 0.f, 0.f}, d1[4] = {0.f, 0.f, 0.f, 0.f};
#pragma unroll
                for (int cb = 0; cb < 4; cb++) mma_bf((cb & 1) ? d1 : d0, x[cb].x, x[cb].y, x[cb].z, x[cb].w, w0[cb], w1[cb]);
                if (t == (g & 1)) stsf(ro + 128 * i, (d0[0] + d0[3]) + (d1[0] + d1[3]));
                if (i == 3) break;
                gate(i);
#pragma unroll
                for (int k = max(4 * i - 4, 1); k < 4 * i; k++) track(k);
                if (i == 2) {
                    const uint32_t wm = warp_max16(mx);
                    if (lane == 0) sts32(sb + M_MX + v * 4, wm);
                    bar_sync(1, 128);
                    eu = min(cta_exp(sb + M_MX) + 3u, 255u);
                    set_scale();
#pragma unroll
                    for (int k = 1; k < 8; k++) to_half(xr[k]);
                }
            }
            bar_sync(4, 256);
            if (at < 16) {
                const uint32_t rb = pack_bf(0.f, row_sum(sb + M_RG + at * 32));
                st_gpu32((uint32_t*)p.ex->r + 16 * c + at, ((rb ^ (((int)rb >> 31) | 0x80000000u)) & 0xffff0000u) | tag);
            }
            if (at == 32) mbar_arrive(bars + 8 * B_XF);
            if (at == 0) TSTAMP(8);
#pragma unroll
            for (int k = 8; k < 12; k++) { track(k); to_half(xr[k]); }
            mbar_spin(bars + 8 * (B_S + 3));
            if (at == 0) TSTAMP(9);
#pragma unroll
            for (int k = 12; k < 17; k++) slice(k & 15);
            uint32_t utail = 0;
            if (at < 64 && r >= 5) utail = lds16(sb + OFF_S + 63 * 1024 + 96 + (12 - r) * 128 + (((r & 1) ^ h) << 4) + 2 * (at >> 3));
#pragma unroll
            for (int k = 12; k < 17; k++) track(k & 15);
            const uint32_t wm = warp_max16(amax2_bf(mx, utail));
            if (lane == 0) sts32(sb + M_MX + 16 + v * 4, wm);
#pragma unroll
            for (int k = 12; k < 17; k++) to_half(xr[k & 15]);
            mbar_spin(bars + 8 * B_KD);
            const uint32_t uo = sb + OFF_U + g * U_CH + t * U_PL;
#pragma unroll
            for (int k = 1; k < 17; k++) sts128(uo + (8 + n0 + 8 * ((k & 15) >> 2) + (k & 3)) * 16, xr[k & 15][0], xr[k & 15][1], xr[k & 15][2], xr[k & 15][3]);
            sts128(uo + v * 32, 0, 0, 0, 0); sts128(uo + v * 32 + 16, 0, 0, 0, 0);
            bar_sync(1, 128);
            const uint32_t ea = cta_exp(sb + M_MX + 16);
            if (ea > eu) {
                eu = ea;
                set_scale();
#pragma unroll 1
                for (int k = 0; k < 16; k++) {
                    uint32_t q[4];
                    ldsm4t(so + (8 * (k >> 2) + (k & 3)) * 1024, q[0], q[1], q[2], q[3]);
                    to_half(q);
                    sts128(uo + (8 + n0 + 8 * (k >> 2) + (k & 3)) * 16, q[0], q[1], q[2], q[3]);
                }
            }
            if (at < 64) sts16(sb + OFF_U + (at >> 3) * U_CH + 72 * 16 + r * 2, pack_h(bf_lo(utail) * bf_lo((257u - eu) << 7), 0.f));
            __syncwarp();
            if (lane == 0) mbar_arrive(bars + 8 * B_U);
#pragma unroll
            for (int cb = 0; cb < 4; cb++) gw[cb] = lds128(go + 128 * cb);
            gate(3);
            bar_sync(1, 128);
            if (at < 16) st_gpu32((uint32_t*)p.ex->g + 1024 * h + 16 * (8 * (pr & 7) + (pr >> 3)) + at,
                                  (pack_bf(sigmoid_f(bf_round(row_sum(sb + M_RG + 512 + at * 32))), 0.f) & 0xffffu) | (tag << 16));
            if (at == 0) TSTAMP(23);
        }
        const int ct = v & 1, kh = v >> 1;
        uint32_t wa[GU_PRE][4][4];
        uint32_t ta, tb;
        {
            const int krow0 = 8 * (mi >> 1) + r;
            const uint32_t off0 = krow0 * 64 + (((2 * ct + (mi & 1)) ^ ((krow0 >> 1) & 3)) << 4);
            ta = sb + OFF_RING + kh * 4096 + off0 + p.swap_gu; tb = ta + 2048 - 2 * p.swap_gu;
        }
        auto gu_load = [&](uint32_t (&a)[4][4], int s) {
            const uint32_t o = s * 8192 + (s > 10 ? -NSLOT * 4096 : s == 10 ? (kh ? -NSLOT * 4096 : dalt) : s == 9 ? dalt : s == 8 ? (kh ? dalt : 0) : 0);
            ldsm4t(ta + o, a[0][0], a[0][1], a[0][2], a[0][3]);
            ldsm4t(tb + o, a[1][0], a[1][1], a[1][2], a[1][3]);
            ldsm4t(ta + o + 1024, a[2][0], a[2][1], a[2][2], a[2][3]);
            ldsm4t(tb + o + 1024, a[3][0], a[3][1], a[3][2], a[3][3]);
        };
        auto gu_release = [&](const uint32_t (&a)[4][4], int s) {
            if (s < B_S - B_EMPTY && lane == 0) mbar_arrive(bars + 8 * (B_EMPTY + s) + (a[0][0] & a[1][0] & a[2][0] & a[3][0] & p.zero));
        };
        auto gu_park = [&](auto S0, auto N) {
            constexpr int s0 = decltype(S0)::value, n = decltype(N)::value;
            if (c < NGU_CTA) {
                mbar_wait_n<n, 16>(bars + 8 * kh + 16 * s0);
#pragma unroll
                for (int s = s0; s < s0 + n; s++) gu_load(wa[s], s);
#pragma unroll
                for (int s = s0; s < s0 + n; s++) gu_release(wa[s], s);
            }
        };
        gu_park(IC<0>(), IC<4>());
        asm volatile("barrier.cluster.wait.acquire.aligned;" ::: "memory");
        mbar_wait(bars + 8 * B_TS);
#pragma unroll 1
        for (int i = 0; i < 2; i++) {
            const int es = group_tables(sb + OFF_TAB + (v + 4 * i) * T_CH, lane) + (int)eu;
            if (lane < 2) { const uint32_t o = mapa(sb, lane); st_async4(o + M_SC + (8 * h + v + 4 * i) * 4, (uint32_t)min(max(es, 1), 254) << 7, o + M_BARS + 8 * B_SC); }
        }
        __syncwarp();
        if (lane == 0) mbar_arrive(bars + 8 * B_TD);
        gu_park(IC<4>(), IC<GU_PRE - 4>());
        if (c < NGU_CTA) {
            float dgt[4] = {0.f, 0.f, 0.f, 0.f}, dup[4] = {0.f, 0.f, 0.f, 0.f}, dg2[4] = {0.f, 0.f, 0.f, 0.f}, du2[4] = {0.f, 0.f, 0.f, 0.f};
            const uint32_t xo = sb + OFF_XSEL + r * XS_ROW + 64 * kh + 16 * mi;
            auto gu_mma = [&](const uint32_t (&a)[4][4], const uint32_t (&b)[4]) {
                mma_bf(dgt, a[0][0], a[0][1], a[0][2], a[0][3], b[0], b[1]);
                mma_bf(dup, a[1][0], a[1][1], a[1][2], a[1][3], b[0], b[1]);
                mma_bf(dg2, a[2][0], a[2][1], a[2][2], a[2][3], b[2], b[3]);
                mma_bf(du2, a[3][0], a[3][1], a[3][2], a[3][3], b[2], b[3]);
            };
            auto gu_batch = [&](auto S0, auto N) {
                constexpr int s0 = decltype(S0)::value, n = decltype(N)::value;
                uint32_t b[n][4];
                mbar_wait_n<n, 16>(bars + 8 * kh + 16 * s0);
#pragma unroll
                for (int i = 0; i < n; i++) { ldsm4(xo + 128 * (s0 + i), b[i][0], b[i][1], b[i][2], b[i][3]); gu_load(wa[i], s0 + i); }
#pragma unroll
                for (int i = 0; i < n; i++) gu_mma(wa[i], b[i]);
#pragma unroll
                for (int i = 0; i < n; i++) gu_release(wa[n - 1], s0 + i);
            };
            mbar_spin(bars + 8 * B_XS);
            if (at == 0) TSTAMP(12);
#pragma unroll
            for (int s = 0; s < GU_PRE; s++) { uint32_t b[4]; ldsm4(xo + 128 * s, b[0], b[1], b[2], b[3]); gu_mma(wa[s], b); }
            static_assert(GU_PRE == 6, "batches below");
            gu_batch(IC<6>(), IC<2>());
            mbar_spin(bars + 8 * (B_XS + 1));
            gu_batch(IC<8>(), IC<4>()); gu_batch(IC<12>(), IC<3>()); gu_batch(IC<15>(), IC<1>());
#pragma unroll
            for (int i = 0; i < 4; i++) { dgt[i] += dg2[i]; dup[i] += du2[i]; }
            if (at == 0) TSTAMP(13);
            const uint32_t red = sb + M_RG, hs = sb + OFF_XSEL;
            sts128(red + ((v ^ 2) * 32 + lane) * 16, __float_as_uint(kh ? dgt[0] : dgt[2]), __float_as_uint(kh ? dgt[1] : dgt[3]),
                   __float_as_uint(kh ? dup[0] : dup[2]), __float_as_uint(kh ? dup[1] : dup[3]));
            bar_sync(1, 128);
            const uint4 oth = lds128(red + at * 16);
#pragma unroll
            for (int i = 0; i < 2; i++) {
                const float gv = bf_round((kh ? dgt[2 + i] : dgt[i]) + __uint_as_float(i ? oth.y : oth.x));
                const float uv = bf_round((kh ? dup[2 + i] : dup[i]) + __uint_as_float(i ? oth.w : oth.z));
                const float sl = bf_round(gv * sigmoid_f(gv));
                uint32_t hv = pack_bf(sl * uv, 0.f) & 0xffffu;
                hv = (hv == 0x8000u) ? 0x8000u : (hv ^ 0x8000u);
                sts16(hs + (2 * t + i) * 64 + (g >> 1) * 16 + (2 * ct + kh) * 4 + (g & 1) * 2, hv);
            }
            bar_sync(1, 128);
            if (v == 0) st_gpu128(&p.ex->h[32 * c + lane], lds128(hs + lane * 16));
        }
        else mbar_wait(bars + 8 * (B_XS + 1));
        if (at == 0) TSTAMP(14);
        if (EPI_AT == 1) bar_arrive(2, 384);
        {
            uint4 hq[14];
            {
                const uint4* hsrc = &p.ex->h[(56 * h + 2 * v) * 32 + lane];
                bool ok = false;
                {
                    const int bi = lane < 14 ? lane : 0;
                    const uint4* pr1 = &p.ex->h[(56 * h + 2 * v + 8 * (bi >> 1) + (bi & 1)) * 32 + 31];
                    if (H_WAIT >= 0) mbar_wait(bars + 8 * (B_FULL + NST_GU + H_WAIT));
                    uint32_t w = lane >= 14;
#pragma unroll 1
                    for (int it = 0; it < (1 << 22); it++) {
                        if (w == 0) asm volatile("ld.relaxed.gpu.global.u32 %0, [%1];" : "=r"(w) : "l"(pr1) : "memory");
                        if (__all_sync(0xffffffffu, w != 0)) break;
                        __nanosleep(PSLEEP);
                    }
                }
                if (at == 0) TSTAMP(15);
                if (EPI_AT == 2) bar_arrive(2, 384);
#pragma unroll 1
                for (int it = 0; it < (1 << 22); it++) {
                    uint32_t mn = 0xffffffffu;
#pragma unroll
                    for (int i = 0; i < 14; i++) hq[i] = ld_gpu128(hsrc + (8 * (i >> 1) + (i & 1)) * 32);
                    mbar_wait_n<2, 8>(bars + 8 * B_SC);
                    mbar_wait_n<DN_PRE, 16>(bars + 8 * (B_FULL + NST_GU) + 8 * (v >> 1));
#pragma unroll
                    for (int i = 0; i < 14; i++) mn = min(mn, hq[i].x);
                    ok = __all_sync(0xffffffffu, mn != 0);
                    if (ok) break;
                    __nanosleep(20);
                }
                if (!ok) __trap();
            }
            if (at == 0) TSTAMP(16);
            if (EPI_AT == 3) bar_arrive(2, 384);
            float dd[4][4];
#pragma unroll
            for (int j = 0; j < 4; j++) { dd[j][0] = dd[j][1] = dd[j][2] = dd[j][3] = 0.f; }
            const int krow0 = 64 * (v & 1) + 8 * (mi >> 1) + r;
            const uint32_t td = sb + OFF_RING + (v >> 1) * 4096 + krow0 * 32 + (((mi & 1) ^ ((krow0 >> 2) & 1)) << 4);
            static_assert((NST_GU + 10) % NSLOT == 0, "stage pairs of the down projection do not straddle the end of the ring");
#pragma unroll
            for (int s = 0; s < 7; s++) {
                if (s >= DN_PRE) mbar_spin(bars + 8 * (B_FULL + NST_GU + 2 * s) + 8 * (v >> 1));
                const uint32_t tile = td + ((NST_GU + 2 * s) % NSLOT) * 4096 + ((NST_GU + 2 * s) % NSLOT >= ALT_SLOT ? dalt : 0);
                uint32_t a[4][4];
#pragma unroll
                for (int j = 0; j < 4; j++) ldsm4t(tile + j * 512, a[j][0], a[j][1], a[j][2], a[j][3]);
                mma_bf(dd[0], a[0][0], a[0][1], a[0][2], a[0][3], hq[2 * s].x, hq[2 * s].y);
                mma_bf(dd[1], a[1][0], a[1][1], a[1][2], a[1][3], hq[2 * s].z, hq[2 * s].w);
                mma_bf(dd[2], a[2][0], a[2][1], a[2][2], a[2][3], hq[2 * s + 1].x, hq[2 * s + 1].y);
                mma_bf(dd[3], a[3][0], a[3][1], a[3][2], a[3][3], hq[2 * s + 1].z, hq[2 * s + 1].w);
            }
            uint32_t ds[4];
#pragma unroll
            for (int j = 0; j < 4; j++) ds[j] = __float_as_uint((dd[0][j] + dd[1][j]) + (dd[2][j] + dd[3][j]));
            if (at == 0) TSTAMP(17);
#pragma unroll
            for (int k = 0; k < 2; k++) {
                const uint32_t o = mapa(sb, k);
                st_async16(o + OFF_DP + (128 * h + at) * 16, ds[0], ds[1], ds[2], ds[3], o + M_BARS + 8 * B_DP);
            }
            const int row = (int)lds32(sb + M_IDX + ftok * 4);
            const int w = row & 7, jj = (row >> 3) & 7, i = (row >> 6) & 15;
            const float xv = bf_lo(lds16(sb + OFF_S + (row >> 5) * 1024 + w * 128 + (jj & 3) * 32 + (((fch >> 3) ^ (w & 1)) << 4) + (fch & 7) * 2));
            const uint32_t gp = lds32(sb + OFF_GP + (8 * w + jj) * 64 + i * 4);
            const float rs = bf_round(sigmoid_f(ldsf(sb + M_RSEL + ftok * 4)));
            mbar_wait_n<4, 8>(bars + 8 * B_Y);
            const float yv = bf_lo(lds16((((fch >> 3) == h) ? sb + OFF_TAB + (fch & 7) * T_CH : alt + A_YIN + (fch & 7) * Y_CH) + (i >> 2) * 512 + (4 * w + (i & 3)) * 16 + jj * 2));
            const float a = bf_round(fmaf(yv, bf_lo(lds32(sb + M_SC + fch * 4)), bf_round(xv * bf_lo(lds16(sb + M_DSK + 2 * fch)))));
            const float ga = bf_round(bf_lo(gp) * a);
            mbar_spin(bars + 8 * B_DP);
            float tot = 0.f;
#pragma unroll
            for (int k = 0; k < 8; k++) tot -= ldsf(sb + OFF_DP + k * 512 + at * 4);
            if ((row >> 10) == h) {
                const float b = bf_round(xv + bf_round(bf_round(tot) * rs));
                p.out[(size_t)row * D_ + 16 * pr + fch] = __float2bfloat16_rn(ga + bf_round(bf_hi(gp) * b));
            }
        }
        if (at == 0) { TSTAMP(18); TSDUMP(c < NGU_CTA ? 0x0087f300u : 0x0087c300u); if (c == 0) *(volatile unsigned*)&p.ex->epoch = epoch + 1; }
    } else {
        const uint32_t t_start = now_ns();
        asm volatile("setmaxnreg.dec.sync.aligned.u32 " HELP_REGS ";");
        if (pw != 12) {
            if (pw >= 14) {
#pragma unroll
                for (int k = 0; k < 5; k++) {
                    const int w = 1 + 2 * k, e = (tid & 63) - 32;
                    sts32(sb + OFF_BAND + k * 256 + (tid & 63) * 4, ((e >= 0 && e < w) ? 0x3C00u : 0u) | ((e + 1 >= 0 && e + 1 < w) ? 0x3C000000u : 0u));
                }
            } else {
                sts32(sb + M_BMAP + lane * 4, 0);
                if (c < NGU_CTA) {
                    st_gpu128(&p.ex->h[32 * c + lane], make_uint4(0, 0, 0, 0));
                    if (ld_gpu128(&p.ex->h[32 * c + lane]).x != 0) __trap();
                }
            }
        } else {
            if (lane == 0) {
#pragma unroll
                for (int k = B_S; k < NBAR; k++) mbar_init(bars + 8 * k, (k >= B_Y && k < B_KD) ? 9 : (k == B_KD || k == B_TS) ? 8 : (k == B_TD || k == B_U) ? 4 : k == B_XS + 1 ? 2 : 1);
#pragma unroll
                for (int k = B_S; k < B_XS; k++) mbar_expect(bars + 8 * k, 16384);
                asm volatile("fence.proxy.async.shared::cta;" ::: "memory");
                asm volatile("fence.mbarrier_init.release.cluster;" ::: "memory");
            }
            __syncwarp();
            asm volatile("barrier.cluster.arrive.relaxed.aligned;" ::: "memory");
            auto rows = [&](int i) {
                mbar_expect(bars + 8 * (B_X + i), 8192);
                tma4d(sb + OFF_RING + X_SLOT * 4096 + i * 8192, &tm_r, 0, 0, 16 * h + 4 * i, pr, bars + 8 * (B_X + i));
            };
            if (lane == 0) {
                asm volatile("prefetch.tensormap [%0];" :: "l"(&tm_x) : "memory");
#pragma unroll 1
                for (int i = 0; i < X_LEAD; i++) rows(i);
            }
            __syncwarp();
            bar_arrive(7, 160);
            asm volatile("barrier.cluster.wait.acquire.aligned;" ::: "memory");
            if (lane == 0) {
                TSTAMP(20);
#pragma unroll 1
                for (int i = 0; i < 4; i++) {
                    tma4d_both(sb + OFF_S + (4 * h + i) * 8192, &tm_x, 16 * pr, 0, 0, 32 * h + 8 * i, bars + 8 * (B_S + i));
                    if (i + X_LEAD < 4) rows(i + X_LEAD);
                }
                TSTAMP(24);
                asm volatile("prefetch.tensormap [%0];" :: "l"(&tm_gu) : "memory");
                asm volatile("prefetch.tensormap [%0];" :: "l"(&tm_down) : "memory");
                asm volatile("prefetch.tensormap [%0];" :: "l"(&tm_o) : "memory");
#pragma unroll
                for (int k = 0; k < B_S; k++) mbar_init(bars + 8 * k, k < B_EMPTY ? 1 : 4);
#pragma unroll
                for (int k = B_XS; k < B_KD; k++) if (k != B_TD && k != B_G) mbar_expect(bars + 8 * k, k < B_TD ? (c < NGU_CTA ? 8192 : 0) : k == B_SC ? 64 : 4096);
                asm volatile("fence.proxy.async.shared::cta;" ::: "memory");
            }
            __syncwarp();
        }
        bar_arrive(4, 256);
        bar_sync(6, 128);
        if (pw == 15) {
            const unsigned tag = (ld_epoch(p.ex) + 1) & 0xffffu;
            const int tok = lane & 7;
            uint32_t top = 0;
            bool ok = false;
            mbar_wait(bars + 8 * B_XF);
#pragma unroll 1
            for (int it = 0; it < (1 << 22); it++) {
                uint32_t tg;
                asm volatile("ld.relaxed.gpu.global.v2.u32 {%0,%1}, [%2];" : "=r"(top), "=r"(tg) : "l"(&p.ex->top[tok]) : "memory");
                ok = __all_sync(0xffffffffu, tg == tag);
                if (ok) break;
            }
            if (!ok) __trap();
            if (lane == 0) TSTAMP(25);
            const int row = 2047 - (int)(top & 0xffffu);
            if (c < NGU_CTA) {
#pragma unroll
                for (int k = 0; k < 8; k++) {
                    const int tk = 4 * h + ((k + pr) & 3), hf = k >> 2;
                    bulk_load_both(sb + OFF_XSEL + tk * XS_ROW + 1024 * hf, p.u + (size_t)__shfl_sync(0xffffffffu, row, tk) * D_ + 512 * hf, 1024, bars + 8 * (B_XS + hf));
                }
            }
            if (lane == 0) TSTAMP(21);
            if (lane < 8) {
                const uint32_t ord = top >> 16;
                sts32(sb + M_RSEL + tok * 4, ((ord & 0x8000u) ? (ord & 0x7fffu) : (~ord & 0xffffu)) << 16);
                sts32(sb + M_IDX + tok * 4, (uint32_t)row);
                if ((row >> 10) == h) asm volatile("red.shared.or.b32 [%0], %1;" :: "r"(sb + M_BMAP + (row & 7) * 16 + ((row >> 4) & 3) * 4),
                                                   "r"(1u << (((row >> 6) & 15) + 2 * (row & 8))) : "memory");
            }
            __syncwarp();
            if (lane == 0) { mbar_arrive(bars + 8 * (B_XS + 1)); TSDUMP(0x02200000u); }
            mbar_wait(bars + 8 * B_TD);
#pragma unroll 1
            for (int i = 0, it = 0; i < 8; ) {
                const uint4 a = ld_gpu128(&p.ex->g[256 * h + 32 * i + lane]), b = ld_gpu128(&p.ex->g[256 * h + 32 * i + 32 + lane]);
                uint32_t gv[8] = {a.x, a.y, a.z, a.w, b.x, b.y, b.z, b.w}, bad = 0;
#pragma unroll
                for (int k = 0; k < 8; k++) { bad |= gv[k] ^ (tag << 16); gv[k] = (gv[k] & 0xffffu) | (pack_bf(1.f - bf_lo(gv[k]), 0.f) << 16); }
                sts128(sb + OFF_GP + (32 * i + lane) * 16, gv[0], gv[1], gv[2], gv[3]);
                sts128(sb + OFF_GP + (32 * i + 32 + lane) * 16, gv[4], gv[5], gv[6], gv[7]);
                if (__all_sync(0xffffffffu, (bad >> 16) == 0)) i += 2;
                else if (++it > (1 << 22)) __trap();
            }
            if (lane == 0) mbar_arrive(bars + 8 * B_G);
            return;
        }
        if (lane != 0) return;
        const int s0 = c < NGU_CTA ? 0 : NST_GU;
        if (T_W == 0) mbar_wait(bars + 8 * (B_S + W_START));
        if (pw == 12) TSTAMP(22);
#pragma unroll 1
        for (int s = s0 + pw - 12; s < NST; s += 3) {
            const int slot = s < NSLOT ? s : s < 2 * NSLOT ? s - NSLOT : s - 2 * NSLOT;
            const uint32_t full = bars + 8 * (B_FULL + s), dst = sb + OFF_RING + slot * 4096 + (slot >= ALT_SLOT ? (h ? ALT1 : ALT0) + A_SLOT - ALT_SLOT * 4096 : 0);
            if (s >= X_SLOT) mbar_wait(bars + 8 * ((s >= s0 + NSLOT) ? B_EMPTY + ((s - NSLOT) >> 1) : slot >= ALT_SLOT ? B_U : B_XF));
            mbar_expect(full, 4096);
            if (T_W > 0) {
                const uint32_t due = T_W + DT_G * s + (s > NST_GU ? (DT_D - DT_G) * (s - NST_GU) : 0);
#pragma unroll 1
                for (int n = 0; n < 100000; n++) {
                    const int left = (int)(due - (now_ns() - t_start));
                    if (left <= 0) break;
                    __nanosleep(left > 100 ? left >> 1 : 20);
                }
            }
            if (s < NST_GU) {
                if (s >= DEPTH_E) mbar_spin(full - 8 * (s < EARLY ? DEPTH_E : DEPTH));
                tma3d(dst, &tm_gu, 32 * c, 32 * s, 0, full);
            } else {
                if (s >= s0 + DEPTH_D) mbar_spin(full - 8 * DEPTH_D);

                tma2d(dst, &tm_down, 16 * pr, 1792 * h + 128 * (s - NST_GU), full);
            }
        }
        if (pw == 12) TSDUMP(0x01500000u);
    }
}

typedef CUresult (*EncodeFn)(CUtensorMap*, CUtensorMapDataType, cuuint32_t, void*, const cuuint64_t*, const cuuint64_t*,
                             const cuuint32_t*, const cuuint32_t*, CUtensorMapInterleave, CUtensorMapSwizzle,
                             CUtensorMapL2promotion, CUtensorMapFloatOOBfill);

void make_map(EncodeFn f, CUtensorMap* m, const void* ptr, int rank, const cuuint64_t* dims, const cuuint64_t* strides, const cuuint32_t* box, CUtensorMapSwizzle sw,
              CUtensorMapL2promotion promo = CU_TENSOR_MAP_L2_PROMOTION_L2_128B) {
    const cuuint32_t es[4] = {1, 1, 1, 1};
    f(m, CU_TENSOR_MAP_DATA_TYPE_BFLOAT16, rank, (void*)ptr, dims, strides, box, es, CU_TENSOR_MAP_INTERLEAVE_NONE, sw,
      promo, CU_TENSOR_MAP_FLOAT_OOB_FILL_NONE);
}

}

extern "C" void kernel_launch(void* const* d_in, const int* in_sizes, int n_in, void* d_out, int out_size) {
    static EncodeFn enc = nullptr;
    static void* ex = nullptr;
    if (!enc) {
        void* fn = nullptr;
        cudaDriverEntryPointQueryResult qr;
        cudaGetDriverEntryPoint("cuTensorMapEncodeTiled", &fn, cudaEnableDefault, &qr);
        enc = (EncodeFn)fn;
        cudaFuncSetAttribute(fused_kernel, cudaFuncAttributeMaxDynamicSharedMemorySize, SMEM_BYTES);
        cudaGetSymbolAddress(&ex, g_ex);
    }
    CUtensorMap tgu, td, tx, tr, to;
    const char *wg = (const char*)d_in[9], *wu = (const char*)d_in[10];
    const bool swap = wu < wg;
    {
        const cuuint64_t dims[3] = {F_, D_, 2}, str[2] = {F_ * 2, (cuuint64_t)(swap ? wg - wu : wu - wg)};
        const cuuint32_t box[3] = {32, 32, 2};
        make_map(enc, &tgu, swap ? wu : wg, 3, dims, str, box, CU_TENSOR_MAP_SWIZZLE_64B);
    }
    {
        const cuuint64_t dims[2] = {D_, F_}, str[1] = {D_ * 2};
        const cuuint32_t box[2] = {16, 128};
        make_map(enc, &td, d_in[11], 2, dims, str, box, CU_TENSOR_MAP_SWIZZLE_32B, PROMO_D);
    }
    {
        const cuuint64_t dims[4] = {D_, 4, 8, L_ / 32}, str[3] = {D_ * 2 * 8, D_ * 2, D_ * 2 * 32};
        const cuuint32_t box[4] = {16, 4, 8, 8};
        make_map(enc, &tx, d_in[0], 4, dims, str, box, CU_TENSOR_MAP_SWIZZLE_32B);
    }
    {
        const cuuint64_t dims[4] = {256, 4, L_ / 64, 64}, str[3] = {512, D_ * 2 * 64, D_ * 2};
        const cuuint32_t box[4] = {256, 4, 4, 1};
        make_map(enc, &tr, d_in[0], 4, dims, str, box, CU_TENSOR_MAP_SWIZZLE_NONE);
    }
    {
        const cuuint64_t dims[3] = {D_, L_ / 8, 8}, str[2] = {D_ * 2 * 8, D_ * 2};
        const cuuint32_t box[3] = {16, 32, 1};
        make_map(enc, &to, d_out, 3, dims, str, box, CU_TENSOR_MAP_SWIZZLE_NONE);
    }
    Params p;
    p.u = (const bf16*)d_in[0]; p.logA = (const bf16*)d_in[1]; p.Aim = (const bf16*)d_in[2];
    p.Cre = (const bf16*)d_in[3]; p.Cim = (const bf16*)d_in[4]; p.logdt = (const bf16*)d_in[5];
    p.Dskip = (const bf16*)d_in[6]; p.wr = (const bf16*)d_in[8]; p.gatew = (const bf16*)d_in[12];
    p.out = (bf16*)d_out;
    p.ex = (Exchange*)ex;
    p.zero = 0;
    p.swap_gu = swap ? 2048 : 0;
    fused_kernel<<<NCTA, NTHREADS, SMEM_BYTES>>>(p, tgu, td, tx, tr, to);
}
```

```cpp
#include <cuda_runtime.h>
#include <cuda_bf16.h>
#include <cuda_fp16.h>
#include <cuda.h>
#include <stdint.h>

typedef __nv_bfloat16 bf16;

namespace {

constexpr int L_ = 2048, D_ = 1024, F_ = 3584;
constexpr int NCTA = 130;
constexpr int NTHREADS = 512;
constexpr int MAIN_W0 = 4;
#define T_W 1600
#define DT_G 316
#define DT_D 344
#define DEPTH_G 5
#define DEPTH_D 3
#define H_WAIT 2
#define DN_PRE 5
#define PSLEEP 0
#define GU_BATCH 0
#define FENCES 16
#define MIX0_AT 2
#define MIX1_AT 4
#define A_REUSE 0
#define MAIN_REGS "176"
#define HELP_REGS "32"
constexpr int GU_PRE = 6;
constexpr int NGU_CTA = 112;

constexpr int NSLOT    = 10;
constexpr int NST_GU   = 16, NST = 23;
constexpr int OFF_RING = 0;
constexpr int OFF_XROW = 53248, X_SLOT = 6;
constexpr int OFF_XSEL = 69632, XS_ROW = 2064;
constexpr int OFF_DP   = OFF_XSEL + 8192;
constexpr int OFF_S    = 87040;
constexpr int ALT0     = OFF_S + 32768, ALT1 = OFF_S - 512;
constexpr int A_YIN    = 32, Y_CH = 2064;
constexpr int A_SLOT   = 16896, ALT_SLOT = 8;
constexpr int U_PL     = 1184;
constexpr int U_CH     = 4752;
constexpr int OFF_U    = 153088;
constexpr int T_CH     = 4112;
constexpr int OFF_TAB  = 191104;
constexpr int T_R2     = 2176, T2_S = 208;
constexpr int T_R3     = 3040, T3_S = 336;
constexpr int OFF_GP   = 224000;
constexpr int OFF_BAND = 228096;
constexpr int OFF_MISC = 229376;
constexpr int M_BARS   = OFF_MISC;
constexpr int M_IDX    = OFF_MISC + 704;
constexpr int M_RSEL   = OFF_MISC + 736;
constexpr int M_BMAP   = OFF_MISC + 768;
constexpr int M_MX     = OFF_MISC + 896;
constexpr int M_SC     = OFF_MISC + 960;
constexpr int M_RG     = OFF_MISC + 1024;
constexpr int SMEM_BYTES = OFF_MISC + 3072;

constexpr int B_FULL = 0, B_EMPTY = NST, B_S = B_EMPTY + NST - NSLOT, B_XS = B_S + 4, B_TD = B_XS + 2, B_SC = B_TD + 1, B_G = B_SC + 1, B_GL = B_G + 1, B_DP = B_GL + 1, B_Y = B_DP + 1,
              B_KD = B_Y + 4, B_U = B_KD + 1, B_TS = B_U + 1, B_XF = B_TS + 1, B_X = B_XF + 1, NBAR = B_X + 4;
static_assert(NBAR <= 84, "barrier area");

struct Exchange {
    unsigned epoch, pad[31];
    uint4 h[8 * F_ / 8];
    uint4 r[L_ / 4];
    uint4 g[L_ / 4];
    uint2 top[16];
};
__device__ __align__(128) Exchange g_ex;

struct Params {
    const bf16 *u, *logA, *Aim, *Cre, *Cim, *logdt, *Dskip, *wr, *gatew;
    bf16* out;
    Exchange* ex;
    uint32_t zero;
    uint32_t swap_gu;
};

#define TSTAMP(i) do {} while (0)
#define CSTAMP(i) do {} while (0)
#define TSDUMP(mask) do {} while (0)
#define DBG_PARAMS
#define DBG_ARGS

__device__ __forceinline__ uint32_t smem_u32(const void* p) { return (uint32_t)__cvta_generic_to_shared(p); }
__device__ __forceinline__ void mbar_init(uint32_t b, uint32_t c) { asm volatile("mbarrier.init.shared::cta.b64 [%0], %1;" :: "r"(b), "r"(c) : "memory"); }
__device__ __forceinline__ void mbar_expect(uint32_t b, uint32_t tx) { asm volatile("mbarrier.arrive.expect_tx.shared::cta.b64 _, [%0], %1;" :: "r"(b), "r"(tx) : "memory"); }
__device__ __forceinline__ void mbar_arrive(uint32_t b) { asm volatile("mbarrier.arrive.shared::cta.b64 _, [%0];" :: "r"(b) : "memory"); }
#define WSLEEP "40"
__device__ __forceinline__ void mbar_wait(uint32_t b) {
    asm volatile("{\n\t.reg .pred p, q;\n\t.reg .u32 n;\n\tmov.u32 n, 0;\n"
                 "W%=:\n\tmbarrier.try_wait.parity.shared::cta.b64 p, [%0], 0;\n\t"
                 "@p bra D%=;\n\tnanosleep.u32 " WSLEEP ";\n\tadd.u32 n, n, 1;\n\tsetp.lt.u32 q, n, 4194304;\n\t@q bra W%=;\n"
                 "D%=:\n\t}" :: "r"(b) : "memory");
}
__device__ __forceinline__ void mbar_spin(uint32_t b) {
    asm volatile("{\n\t.reg .pred p, q;\n\t.reg .u32 n;\n\tmov.u32 n, 0;\n"
                 "W%=:\n\tmbarrier.try_wait.parity.shared::cta.b64 p, [%0], 0;\n\t"
                 "@p bra D%=;\n\tadd.u32 n, n, 1;\n\tsetp.lt.u32 q, n, 4194304;\n\t@q bra W%=;\n"
                 "D%=:\n\t}" :: "r"(b) : "memory");
}
template <int N, int STEP>
__device__ __forceinline__ void mbar_wait_n(uint32_t b) {
#pragma unroll 1
    for (int n = 0; n < 4194304; n++) {
        uint32_t ok = 1;
#pragma unroll
        for (int i = 0; i < N; i++) {
            uint32_t d;
            asm volatile("{ .reg .pred p; mbarrier.try_wait.parity.shared::cta.b64 p, [%1], 0; selp.u32 %0, 1, 0, p; }" : "=r"(d) : "r"(b + STEP * i) : "memory");
            ok &= d;
        }
        if (ok) break;
    }
}
__device__ __forceinline__ unsigned ld_epoch(const Exchange* e) { unsigned v; asm volatile("ld.volatile.global.u32 %0, [%1];" : "=r"(v) : "l"(e) : "memory"); return v; }
__device__ __forceinline__ uint32_t now_ns() { uint32_t t; asm volatile("mov.u32 %0, %globaltimer_lo;" : "=r"(t)); return t; }
__device__ __forceinline__ uint32_t mapa(uint32_t addr, uint32_t rank) { uint32_t r; asm("mapa.shared::cluster.u32 %0, %1, %2;" : "=r"(r) : "r"(addr), "r"(rank)); return r; }
__device__ __forceinline__ void bulk_load(uint32_t dst, const void* src, uint32_t bytes, uint32_t bar) {
    asm volatile("cp.async.bulk.shared::cluster.global.mbarrier::complete_tx::bytes [%0], [%1], %2, [%3];" :: "r"(dst), "l"(src), "r"(bytes), "r"(bar) : "memory");
}
__device__ __forceinline__ void bulk_load_both(uint32_t dst, const void* src, uint32_t bytes, uint32_t bar) {
    asm volatile("{ .reg .pred p; elect.sync _|p, 0xffffffff;\n\t@p cp.async.bulk.shared::cluster.global.mbarrier::complete_tx::bytes.multicast::cluster [%0], [%1], %2, [%3], %4; }"
                 :: "r"(dst), "l"(src), "r"(bytes), "r"(bar), "h"((unsigned short)3) : "memory");
}
__device__ __forceinline__ void tma2d_warp(uint32_t dst, const CUtensorMap* tm, int c0, int c1, uint32_t bar) {
    asm volatile("{ .reg .pred p; elect.sync _|p, 0xffffffff;\n\t@p cp.async.bulk.tensor.2d.shared::cluster.global.mbarrier::complete_tx::bytes [%0], [%1, {%3, %4}], [%2]; }"
        :: "r"(dst), "l"(tm), "r"(bar), "r"(c0), "r"(c1) : "memory");
}
__device__ __forceinline__ void tma3d_warp(uint32_t dst, const CUtensorMap* tm, int c0, int c1, int c2, uint32_t bar) {
    asm volatile("{ .reg .pred p; elect.sync _|p, 0xffffffff;\n\t@p cp.async.bulk.tensor.3d.shared::cluster.global.mbarrier::complete_tx::bytes [%0], [%1, {%3, %4, %5}], [%2]; }"
        :: "r"(dst), "l"(tm), "r"(bar), "r"(c0), "r"(c1), "r"(c2) : "memory");
}
__device__ __forceinline__ void tma4d(uint32_t dst, const CUtensorMap* tm, int c0, int c1, int c2, int c3, uint32_t bar) {
    asm volatile("cp.async.bulk.tensor.4d.shared::cluster.global.mbarrier::complete_tx::bytes [%0], [%1, {%3, %4, %5, %6}], [%2];"
        :: "r"(dst), "l"(tm), "r"(bar), "r"(c0), "r"(c1), "r"(c2), "r"(c3) : "memory");
}
__device__ __forceinline__ void tma4d_both(uint32_t dst, const CUtensorMap* tm, int c0, int c1, int c2, int c3, uint32_t bar) {
    asm volatile("cp.async.bulk.tensor.4d.shared::cluster.global.mbarrier::complete_tx::bytes.multicast::cluster [%0], [%1, {%3, %4, %5, %6}], [%2], %7;"
        :: "r"(dst), "l"(tm), "r"(bar), "r"(c0), "r"(c1), "r"(c2), "r"(c3), "h"((unsigned short)3) : "memory");
}
__device__ __forceinline__ void st_async16(uint32_t dst, uint32_t x, uint32_t y, uint32_t z, uint32_t w, uint32_t bar) {
    asm volatile("st.async.weak.shared::cluster.mbarrier::complete_tx::bytes.v4.b32 [%0], {%1,%2,%3,%4}, [%5];"
                 :: "r"(dst), "r"(x), "r"(y), "r"(z), "r"(w), "r"(bar) : "memory");
}
__device__ __forceinline__ void st_async4(uint32_t dst, uint32_t v, uint32_t bar) {
    asm volatile("st.async.weak.shared::cluster.mbarrier::complete_tx::bytes.b32 [%0], %1, [%2];" :: "r"(dst), "r"(v), "r"(bar) : "memory");
}
__device__ __forceinline__ void bar_sync(int id, int n) { asm volatile("bar.sync %0, %1;" :: "r"(id), "r"(n) : "memory"); }
__device__ __forceinline__ void bar_arrive(int id, int n) { asm volatile("bar.arrive %0, %1;" :: "r"(id), "r"(n) : "memory"); }
__device__ __forceinline__ void cp16(uint32_t dst, const void* src) { asm volatile("cp.async.cg.shared.global [%0], [%1], 16;" :: "r"(dst), "l"(src) : "memory"); }
__device__ __forceinline__ void cp_wait_all() { asm volatile("cp.async.wait_all;" ::: "memory"); }
__device__ __forceinline__ uint32_t ldg16(const void* p) { uint32_t v; asm volatile("ld.global.nc.u16 %0, [%1];" : "=r"(v) : "l"(p)); return v; }
__device__ __forceinline__ uint2 ldg64(const void* p) { uint2 v; asm volatile("ld.global.nc.v2.u32 {%0,%1}, [%2];" : "=r"(v.x), "=r"(v.y) : "l"(p)); return v; }
__device__ __forceinline__ uint4 ldg128(const void* p) { uint4 v; asm volatile("ld.global.nc.v4.u32 {%0,%1,%2,%3}, [%4];" : "=r"(v.x), "=r"(v.y), "=r"(v.z), "=r"(v.w) : "l"(p)); return v; }
__device__ __forceinline__ uint4 ld_gpu128(const void* p) { uint4 v; asm volatile("ld.relaxed.gpu.global.v4.u32 {%0,%1,%2,%3}, [%4];" : "=r"(v.x), "=r"(v.y), "=r"(v.z), "=r"(v.w) : "l"(p) : "memory"); return v; }
__device__ __forceinline__ void st_gpu32(void* p, uint32_t v) { asm volatile("st.relaxed.gpu.global.u32 [%0], %1;" :: "l"(p), "r"(v) : "memory"); }
__device__ __forceinline__ void st_gpu128(void* p, const uint4& v) { asm volatile("st.relaxed.gpu.global.v4.u32 [%0], {%1,%2,%3,%4};" :: "l"(p), "r"(v.x), "r"(v.y), "r"(v.z), "r"(v.w) : "memory"); }

__device__ __forceinline__ void ldsm4(uint32_t a, uint32_t& r0, uint32_t& r1, uint32_t& r2, uint32_t& r3) {
    asm volatile("ldmatrix.sync.aligned.m8n8.x4.shared.b16 {%0,%1,%2,%3}, [%4];" : "=r"(r0), "=r"(r1), "=r"(r2), "=r"(r3) : "r"(a) : "memory");
}
__device__ __forceinline__ void ldsm2(uint32_t a, uint32_t& r0, uint32_t& r1) {
    asm volatile("ldmatrix.sync.aligned.m8n8.x2.shared.b16 {%0,%1}, [%2];" : "=r"(r0), "=r"(r1) : "r"(a) : "memory");
}
__device__ __forceinline__ void ldsm4t(uint32_t a, uint32_t& r0, uint32_t& r1, uint32_t& r2, uint32_t& r3) {
    asm volatile("ldmatrix.sync.aligned.m8n8.x4.trans.shared.b16 {%0,%1,%2,%3}, [%4];" : "=r"(r0), "=r"(r1), "=r"(r2), "=r"(r3) : "r"(a) : "memory");
}
__device__ __forceinline__ uint32_t lds16(uint32_t a) { uint32_t v; asm volatile("ld.shared.u16 %0, [%1];" : "=r"(v) : "r"(a) : "memory"); return v; }
__device__ __forceinline__ uint32_t lds32(uint32_t a) { uint32_t v; asm volatile("ld.shared.u32 %0, [%1];" : "=r"(v) : "r"(a) : "memory"); return v; }
__device__ __forceinline__ uint2 lds64(uint32_t a) { uint2 v; asm volatile("ld.shared.v2.u32 {%0,%1}, [%2];" : "=r"(v.x), "=r"(v.y) : "r"(a) : "memory"); return v; }
__device__ __forceinline__ uint4 lds128(uint32_t a) { uint4 v; asm volatile("ld.shared.v4.u32 {%0,%1,%2,%3}, [%4];" : "=r"(v.x), "=r"(v.y), "=r"(v.z), "=r"(v.w) : "r"(a) : "memory"); return v; }
__device__ __forceinline__ void sts16(uint32_t a, uint32_t v) { asm volatile("st.shared.u16 [%0], %1;" :: "r"(a), "r"(v) : "memory"); }
__device__ __forceinline__ void sts32(uint32_t a, uint32_t v) { asm volatile("st.shared.u32 [%0], %1;" :: "r"(a), "r"(v) : "memory"); }
__device__ __forceinline__ void sts64(uint32_t a, uint32_t x, uint32_t y) { asm volatile("st.shared.v2.u32 [%0], {%1,%2};" :: "r"(a), "r"(x), "r"(y) : "memory"); }
__device__ __forceinline__ void sts128(uint32_t a, uint32_t x, uint32_t y, uint32_t z, uint32_t w) { asm volatile("st.shared.v4.u32 [%0], {%1,%2,%3,%4};" :: "r"(a), "r"(x), "r"(y), "r"(z), "r"(w) : "memory"); }
__device__ __forceinline__ void sts16_if(bool p, uint32_t a, uint32_t v) { asm volatile("{ .reg .pred q; setp.ne.u32 q, %2, 0; @q st.shared.u16 [%0], %1; }" :: "r"(a), "h"((unsigned short)v), "r"((uint32_t)p) : "memory"); }
__device__ __forceinline__ void sts128_if(bool p, uint32_t a, uint32_t x, uint32_t y, uint32_t z, uint32_t w) {
    asm volatile("{ .reg .pred q; setp.ne.u32 q, %5, 0; @q st.shared.v4.u32 [%0], {%1,%2,%3,%4}; }" :: "r"(a), "r"(x), "r"(y), "r"(z), "r"(w), "r"((uint32_t)p) : "memory");
}
__device__ __forceinline__ void stsf(uint32_t a, float v) { asm volatile("st.shared.f32 [%0], %1;" :: "r"(a), "f"(v) : "memory"); }
__device__ __forceinline__ float ldsf(uint32_t a) { float v; asm volatile("ld.shared.f32 %0, [%1];" : "=f"(v) : "r"(a) : "memory"); return v; }

__device__ __forceinline__ void mma_bf(float (&d)[4], uint32_t a0, uint32_t a1, uint32_t a2, uint32_t a3, uint32_t b0, uint32_t b1) {
    asm volatile("mma.sync.aligned.m16n8k16.row.col.f32.bf16.bf16.f32 {%0,%1,%2,%3}, {%4,%5,%6,%7}, {%8,%9}, {%0,%1,%2,%3};"
        : "+f"(d[0]), "+f"(d[1]), "+f"(d[2]), "+f"(d[3]) : "r"(a0), "r"(a1), "r"(a2), "r"(a3), "r"(b0), "r"(b1));
}
__device__ __forceinline__ void widen_bf(float (&d)[4], uint32_t a0, uint32_t a1, uint32_t b) {
    asm volatile("mma.sync.aligned.m16n8k8.row.col.f32.bf16.bf16.f32 {%0,%1,%2,%3}, {%4,%5}, {%6}, {%7,%7,%7,%7};"
        : "=f"(d[0]), "=f"(d[1]), "=f"(d[2]), "=f"(d[3]) : "r"(a0), "r"(a1), "r"(b), "f"(0.f));
}
__device__ __forceinline__ void widen_h(float (&d)[4], const uint32_t (&a)[2], uint32_t b) {
    asm volatile("mma.sync.aligned.m16n8k8.row.col.f32.f16.f16.f32 {%0,%1,%2,%3}, {%4,%5}, {%6}, {%7,%7,%7,%7};"
        : "=f"(d[0]), "=f"(d[1]), "=f"(d[2]), "=f"(d[3]) : "r"(a[0]), "r"(a[1]), "r"(b), "f"(0.f));
}
__device__ __forceinline__ void widen_add_h(float (&d)[4], const uint32_t (&a)[2], uint32_t b, const float (&c)[4]) {
    asm volatile("mma.sync.aligned.m16n8k8.row.col.f32.f16.f16.f32 {%0,%1,%2,%3}, {%4,%5}, {%6}, {%7,%8,%9,%10};"
        : "=f"(d[0]), "=f"(d[1]), "=f"(d[2]), "=f"(d[3]) : "r"(a[0]), "r"(a[1]), "r"(b), "f"(c[0]), "f"(c[1]), "f"(c[2]), "f"(c[3]));
}
__device__ __forceinline__ void mma_h(uint32_t (&d)[2], const uint32_t (&a)[4], uint32_t b0, uint32_t b1) {
    asm volatile("mma.sync.aligned.m16n8k16.row.col.f16.f16.f16.f16 {%0,%1}, {%2,%3,%4,%5}, {%6,%7}, {%0,%1};"
        : "+r"(d[0]), "+r"(d[1]) : "r"(a[0]), "r"(a[1]), "r"(a[2]), "r"(a[3]), "r"(b0), "r"(b1));
}
__device__ __forceinline__ void mma_h_z(uint32_t& d0, uint32_t& d1, const uint32_t (&a)[4], uint32_t b0, uint32_t b1) {
    asm volatile("mma.sync.aligned.m16n8k16.row.col.f16.f16.f16.f16 {%0,%1}, {%2,%3,%4,%5}, {%6,%7}, {%8,%8};"
        : "=r"(d0), "=r"(d1) : "r"(a[0]), "r"(a[1]), "r"(a[2]), "r"(a[3]), "r"(b0), "r"(b1), "r"(0u));
}
__device__ __forceinline__ void mma_h2(uint32_t& d0, uint32_t& d1, const uint32_t (&a)[4], uint32_t b0, uint32_t b1) {
    asm volatile("mma.sync.aligned.m16n8k16.row.col.f16.f16.f16.f16 {%0,%1}, {%2,%3,%4,%5}, {%6,%7}, {%0,%1};"
        : "+r"(d0), "+r"(d1) : "r"(a[0]), "r"(a[1]), "r"(a[2]), "r"(a[3]), "r"(b0), "r"(b1));
}
__device__ __forceinline__ void mma_h_k8(uint32_t& d0, uint32_t& d1, uint32_t a0, uint32_t a1, uint32_t b) {
    asm volatile("mma.sync.aligned.m16n8k8.row.col.f16.f16.f16.f16 {%0,%1}, {%2,%3}, {%4}, {%0,%1};" : "+r"(d0), "+r"(d1) : "r"(a0), "r"(a1), "r"(b));
}
__device__ __forceinline__ void mma_h_k8_z(uint32_t (&d)[2], uint32_t a0, uint32_t a1, uint32_t b) {
    asm volatile("mma.sync.aligned.m16n8k8.row.col.f16.f16.f16.f16 {%0,%1}, {%2,%3}, {%4}, {%5,%5};" : "=r"(d[0]), "=r"(d[1]) : "r"(a0), "r"(a1), "r"(b), "r"(0u));
}
__device__ __forceinline__ uint32_t pack_bf(float lo, float hi) { uint32_t r; asm("cvt.rn.bf16x2.f32 %0, %1, %2;" : "=r"(r) : "f"(hi), "f"(lo)); return r; }
__device__ __forceinline__ uint32_t pack_h(float lo, float hi) { uint32_t r; asm("cvt.rn.f16x2.f32 %0, %1, %2;" : "=r"(r) : "f"(hi), "f"(lo)); return r; }
__device__ __forceinline__ float bf_lo(uint32_t v) { return __uint_as_float(v << 16); }
__device__ __forceinline__ float bf_hi(uint32_t v) { return __uint_as_float(v & 0xffff0000u); }
__device__ __forceinline__ float bf_round(float x) { return __uint_as_float(pack_bf(0.f, x) & 0xffff0000u); }
__device__ __forceinline__ uint32_t hmul2_bf(uint32_t a, uint32_t b) { uint32_t r; asm("mul.rn.bf16x2 %0, %1, %2;" : "=r"(r) : "r"(a), "r"(b)); return r; }
__device__ __forceinline__ uint32_t hadd2_bf(uint32_t a, uint32_t b) { uint32_t r; asm("add.rn.bf16x2 %0, %1, %2;" : "=r"(r) : "r"(a), "r"(b)); return r; }
__device__ __forceinline__ uint32_t hfma2_bf(uint32_t a, uint32_t b, uint32_t c) { uint32_t r; asm("fma.rn.bf16x2 %0, %1, %2, %3;" : "=r"(r) : "r"(a), "r"(b), "r"(c)); return r; }
__device__ __forceinline__ uint32_t hi_mul_bf(uint32_t a, uint32_t b) { uint32_t r; asm("{ .reg .b16 l, h; .reg .b32 t; mov.b32 {l, h}, %1; mov.b32 t, {h, h}; mul.rn.bf16x2 %0, t, %2; }" : "=r"(r) : "r"(a), "r"(b)); return r; }
__device__ __forceinline__ uint32_t lo_fma_bf(uint32_t a, uint32_t b, uint32_t c) { uint32_t r; asm("{ .reg .b16 l, h; .reg .b32 t; mov.b32 {l, h}, %1; mov.b32 t, {l, l}; fma.rn.bf16x2 %0, t, %2, %3; }" : "=r"(r) : "r"(a), "r"(b), "r"(c)); return r; }
__device__ __forceinline__ uint32_t amax2_bf(uint32_t m, uint32_t v) { uint32_t r; asm("max.xorsign.abs.bf16x2 %0, %1, %2;" : "=r"(r) : "r"(m), "r"(v)); return r; }
__device__ __forceinline__ uint32_t amax2_h(uint32_t m, uint32_t v) { uint32_t r; asm("max.xorsign.abs.f16x2 %0, %1, %2;" : "=r"(r) : "r"(m), "r"(v)); return r; }
__device__ __forceinline__ uint32_t hadd(uint32_t a, uint32_t b) { uint32_t r; asm("add.rn.f16x2 %0, %1, %2;" : "=r"(r) : "r"(a), "r"(b)); return r; }
__device__ __forceinline__ uint32_t hsub(uint32_t a, uint32_t b) { uint32_t r; asm("sub.rn.f16x2 %0, %1, %2;" : "=r"(r) : "r"(a), "r"(b)); return r; }
__device__ __forceinline__ uint32_t hsub2(uint32_t a, uint32_t b) { uint32_t r; asm("sub.rn.ftz.f16x2 %0, %1, %2;" : "=r"(r) : "r"(a), "r"(b)); return r; }
__device__ __forceinline__ uint32_t hmul(uint32_t a, uint32_t b) { uint32_t r; asm("mul.rn.f16x2 %0, %1, %2;" : "=r"(r) : "r"(a), "r"(b)); return r; }
__device__ __forceinline__ uint32_t hfma(uint32_t a, uint32_t b, uint32_t c) { uint32_t r; asm("fma.rn.f16x2 %0, %1, %2, %3;" : "=r"(r) : "r"(a), "r"(b), "r"(c)); return r; }
__device__ __forceinline__ uint32_t hfms(uint32_t a, uint32_t b, uint32_t c) { uint32_t r; asm("{ .reg .b32 t; neg.f16x2 t, %3; fma.rn.f16x2 %0, %1, %2, t; }" : "=r"(r) : "r"(a), "r"(b), "r"(c)); return r; }
__device__ __forceinline__ uint32_t warp_max16(uint32_t m) { return __reduce_max_sync(0xffffffffu, max(m & 0x7fffu, (m >> 16) & 0x7fffu)); }
__device__ __forceinline__ float ex2f(float x) { float r; asm("ex2.approx.ftz.f32 %0, %1;" : "=f"(r) : "f"(x)); return r; }

__device__ __forceinline__ float exp_acc(float x) {
    const float t = x * 1.4426950216293335f;
    const float r = fmaf(x, 1.4426950216293335f, -t) + x * 1.9259629911266175e-8f;
    return ex2f(t) * fmaf(r, 0.6931471805599453f, 1.f);
}
__device__ __forceinline__ float sigmoid_f(float x) { return __fdividef(1.f, 1.f + ex2f(-x * 1.4426950408889634f)); }
__device__ __forceinline__ void cexp(float l2, float th, float& zr, float& zi) {
    const float mag = ex2f(l2);
    const float k = (th * 0.15915494309189535f + 12582912.f) - 12582912.f;
    float r = fmaf(-k, 6.2831854820251465f, th);
    r = fmaf(-k, -1.7484555314695172e-7f, r);
    zr = mag * __cosf(r);
    zi = mag * __sinf(r);
}
struct hc { uint32_t re, im; };
__device__ __forceinline__ hc cmul(const hc& a, const hc& b) { return {hfms(a.re, b.re, hmul(a.im, b.im)), hfma(a.re, b.im, hmul(a.im, b.re))}; }
__device__ __forceinline__ hc cmulc(const hc& a, const hc& b) { return {hfma(a.re, b.re, hmul(a.im, b.im)), hfms(a.im, b.re, hmul(a.re, b.im))}; }
struct fc2 { float r[2], i[2]; };
__device__ __forceinline__ void csq(fc2& z) {
#pragma unroll
    for (int m = 0; m < 2; m++) {
        const float r = fmaf(z.r[m], z.r[m], -(z.i[m] * z.i[m]));
        asm("{ .reg .f32 t; mul.f32 t, %0, %1; mul.f32 %0, t, 0f40000000; }" : "+f"(z.i[m]) : "f"(z.r[m]));
        z.r[m] = r;
    }
}
__device__ __forceinline__ hc pk(const fc2& z) { return {pack_h(z.r[0], z.r[1]), pack_h(z.i[0], z.i[1])}; }
__device__ __forceinline__ void csq_conj(fc2& z) {
#pragma unroll
    for (int m = 0; m < 2; m++) {
        const float r = fmaf(z.r[m], z.r[m], -(z.i[m] * z.i[m]));
        asm("{ .reg .f32 t, n; neg.f32 n, %1; mul.f32 t, %0, n; mul.f32 %0, t, 0f40000000; }" : "+f"(z.i[m]) : "f"(z.r[m]));
        z.r[m] = r;
    }
}

struct Powers { hc C, z1, z2, z4, c8, c16, c32, c64, z128, z256, z512, z1024; };
__device__ __forceinline__ void kg_powers(Powers& q, uint32_t la, uint32_t ai, uint32_t cr, uint32_t ci, float dt, float cf) {
    fc2 z, y;
    const float dtl = -dt * 1.4426950408889634f;
    const uint32_t eb = pack_bf(ex2f(bf_lo(la) * 1.4426950408889634f), ex2f(bf_hi(la) * 1.4426950408889634f));
    const float l2[2] = {bf_lo(eb) * dtl, bf_hi(eb) * dtl}, th[2] = {bf_lo(ai) * dt, bf_hi(ai) * dt};
#pragma unroll
    for (int m = 0; m < 2; m++) { cexp(l2[m], th[m], z.r[m], z.i[m]); cexp(l2[m] * 128.f, th[m] * 128.f, y.r[m], y.i[m]); }
    q.C.re = pack_h(bf_lo(cr) * cf, bf_hi(cr) * cf);
    q.C.im = pack_h(bf_lo(ci) * cf, bf_hi(ci) * cf);
    q.z1 = pk(z); csq(z); q.z128 = pk(y); csq(y);
    q.z2 = pk(z); csq(z); q.z256 = pk(y); csq(y);
    q.z4 = pk(z); csq_conj(z); q.z512 = pk(y); csq(y);
    q.c8 = pk(z); csq(z); q.z1024 = pk(y);
    q.c16 = pk(z); csq(z);
    q.c32 = pk(z); csq(z);
    q.c64 = pk(z);
}
struct Rows { hc ta[8], tb[8], tc[8], pp[8]; };
#define PUT(a0, a1, row, a, b) sts128((((row) & 1) ? (a1) : (a0)) + (row) * 512, (a).re, (a).im, (b).re, (b).im)
template <bool FIRST>
__device__ __forceinline__ void kg_rows(Rows& w, const Powers& q, uint32_t t0, uint32_t t1, uint32_t u0, uint32_t u1, uint32_t uc, uint32_t zr, uint32_t (&Rl)[2]) {
    w.ta[0] = q.C; w.ta[1] = cmul(q.C, q.z1); w.ta[2] = cmul(q.C, q.z2); w.ta[4] = cmul(q.C, q.z4); w.tb[0] = cmul(q.C, q.z256); w.tb[4] = cmul(q.C, q.z512);
    PUT(t0, t1, 0, w.ta[0], w.tb[0]); PUT(t0, t1, 4, w.ta[4], w.tb[4]);
    w.tb[1] = cmul(w.ta[2], q.z256); w.tb[2] = cmul(w.ta[4], q.z256);
    PUT(t0, t1, 1, w.ta[1], w.tb[1]); PUT(t0, t1, 2, w.ta[2], w.tb[2]);
    w.ta[3] = cmul(w.ta[1], q.z2); w.ta[6] = cmul(w.ta[2], q.z4); w.ta[5] = cmul(w.ta[1], q.z4); w.tb[5] = cmul(w.ta[4], q.z512); w.tb[6] = cmul(w.tb[0], q.z512);
    PUT(t0, t1, 5, w.ta[5], w.tb[5]); PUT(t0, t1, 6, w.ta[6], w.tb[6]);
    w.tb[3] = cmul(w.ta[6], q.z256); w.ta[7] = cmul(w.ta[3], q.z4); w.tb[7] = cmul(w.tb[2], q.z512);
    PUT(t0, t1, 3, w.ta[3], w.tb[3]); PUT(t0, t1, 7, w.ta[7], w.tb[7]);
    sts64(uc, q.c64.re, q.c64.im);
    w.pp[0] = hc{0x3C003C00u ^ zr, zr}; w.pp[1] = q.c8; w.pp[2] = q.c16; w.pp[4] = q.c32;
    w.tc[0] = cmul(q.C, q.z1024); w.pp[3] = cmul(q.c8, q.c16); w.pp[5] = cmul(q.c8, q.c32); w.pp[6] = cmul(q.c16, q.c32);
    w.tc[2] = cmul(w.tc[0], q.z128); w.tc[4] = cmul(w.tc[0], q.z256); w.tc[1] = cmul(w.tc[0], q.z512); w.pp[7] = cmul(w.pp[3], q.c32);
    PUT(u0, u1, 0, w.tc[0], w.pp[0]); PUT(u0, u1, 1, w.tc[1], w.pp[1]); PUT(u0, u1, 2, w.tc[2], w.pp[2]); PUT(u0, u1, 4, w.tc[4], w.pp[4]);
    w.tc[6] = cmul(w.tc[2], q.z256); w.tc[3] = cmul(w.tc[2], q.z512); w.tc[5] = cmul(w.tc[4], q.z512);
    PUT(u0, u1, 3, w.tc[3], w.pp[3]); PUT(u0, u1, 5, w.tc[5], w.pp[5]); PUT(u0, u1, 6, w.tc[6], w.pp[6]);
    w.tc[7] = cmul(w.tc[6], q.z512);
    PUT(u0, u1, 7, w.tc[7], w.pp[7]);
    const uint32_t last = hfms(w.tc[0].re, q.z1024.re, hmul(w.tc[0].im, q.z1024.im));
    if (FIRST) mma_h_k8_z(Rl, 0x3C003C00u - zr, 0x3C003C00u + zr, last); else mma_h_k8(Rl[0], Rl[1], 0x3C003C00u - zr, 0x3C003C00u + zr, last);
}
#undef PUT
template <bool FIRST>
__device__ __forceinline__ void kg_products(uint32_t rt0, uint32_t rt1, uint32_t ru0, uint32_t ru1, uint32_t rc, uint32_t zr,
                                            uint32_t (&Ra)[2][2], uint32_t (&Rb)[2][2], uint32_t (&Rc)[2]) {
    uint4 q1[8], q2[8], cw[8];
#pragma unroll
    for (int ks = 0; ks < 8; ks++) {
        q2[ks] = lds128(((ks & 1) ? ru1 : ru0) + (ks >> 1) * 128); if (!(ks & 1)) cw[ks] = lds128(rc + ks * 32); q1[ks] = lds128(((ks & 1) ? rt1 : rt0) + (ks >> 1) * 128);
    }
#pragma unroll
    for (int ks = 0; ks < 8; ks++) {
        const hc p0 = {q2[ks].z, q2[ks].w}, u = (ks & 1) ? hc{cw[ks & 6].z, cw[ks & 6].w} : hc{cw[ks].x, cw[ks].y};
        const hc p1 = cmul(p0, u), p2 = cmul(p1, u), p3 = cmul(p2, u);

        const uint32_t qa[4] = {p0.re ^ zr, p1.re, p0.im ^ zr, p1.im}, qb[4] = {p2.re, p3.re, p2.im, p3.im};
        if (FIRST && ks == 0) {
            mma_h_z(Rc[0], Rc[1], qa, q2[ks].x, q2[ks].y); mma_h_z(Ra[0][0], Ra[0][1], qa, q1[ks].x, q1[ks].y); mma_h_z(Rb[0][0], Rb[0][1], qa, q1[ks].z, q1[ks].w);
            mma_h_z(Ra[1][0], Ra[1][1], qb, q1[ks].x, q1[ks].y); mma_h_z(Rb[1][0], Rb[1][1], qb, q1[ks].z, q1[ks].w);
        } else {
            mma_h(Rc, qa, q2[ks].x, q2[ks].y); mma_h(Ra[0], qa, q1[ks].x, q1[ks].y); mma_h(Rb[0], qa, q1[ks].z, q1[ks].w);
            mma_h(Ra[1], qb, q1[ks].x, q1[ks].y); mma_h(Rb[1], qb, q1[ks].z, q1[ks].w);
        }
    }
}
__device__ __forceinline__ void kernel_gen(const uint2& la, const uint2& ai, const uint2& cr, const uint2& ci, float dt, float cf, uint32_t TB, uint32_t UB,
                                           int lane, uint32_t zr, uint32_t (&Ra)[2][2], uint32_t (&Rb)[2][2], uint32_t (&Rc)[2], uint32_t (&Rl)[2]) {
    const int g = lane >> 2, t = lane & 3;
    const uint32_t w0 = lane << 4, w1 = w0 ^ 64, r0 = g * 512 + (((g & 1) << 6) | (t << 4)), r1 = r0 ^ 64;
    const uint32_t t0 = TB + w0, t1 = TB + w1, u0 = UB + w0, u1 = UB + w1;
    const uint32_t uc = UB + 4096 + (lane >> 3) * 64 + t * 16 + (lane & 4) * 2;
    Powers p0, p1;
    Rows w;
    kg_powers(p0, la.x, ai.x, cr.x, ci.x, dt, cf);
    kg_rows<true>(w, p0, t0, t1, u0, u1, uc, zr, Rl);
    kg_powers(p1, la.y, ai.y, cr.y, ci.y, dt, cf);
    __syncwarp();
    kg_products<true>(TB + r0, TB + r1, UB + r0, UB + r1, UB + 4096 + t * 16, zr, Ra, Rb, Rc);
    __syncwarp();
    kg_rows<false>(w, p1, t0, t1, u0, u1, uc, zr, Rl);
    __syncwarp();
    kg_products<false>(TB + r0, TB + r1, UB + r0, UB + r1, UB + 4096 + t * 16, zr, Ra, Rb, Rc);
    __syncwarp();
}

template <int V> struct IC { static constexpr int value = V; };

#define LANE_VARS \
    int tid_; asm volatile("mov.u32 %0, %%tid.x;" : "=r"(tid_)); \
    [[maybe_unused]] const int lane = tid_ & 31, warp = (tid_ >> 5) - MAIN_W0, g = lane >> 2, t = lane & 3, mi = lane >> 3, r = lane & 7; \
    [[maybe_unused]] const uint32_t TB = sb + OFF_TAB + warp * T_CH, UB = sb + OFF_U + warp * U_CH; \
    [[maybe_unused]] const bool lead = (tid_ == 32 * MAIN_W0)

__device__ __forceinline__ void dense_step(uint32_t (&M)[8][2], uint32_t (&Ye)[8][2], uint32_t (&Yo)[8][2], uint32_t (&X)[8][2],
                                           uint32_t (&F)[8][2], uint32_t (&Bq)[2][4], uint32_t ua, uint32_t ta, uint32_t zr) {
    uint32_t E[8][2], A[2][4], S[2][4], G[8][2];
#pragma unroll
    for (int jp = 0; jp < 4; jp++) ldsm4(ua + jp * 256, E[2 * jp][0], E[2 * jp][1], E[2 * jp + 1][0], E[2 * jp + 1][1]);
#pragma unroll
    for (int h = 0; h < 2; h++) { A[h][0] = A_REUSE ? Bq[h][3] ^ zr : lds32(ta + 1024 * h); A[h][1] = lds32(ta + 1024 * h + 32); A[h][3] = lds32(ta + 1024 * h + 64); A[h][2] = A[h][1] ^ zr; }
#pragma unroll
    for (int J = 0; J < 8; J++) mma_h(Ye[J], Bq[0], F[J][0], F[J][1]);
#pragma unroll
    for (int J = 1; J < 8; J++) mma_h(Ye[J], Bq[1], F[J - 1][0], F[J - 1][1]);
#pragma unroll
    for (int J = 0; J < 8; J++) { G[J][0] = hsub(X[J][0], E[J][0]); G[J][1] = hsub(X[J][1], E[J][1]); }
#pragma unroll
    for (int jp = 0; jp < 4; jp++) ldsm4(ua + 2 * U_PL + jp * 256 - 16, X[2 * jp][0], X[2 * jp][1], X[2 * jp + 1][0], X[2 * jp + 1][1]);
#pragma unroll
    for (int h = 0; h < 2; h++) { Bq[h][1] = lds32(ta + 1024 * h + 96); Bq[h][3] = lds32(ta + 1024 * h + 128); Bq[h][0] = A[h][3] ^ zr; Bq[h][2] = Bq[h][1] ^ zr; }
#pragma unroll
    for (int J = 0; J < 8; J++) mma_h(Yo[J], A[0], G[J][0], G[J][1]);
#pragma unroll
    for (int J = 1; J < 8; J++) mma_h(Yo[J], A[1], G[J - 1][0], G[J - 1][1]);
#pragma unroll
    for (int h = 0; h < 2; h++)
#pragma unroll
        for (int i = 0; i < 4; i++) S[h][i] = hadd(A[h][i], Bq[h][i]);
#pragma unroll
    for (int J = 0; J < 8; J++) mma_h(M[J], S[0], E[J][0], E[J][1]);
#pragma unroll
    for (int J = 1; J < 8; J++) mma_h(M[J], S[1], E[J - 1][0], E[J - 1][1]);
#pragma unroll
    for (int J = 0; J < 8; J++) { F[J][0] = hsub(X[J][0], E[J][0]); F[J][1] = hsub(X[J][1], E[J][1]); }
}

__device__ __forceinline__ int group_tables(uint32_t TB, int lane) {
    const int g = lane >> 2, t = lane & 3;
    const uint4 b4 = lds128(TB + T_R2 + 16 * lane), c4 = lds128(TB + T_R2 + 512 + 16 * lane);
    uint32_t vb[4] = {b4.x, b4.y, b4.z, b4.w}, vc[2] = {c4.x, c4.y};
    const uint32_t k1024 = __shfl_sync(0xffffffffu, vc[0], 0) & 0xffffu;
    uint32_t kl = hadd(c4.z, __byte_perm(c4.z, 0, 0x1032));
    kl = hadd(kl, __shfl_xor_sync(0xffffffffu, kl, 1)); kl = hadd(kl, __shfl_xor_sync(0xffffffffu, kl, 2));
#pragma unroll
    for (int i = 0; i < 3; i++) sts128(TB + T_R2 + 16 * lane + 512 * i, 0, 0, 0, 0);
    if (lane == 2) vb[0] &= 0xffff0000u;
    if (lane == 0) vc[0] &= 0xffff0000u;
    if (lane == 4) vc[0] = hsub(vc[0], k1024);
    __syncwarp();
    if (t >= 2) {
        const uint32_t g1 = TB + T_R2 + T2_S * (g & 3) + 8 * (8 * t - 10 + (g >> 2));
        const uint32_t g0 = TB + T_R2 + T2_S * ((g - 1) & 3) + 8 * (8 * t - 10 + ((g - 1) >> 2)) + 4;
#pragma unroll
        for (int i = 0; i < 4; i++) {
            sts16(g0 + 16 * i, vb[i]); sts16(g0 + 16 * i + 10, vb[i]);
            sts16(g1 + 16 * i, vb[i] >> 16); sts16(g1 + 16 * i + 10, vb[i] >> 16);
        }
    }
    const uint32_t g3 = TB + T_R3 + T3_S * (((g - 1) >> 1) & 1) + 8 * (7 + 4 * t + ((g - 1) >> 2)) + 4 * ((g - 1) & 1);
#pragma unroll
    for (int i = 0; i < 2; i++) {
        sts16(g3 + 16 * i, vc[i]); sts16(g3 + 16 * i + 10, vc[i]);
        sts16(g3 + 16 * i + 128, vc[i] >> 16); sts16(g3 + 16 * i + 138, vc[i] >> 16);
    }
    const uint32_t g4 = (uint32_t)(((uint64_t)(T_R3 + T3_S + 308) << 48 | (uint64_t)(T_R2 + 180) << 32 | (T_R2 + 176) << 16 | (T_R2 + 3 * T2_S + 172)) >> (8 * (lane & 6))) & 0xffffu;
    sts16(TB + g4 + 10 * (lane & 1), (lane & 7) < 6 ? k1024 : kl);
    return (int)c4.w;
}

#define FENCE() do { if (zr) asm volatile("exit;"); } while (0)
struct Chunks { uint32_t c3, c2, c1, c0, cm1, cm2, cm3, cm4, d2, d1, d0, dm1, em2, em3; };
__device__ __forceinline__ void convolve(uint32_t sb, int h, uint32_t zr, int pr, bf16* out, const CUtensorMap* tm_o DBG_PARAMS) {
    const uint32_t bars = sb + M_BARS;
    uint32_t M[8][2], Ye[8][2], Yo[8][2], F[8][2], Bq[2][4];
    {
        LANE_VARS;
        uint32_t X[8][2];
        uint32_t ua = UB + ((mi & 1) ? 0 : U_PL) + (8 + 8 * (mi >> 1) + r) * 16, ta = TB + 4 * (1 + g + 2 * t);
        uint32_t A[3][4], S[2][4];
        __syncwarp();
#pragma unroll
        for (int h2 = 0; h2 < 3; h2++) { A[h2][0] = lds32(ta + 1024 * h2); A[h2][1] = lds32(ta + 1024 * h2 + 32); A[h2][3] = lds32(ta + 1024 * h2 + 64); A[h2][2] = A[h2][1] ^ zr; }
#pragma unroll
        for (int h2 = 0; h2 < 2; h2++) {
            Bq[h2][1] = lds32(ta + 1024 * h2 + 96); Bq[h2][3] = lds32(ta + 1024 * h2 + 128); Bq[h2][0] = A[h2][3] ^ zr; Bq[h2][2] = Bq[h2][1] ^ zr;
#pragma unroll
            for (int i = 0; i < 4; i++) S[h2][i] = hadd(A[h2][i], Bq[h2][i]);
        }
        const uint32_t an = A[0][0] ^ zr, un = UB + (9 + lane) * 16;
        if (lead) TSTAMP(10);
        mbar_spin(bars + 8 * B_U);
        if (lead) { TSTAMP(3); CSTAMP(27); }
        uint32_t E[8][2], N[8], G[8][2];
#pragma unroll
        for (int jp = 0; jp < 4; jp++) ldsm4(ua + jp * 256, E[2 * jp][0], E[2 * jp][1], E[2 * jp + 1][0], E[2 * jp + 1][1]);
#pragma unroll
        for (int jp = 0; jp < 4; jp++) ldsm4(ua + 2 * U_PL + jp * 256, X[2 * jp][0], X[2 * jp][1], X[2 * jp + 1][0], X[2 * jp + 1][1]);
        ldsm4(un, N[0], N[1], N[2], N[3]); ldsm4(un + 512, N[4], N[5], N[6], N[7]);
#pragma unroll
        for (int J = 0; J < 8; J++) mma_h_z(M[J][0], M[J][1], S[0], E[J][0], E[J][1]);
#pragma unroll
        for (int J = 1; J < 8; J++) mma_h(M[J], S[1], E[J - 1][0], E[J - 1][1]);
#pragma unroll
        for (int J = 2; J < 8; J++) mma_h(M[J], A[2], E[J - 2][0], E[J - 2][1]);
        if (FENCES & 32) FENCE();
#pragma unroll
        for (int J = 0; J < 8; J++) mma_h_k8_z(Ye[J], zr, an, X[J][1]);
#pragma unroll
        for (int J = 0; J < 8; J++) mma_h_k8_z(Yo[J], zr, an, N[J]);
#pragma unroll
        for (int J = 0; J < 8; J++) { G[J][0] = hsub(X[J][0], E[J][0]); G[J][1] = hsub(X[J][1], E[J][1]); }
#pragma unroll
        for (int jp = 0; jp < 4; jp++) ldsm4(ua + 2 * U_PL + jp * 256 - 16, X[2 * jp][0], X[2 * jp][1], X[2 * jp + 1][0], X[2 * jp + 1][1]);
#pragma unroll
        for (int J = 0; J < 8; J++) mma_h(Yo[J], A[0], G[J][0], G[J][1]);
#pragma unroll
        for (int J = 1; J < 8; J++) mma_h(Yo[J], A[1], G[J - 1][0], G[J - 1][1]);
#pragma unroll
        for (int J = 2; J < 8; J++) mma_h(Yo[J], A[2], G[J - 2][0], G[J - 2][1]);
#pragma unroll
        for (int J = 0; J < 8; J++) { F[J][0] = hsub(X[J][0], E[J][0]); F[J][1] = hsub(X[J][1], E[J][1]); }
#pragma unroll 1
        for (int k = 1; k < 8; k++) {
            ua -= 16; ta += 128;
            dense_step(M, Ye, Yo, X, F, Bq, ua, ta, zr);
        }
    }
    mbar_wait_n<2, 8>(bars + 8 * B_TD);
    LANE_VARS;
    if (lead) { TSTAMP(4); CSTAMP(28); }
    __syncwarp();
    const uint32_t idh = (g == 2 * t) ? 0x3C00u : (g == 2 * t + 1) ? 0x3C000000u : 0u;
    const uint32_t sbr = mapa(sb, h ^ 1);
    const uint32_t yl = TB + lane * 16, yr = sbr + (h ? ALT0 : ALT1) + A_YIN + warp * Y_CH + lane * 16;
    const uint32_t ys = lds32(sb + M_SC + (8 * h + warp) * 4);
    uint32_t ea[4];
    auto finish = [&](int J) {
        float m[4], e[4], o[4];
        widen_h(m, M[J], idh); widen_add_h(e, Ye[J], idh, m); widen_add_h(o, Yo[J], idh, m);
        const uint32_t y[4] = {hmul2_bf(pack_bf(e[0], e[2]), ys), hmul2_bf(pack_bf(o[0], o[2]), ys), hmul2_bf(pack_bf(e[1], e[3]), ys), hmul2_bf(pack_bf(o[1], o[3]), ys)};
        if (!(J & 1)) {
#pragma unroll
            for (int i = 0; i < 4; i++) ea[i] = y[i];
        } else {
            st_async16(yr + (J >> 1) * 512, h ? ea[0] : y[0], h ? ea[1] : y[1], h ? ea[2] : y[2], h ? ea[3] : y[3], sbr + M_BARS + 8 * (B_Y + (J >> 1)));
            sts128(yl + (J >> 1) * 512, h ? y[0] : ea[0], h ? y[1] : ea[1], h ? y[2] : ea[2], h ? y[3] : ea[3]);
            __syncwarp();
            if (lane == 0) mbar_arrive(bars + 8 * (B_Y + (J >> 1)));
        }
    };
    const uint32_t a1 = UB + (3 - mi) * U_PL + (8 + r) * 16;
    const uint32_t a2 = UB + ((2 - mi) & 3) * U_PL + (8 + r - (mi == 3)) * 16;
    const uint32_t a3 = UB + (2 - (mi & 1)) * U_PL + (7 + r) * 16;
    const uint32_t bt = sb + OFF_BAND + 4 * (32 + g + 2 * t);
    auto load3 = [&](Chunks& u, int j) { ldsm4(a2 + j * 128, u.d2, u.d1, u.d0, u.dm1); ldsm4(a1 + j * 128, u.c3, u.c2, u.c1, u.c0); ldsm2(a3 + j * 128, u.em2, u.em3); };
    auto load2 = [&](Chunks& u, int j) { load3(u, j); ldsm4(a1 + j * 128 - 16, u.cm1, u.cm2, u.cm3, u.cm4); };
    Chunks u;
    uint32_t B35[4];
    uint2 Q[4][3], QS[2][3];
    {
        const uint32_t f7 = lds32(bt + 768 - 36), g7 = lds32(bt + 768 - 4), f9 = lds32(bt + 1024 - 32), g9 = lds32(bt + 1024), h9 = lds32(bt + 1024 + 32);
        const uint32_t f1 = hmul(lds32(bt - 28), lds16(TB + T_R2 + 176) * 0x10001u);
        load3(u, 0);
        const uint32_t tq = TB + T_R3 + 8 * (7 + g - 2 * t);
        uint2 Q0[4], Q1[4], Q2[4];
#pragma unroll
        for (int i = 0; i < 4; i++) { Q0[i] = lds64(tq + 64 * i); Q1[i] = lds64(tq + T3_S + 64 * i); Q2[i] = lds64(tq + T3_S - 8 + 64 * i); }
#pragma unroll
        for (int J = 0; J < 8; J++) mma_h(Ye[J], Bq[0], F[J][0], F[J][1]);
#pragma unroll
        for (int J = 1; J < 8; J++) mma_h(Ye[J], Bq[1], F[J - 1][0], F[J - 1][1]);
        const uint32_t B7[4] = {zr, f7, f7 ^ zr, g7}, B9a[4] = {zr + zr, f9, f9 ^ zr, g9}, B9b[4] = {g9 ^ zr, h9, h9 ^ zr, zr * 3}, B1[4] = {zr * 5, f1, f1 ^ zr, zr * 7};
        const uint32_t g7b = g7 ^ zr, z7 = zr * 9;
        if (FENCES & 1) FENCE();
        uint32_t WE[2][4], WO[2][4];
#pragma unroll
        for (int j = 0; j < 5; j++) {
            uint32_t (&we)[4] = WE[j & 1], (&wo)[4] = WO[j & 1], (&pe)[4] = WE[~j & 1], (&po)[4] = WO[~j & 1];
            if (j == 3) {
                const uint32_t t2 = TB + T_R2 + 8 * (6 + g - 2 * t);
                B35[0] = lds32(bt + 256 - 28); B35[1] = lds32(bt + 512 - 40); B35[2] = lds32(bt + 256 + 4); B35[3] = lds32(bt + 512 - 8);
#pragma unroll
                for (int i = 0; i < 3; i++)
#pragma unroll
                    for (int s = 0; s < 4; s++) Q[s][i] = lds64(t2 + T2_S * s + 64 * i);
            }
            if (j < 4) {
                mma_h_z(we[2], we[3], B9a, u.d0, u.dm1); mma_h_z(wo[2], wo[3], B9a, u.d2, u.d1);
                mma_h_z(we[0], we[1], B7, u.c1, u.c0); mma_h_z(wo[0], wo[1], B7, u.c3, u.c2);
            }
            if (j == 0) { finish(0); finish(1); }
#pragma unroll
            for (int i = 0; i < 5 - j && j > 0; i++) { mma_h(Ye[j + 3 + i], pe, Q0[i].x, Q0[i].y); mma_h(Yo[j + 3 + i], pe, Q1[i].x, Q1[i].y); }
            if (j < 4) {
                mma_h2(we[2], we[3], B9b, u.em2, u.em3); mma_h2(wo[2], wo[3], B9b, u.d0, u.dm1);
                mma_h_k8(we[0], we[1], g7b, z7, u.dm1); mma_h_k8(wo[0], wo[1], g7b, z7, u.c1);
                mma_h(Ye[j + 4], B1, u.d0, u.dm1); mma_h(Yo[j + 4], B1, u.d2, u.d1);
                if (j < 3) load3(u, j + 1); else load2(u, 0);
            }
#pragma unroll
            for (int i = 0; i < 5 - j && j > 0; i++) { mma_h(Ye[j + 3 + i], po, Q2[i].x, Q2[i].y); mma_h(Yo[j + 3 + i], po, Q0[i].x, Q0[i].y); }
            if (j == 3) {
#pragma unroll
                for (int i = 0; i < 3; i++)
#pragma unroll
                    for (int s = 0; s < 2; s++) { QS[s][i].x = hadd(Q[s][i].x, Q[s + 2][i].x); QS[s][i].y = hadd(Q[s][i].y, Q[s + 2][i].y); }
            }
            if (j < 3 ? ((FENCES & 2) || (j == 2 && (FENCES & 4))) : (j == 4 && (FENCES & 8))) FENCE();
        }
    }
    uint32_t xo, go, ya, sel, any, wu, oo;
    auto mix_setup = [&]() {
        LANE_VARS;
        const int pos = 4 * (warp & 1) + (t >> 1);
        xo = sb + OFF_S + h * 32768 + (warp & 1) * 4096 + ((warp & 6) + (g >> 2)) * 512 + (t >> 1) * 128 + (g & 3) * 32 + (((t ^ (t >> 1)) & 1) << 4);
        go = sb + OFF_GP + (8 * pos + g) * 64 + ((warp >> 1) ^ (g >> 1)) * 16;
        const int ch = 2 * mi + (r & 1);
        ya = sb + ((((r >> 1) & 1) == h) ? OFF_TAB + ch * T_CH : (h ? ALT1 : ALT0) + A_YIN + ch * Y_CH) + (16 * (warp & 1) + (r & 4) + (warp >> 1)) * 16;
        sel = lds16(sb + M_BMAP + (8 * warp + g) * 2);
        any = __reduce_or_sync(0xffffffffu, sel);
        sel >>= t >> 1;
        oo = (64 * (warp >> 1) + 8 * g + pos) * D_ + 8 * (t & 1);
        wu = __shfl_sync(0xffffffffu, warp, 0);
    };
    struct MixIn { uint32_t gp[2]; uint4 e[2]; };
    auto mix_load = [&](MixIn& q, int J) {
#pragma unroll
        for (int k = 0; k < 2; k++) {
            q.gp[k] = lds32(go + k * 1024 + J * 4);
            const uint4 x = lds128(xo + J * 8192 + k * 256);
            q.e[k] = make_uint4(hi_mul_bf(q.gp[k], x.x), hi_mul_bf(q.gp[k], x.y), hi_mul_bf(q.gp[k], x.z), hi_mul_bf(q.gp[k], x.w));
        }
    };
    auto mix_calc = [&](MixIn& q, int J) {
#pragma unroll
        for (int k = 0; k < 2; k++) {
            uint32_t y[4];
            ldsm4t(ya + J * 512 + k * 128, y[0], y[1], y[2], y[3]);
            q.e[k] = make_uint4(lo_fma_bf(q.gp[k], y[0], q.e[k].x), lo_fma_bf(q.gp[k], y[1], q.e[k].y), lo_fma_bf(q.gp[k], y[2], q.e[k].z), lo_fma_bf(q.gp[k], y[3], q.e[k].w));
        }
    };
    auto mix_send = [&](const MixIn& q, int J) {
        if ((any >> (4 * J)) & 15u) {
#pragma unroll
            for (int k = 0; k < 2; k++) if (!((sel >> (4 * J + 2 * k)) & 1u)) *(uint4*)(out + (size_t)(512 * J + 256 * h + 2 * k) * D_ + 16 * pr + oo) = q.e[k];
        } else {
#pragma unroll
            for (int k = 0; k < 2; k++) sts128(xo + J * 8192 + k * 256, q.e[k].x, q.e[k].y, q.e[k].z, q.e[k].w);
            asm volatile("fence.proxy.async.shared::cta;" ::: "memory");
            __syncwarp();
            asm volatile("{ .reg .pred p; elect.sync _|p, 0xffffffff;\n\t@p cp.async.bulk.tensor.4d.global.shared::cta.bulk_group [%0, {%2, %3, %4, %5}], [%1]; }"
                         :: "l"(tm_o), "r"(sb + OFF_S + h * 32768 + J * 8192 + (wu & 1) * 4096 + (wu & 6) * 512),
                            "r"(16 * pr), "r"(0), "r"(4 * (wu & 1)), "r"(16 * J + 8 * h + (wu & 6)) : "memory");
        }
    };
    MixIn q, q2, q3;
    const uint32_t zq = zr + zr;
#pragma unroll
    for (int j = 0; j < 6; j++) {
        if (j == MIX0_AT + 1) mix_send(q, 0);
        if (j == MIX1_AT + 1) mix_send(q, 1);
        if (j == MIX0_AT) mbar_wait_n<2, 8 * (B_Y - B_G)>(bars + 8 * B_G);
        else if (j == MIX1_AT) mbar_spin(bars + 8 * (B_Y + 1));
        else if (j > 0 && (FENCES & 16) && j != MIX0_AT + 1 && j != MIX1_AT + 1) FENCE();
        uint32_t H[7][2];
        mma_h_z(H[3][0], H[3][1], B35, u.d0, u.dm1); mma_h_z(H[4][0], H[4][1], B35, u.c1, u.c0);
        mma_h_z(H[5][0], H[5][1], B35, u.d2, u.d1); mma_h_z(H[6][0], H[6][1], B35, u.c3, u.c2);
        mma_h_z(H[2][0], H[2][1], B35, u.cm1, u.cm2); mma_h_z(H[1][0], H[1][1], B35, u.em2, u.em3); mma_h_z(H[0][0], H[0][1], B35, u.cm3, u.cm4);
        if (j < 5) load2(u, j + 1);
        if (j > 0) finish(j + 1);
        if (j == MIX0_AT) { mix_setup(); mix_load(q, 0); mix_calc(q, 0); }
        if (j == MIX1_AT) { mix_load(q, 1); mix_calc(q, 1); }
        if (j == 5) { mix_load(q2, 2); mix_load(q3, 3); }
        const int n = j < 4 ? 3 : 6 - j;
#pragma unroll
        for (int s = 0; s < 2; s++) {
            const int o = 3 - s;
            const uint32_t qe[4] = {H[o][0] ^ zr, H[o + 1][0] ^ zq, H[o][1] ^ zr, H[o + 1][1] ^ zq};
            const uint32_t qg[4] = {hsub(H[o + 2][0], H[o][0]), hsub2(H[o + 3][0], H[o + 1][0]), hsub(H[o + 2][1], H[o][1]), hsub2(H[o + 3][1], H[o + 1][1])};
            const uint32_t qf[4] = {hsub(H[o - 2][0], H[o][0]), hsub2(H[o - 1][0], H[o + 1][0]), hsub(H[o - 2][1], H[o][1]), hsub2(H[o - 1][1], H[o + 1][1])};
#pragma unroll
            for (int i = 0; i < n; i++) mma_h(M[j + 2 + i], qe, QS[s][i].x, QS[s][i].y);
#pragma unroll
            for (int i = 0; i < n; i++) mma_h(Yo[j + 2 + i], qg, Q[s][i].x, Q[s][i].y);
#pragma unroll
            for (int i = 0; i < n; i++) mma_h(Ye[j + 2 + i], qf, Q[s + 2][i].x, Q[s + 2][i].y);
        }
    }
    finish(7);
    if (lead) { TSTAMP(5); CSTAMP(29); }
    if (MIX1_AT == 5) mix_send(q, 1);
    mbar_spin(bars + 8 * (B_Y + 2));
    mix_calc(q2, 2);
    mix_send(q2, 2);
    mbar_spin(bars + 8 * (B_Y + 3));
    if (lead) TSTAMP(6);
    mix_calc(q3, 3);
    mix_send(q3, 3);
    asm volatile("cp.async.bulk.commit_group;" ::: "memory");
    asm volatile("cp.async.bulk.wait_group.read 0;" ::: "memory");
}

__global__ void __cluster_dims__(2, 1, 1) __launch_bounds__(NTHREADS, 1)
fused_kernel(const Params p, const __grid_constant__ CUtensorMap tm_gu, const __grid_constant__ CUtensorMap tm_down, const __grid_constant__ CUtensorMap tm_x,
             const __grid_constant__ CUtensorMap tm_r, const __grid_constant__ CUtensorMap tm_o) {
    extern __shared__ __align__(1024) unsigned char smem[];
    const uint32_t sb = __shfl_sync(0xffffffffu, smem_u32(smem), 0);
    int tid;
    asm volatile("mov.u32 %0, %%tid.x;" : "=r"(tid));
    const int pw = tid >> 5, lane = tid & 31;
    const int kc = ((blockIdx.x >> 1) + 60) & 63, k7 = ((kc - 32) * 37) >> 8;
    const int h = blockIdx.x & 1;
    const int pr = kc < 32 ? ((kc & 7) << 2) | (kc >> 3) : kc < 60 ? 32 + 4 * (kc - 32 - 7 * k7) + k7 : kc;
    const int c = 2 * pr + h;
    const uint32_t bars = sb + M_BARS;

    if (blockIdx.x >= 128) {
        if (blockIdx.x != 128) return;
        const unsigned tag = (ld_epoch(p.ex) + 1) & 0xffffu;
        const uint32_t idx0 = 2047 - (512 * (tid & 3) + (tid >> 3) + 256 * ((tid >> 2) & 1));
        const uint32_t list = sb + 128;
#pragma unroll 1
        for (int pass = 0; pass < 2; pass++) {
            if (tid == 0) sts32(sb + 64, 0);
            sts128(list + 16 * tid, 0, 0, 0, 0);
            uint4 a = make_uint4(lane == 0 ? 0x10000u : 0u, 0, 0, 0);
            bool ok = pass == 0;
#pragma unroll 1
            for (int it = 0; it < (1 << 22) && !ok; it++) {
                a = ld_gpu128(&p.ex->r[tid]);
                ok = (((a.x ^ tag) | (a.y ^ tag) | (a.z ^ tag) | (a.w ^ tag)) & 0xffffu) == 0;
            }
            if (!ok) __trap();
            const uint32_t key[4] = {(a.x & 0xffff0000u) | idx0, (a.y & 0xffff0000u) | (idx0 - 64), (a.z & 0xffff0000u) | (idx0 - 128), (a.w & 0xffff0000u) | (idx0 - 192)};
            const uint32_t wm = __reduce_max_sync(0xffffffffu, max(max(key[0], key[1]), max(key[2], key[3])));
            if (lane == 0) sts32(sb + pw * 4, wm);
            __syncthreads();
            const uint2 q = lds64(sb + 8 * (lane & 7));
            const uint32_t thr = __reduce_min_sync(0xffffffffu, max(q.x, q.y));
            if (tid == 0) TSTAMP(0);
            const uint32_t n = (key[0] >= thr) + (key[1] >= thr) + (key[2] >= thr) + (key[3] >= thr);
            if (n) {
                uint32_t pos;
                asm volatile("atom.shared.add.u32 %0, [%1], %2;" : "=r"(pos) : "r"(sb + 64), "r"(n) : "memory");
#pragma unroll
                for (int i = 0; i < 4; i++) if (key[i] >= thr) { sts32(list + 4 * pos, key[i]); pos++; }
            }
            __syncthreads();
            const int ncand = (int)lds32(sb + 64);
            const uint2 l0 = lds64(list + 8 * lane);
#pragma unroll 1
            for (int j = pw; j < ncand; j += 16) {
                const uint32_t mine = lds32(list + 4 * j);
                int rank = __popc(__ballot_sync(0xffffffffu, l0.x > mine)) + __popc(__ballot_sync(0xffffffffu, l0.y > mine));
#pragma unroll 1
                for (int i = 64; i < ncand; i += 32) rank += __popc(__ballot_sync(0xffffffffu, lds32(list + 4 * (i + lane)) > mine));
                if (rank < 8 && lane == 0) asm volatile("st.relaxed.gpu.global.v2.u32 [%0], {%1, %2};" :: "l"(&p.ex->top[rank]), "r"(mine), "r"(pass ? tag : tag ^ 0x8000u) : "memory");
            }
            if (tid == 0) TSTAMP(1);
            __syncthreads();
        }
        if (tid == 0) TSDUMP(3u);
        return;
    }

    if (pw != 12) asm volatile("barrier.cluster.arrive.relaxed.aligned;" ::: "memory");

    if (pw >= MAIN_W0 && pw < MAIN_W0 + 8) {
        const int warp = pw - MAIN_W0;
        const uint32_t po = (8 * c + warp) * 128 + 4 * lane;
        uint2 v_la = ldg64(p.logA + po), v_ai = ldg64(p.Aim + po), v_cr = ldg64(p.Cre + po), v_ci = ldg64(p.Cim + po);
        const uint32_t ldt16 = ldg16(p.logdt + 8 * c + warp), dsk16 = ldg16(p.Dskip + 8 * c + warp);
        [[maybe_unused]] const bool lead = (tid == 32 * MAIN_W0);
        asm volatile("setmaxnreg.inc.sync.aligned.u32 " MAIN_REGS ";");
        [[maybe_unused]] const int d = 8 * c + warp;
        const int g = lane >> 2, t = lane & 3, mi = lane >> 3, r = lane & 7;
        const uint32_t TB = sb + OFF_TAB + warp * T_CH;
        const uint32_t UB = sb + OFF_U + warp * U_CH;
        const uint32_t zr = p.zero;

        uint32_t Ra[2][2], Rb[2][2], Rc[2], Rl[2];
        int esum;
        {
            const float dt = bf_round(exp_acc(__uint_as_float(ldt16 << 16)));
            const uint32_t ec = max(warp_max16(amax2_bf(amax2_bf(v_cr.x, v_cr.y), amax2_bf(v_ci.x, v_ci.y))) >> 7, 6u);
            const float cf = __uint_as_float((__float_as_uint(dt) & 0x7fffffu) | ((260u - ec) << 23));
            esum = (int)ec + (int)(__float_as_uint(dt) >> 23) - 274;
            kernel_gen(v_la, v_ai, v_cr, v_ci, dt, cf, TB, UB, lane, zr, Ra, Rb, Rc, Rl);
        }
        asm volatile("barrier.cluster.wait.acquire.aligned;" ::: "memory");
        if (lane == 0) mbar_arrive(bars + 8 * B_KD + (Rc[0] & zr));
        if (lead) TSTAMP(2);

        {
            uint32_t mk = amax2_h(amax2_h(amax2_h(Ra[0][0], Ra[0][1]), amax2_h(Ra[1][0], Ra[1][1])), amax2_h(amax2_h(Rb[0][0], Rb[0][1]), amax2_h(Rb[1][0], Rb[1][1])));
            mk = amax2_h(amax2_h(mk, hmul(Rl[0], 0x34003400u)), amax2_h(Rc[0], Rc[1]));
            const int eb = (dsk16 >> 7) & 0xff, ek = max((int)(warp_max16(mk) >> 10), eb ? eb - 127 - esum : 0), en = eb - esum - 3 - ek;
            const float ds = (lane == 0 && eb && en > 0) ? __uint_as_float(((dsk16 & 0x807fu) << 16) | (en << 23)) : 0.f;
            const float fs = __uint_as_float(max(139 - ek, 1) << 23);
            const uint32_t ks = pack_h(fs, fs);
            uint32_t va[4], vb[4];
#pragma unroll
            for (int i = 0; i < 4; i++) { va[i] = hmul(Ra[i >> 1][i & 1], ks); vb[i] = hmul(Rb[i >> 1][i & 1], ks); }
            va[0] = hadd(va[0], pack_h(ds, 0.f));
            const uint32_t k512 = __shfl_sync(0xffffffffu, vb[0], 2) & 0xffffu, k255 = __shfl_sync(0xffffffffu, va[3], 31);
#pragma unroll
            for (int i = 0; i < 4; i++) {
                const uint32_t pv = __shfl_sync(0xffffffffu, lane == 31 ? (i ? va[i - 1] : 0u) : va[i], lane - 1);
                sts64(TB + 48 + 256 * i + 8 * lane, __byte_perm(pv, va[i], 0x5432), va[i]);
            }
#pragma unroll
            for (int i = 0; i < 4; i++) {
                const uint32_t nx = __shfl_sync(0xffffffffu, lane == 0 ? (i < 3 ? vb[i + (i < 3)] : k512) : vb[i], lane + 1 + 2 * (lane & 1));
                const uint32_t aa = __byte_perm(vb[i], 0, 0x1010);
                sts128_if(t < 2, TB + 1072 + 256 * i + 32 * g + 16 * t, (i == 0 && lane == 0) ? __byte_perm(k255, aa, 0x5432) : aa ^ zr, aa, vb[i] ^ zr, __byte_perm(vb[i], nx, 0x5432));
            }
            const uint32_t k0 = lane == 3 ? k512 : 0u, kk = k0 * 0x10001u;
            sts128_if(lane < 8, TB + 16 * lane + (lane < 3 ? 0 : 2048), kk, kk ^ zr, kk + zr, k0);
            esum += (int)ek;
            sts128(TB + T_R2 + 16 * lane, vb[0], vb[1], vb[2], vb[3]);
            sts128(TB + T_R2 + 512 + 16 * lane, hmul(Rc[0], ks), hmul(Rc[1], ks), hmul(Rl[0], ks), (uint32_t)esum);
            __syncwarp();
            if (lane == 0) mbar_arrive(bars + 8 * B_TS);
        }
        if (lead) TSTAMP(11);

        convolve(sb, h, zr, pr, p.out, &tm_o DBG_ARGS);
        { LANE_VARS; if (lead) { TSTAMP(7); TSDUMP(0x3c000cffu); } }
    } else if (pw < 4) {
        const int v = pw, at = tid;
        const int g = lane >> 2, t = lane & 3, mi = lane >> 3, r = lane & 7;
        const uint32_t dalt = (h ? ALT1 : ALT0) + A_SLOT - ALT_SLOT * 8192;
        cp16(sb + OFF_GP + tid * 16, p.wr + tid * 8);
        cp16(sb + OFF_GP + 2048 + tid * 16, p.gatew + tid * 8);
        const unsigned epoch = ld_epoch(p.ex);
        if (tid < 24) sts128(sb + OFF_S - 384 + tid * 16, 0, 0, 0, 0);
        const unsigned tag = (epoch + 1) & 0xffffu;
        const int ftok = 2 * ((at >> 2) & 3) + (at & 1), fch = (at >> 4) + 8 * ((at >> 1) & 1);
        uint32_t eu;
        {
            cp_wait_all();
            bar_sync(7, 160);
            const uint32_t wo = sb + OFF_GP + 512 * v + 64 * ((g >> 1) & 1) + 16 * t + 4 * (g & 1);
            uint32_t w0[4], w1[4];
#pragma unroll
            for (int cb = 0; cb < 4; cb++) { w0[cb] = lds32(wo + 128 * cb); w1[cb] = lds32(wo + 128 * cb + 8); }
            const uint32_t go = sb + OFF_GP + 2048 + 512 * v + 64 * (g & 1) + 16 * t;
            const uint32_t ro = sb + M_RG + (g >> 1) * 32 + (2 * v + (g & 1)) * 4;
            const uint32_t xo = sb + OFF_XROW + (g >> 1) * 2048 + 512 * v + 64 * (g & 1) + 16 * t;
            const uint32_t one0 = 0x3F803F80u ^ p.zero, one1 = 0x3F803F80u + p.zero;
            auto row_sum = [&](uint32_t a) {
                const uint4 x = lds128(a), y = lds128(a + 16);
                return ((__uint_as_float(x.x) + __uint_as_float(x.y)) + (__uint_as_float(x.z) + __uint_as_float(x.w)))
                     + ((__uint_as_float(y.x) + __uint_as_float(y.y)) + (__uint_as_float(y.z) + __uint_as_float(y.w)));
            };
            const int dl = 8 * (r >> 1) + 4 - 2 * mi - (r & 1);
            const uint32_t so = sb + OFF_S + (v >> 1) * 32768 + (dl & 4) * 1024 + (4 * (v & 1) + (dl >> 5)) * 512 + (dl & 3) * 128 + ((dl >> 3) & 3) * 32 + (((dl & 1) ^ h) << 4);
            const uint32_t so1 = so + (dl >= 0 ? 0 : v == 2 ? -28672 : v == 0 ? -4096 : 0), so2 = so1 + ((dl < 0 && v == 0) ? 32768 : 0);
            auto src = [&](int k) { return (k == 0 ? so1 : (k & 3) == 0 ? so2 : so) + (k >> 2) * 8192 + (k & 3) * 512; };
            uint32_t xr[16][4], mx = 0, idb = 0;
            auto slice = [&](int k) { ldsm4t(src(k), xr[k][0], xr[k][1], xr[k][2], xr[k][3]); };
            auto to_half = [&](uint32_t (&q)[4]) {
                float f0[4], f1[4];
                widen_bf(f0, q[0], q[1], idb); widen_bf(f1, q[2], q[3], idb);
                q[0] = pack_h(f0[0], f0[1]); q[1] = pack_h(f0[2], f0[3]); q[2] = pack_h(f1[0], f1[1]); q[3] = pack_h(f1[2], f1[3]);
            };
            auto track = [&](int k) { mx = amax2_bf(amax2_bf(mx, amax2_bf(xr[k][0], xr[k][1])), amax2_bf(xr[k][2], xr[k][3])); };
            auto cta_exp = [&](uint32_t slot) {
                const uint4 m4 = lds128(slot);
                return max(max(m4.x, m4.y), max(m4.z, m4.w)) >> 7;
            };
            auto set_scale = [&]() { const uint32_t sc = (257u - eu) << 7; idb = (g == 2 * t) ? sc : (g == 2 * t + 1) ? sc << 16 : 0u; };
            uint4 x[4], gw[4];
#pragma unroll
            for (int cb = 0; cb < 4; cb++) gw[cb] = lds128(go + 128 * cb);
            auto gate = [&](int i) {
                float e0[4] = {0.f, 0.f, 0.f, 0.f}, e1[4] = {0.f, 0.f, 0.f, 0.f};
#pragma unroll
                for (int cb = 0; cb < 4; cb++)
                    mma_bf((cb & 1) ? e1 : e0, hmul2_bf(x[cb].x, gw[cb].x), hmul2_bf(x[cb].y, gw[cb].y), hmul2_bf(x[cb].z, gw[cb].z), hmul2_bf(x[cb].w, gw[cb].w), one0, one1);
                if (t == 0) stsf(ro + 512 + 128 * i, (e0[0] + e0[3]) + (e1[0] + e1[3]));
            };
#pragma unroll
            for (int i = 0; i < 4; i++) {
                if (i == 0) mbar_spin(bars + 8 * B_X); else mbar_wait_n<2, 8 * (B_X - B_S + 1)>(bars + 8 * (B_S + i - 1));
#pragma unroll
                for (int cb = 0; cb < 4; cb++) x[cb] = lds128(xo + 8192 * i + 128 * cb);
#pragma unroll
                for (int k = max(4 * i - 4, 0); k < 4 * i; k++) slice(k);
                float d0[4] = {0.f, 0.f, 0.f, 0.f}, d1[4] = {0.f, 0.f, 0.f, 0.f};
#pragma unroll
                for (int cb = 0; cb < 4; cb++) mma_bf((cb & 1) ? d1 : d0, x[cb].x, x[cb].y, x[cb].z, x[cb].w, w0[cb], w1[cb]);
                if (t == (g & 1)) stsf(ro + 128 * i, (d0[0] + d0[3]) + (d1[0] + d1[3]));
                if (i == 3) break;
                gate(i);
#pragma unroll
                for (int k = max(4 * i - 4, 0); k < 4 * i; k++) track(k);
                if (i == 2) {
                    const uint32_t wm = warp_max16(mx);
                    if (lane == 0) sts32(sb + M_MX + v * 4, wm);
                    bar_sync(1, 128);
                    eu = min(cta_exp(sb + M_MX) + 3u, 255u);
                    set_scale();
#pragma unroll
                    for (int k = 0; k < 8; k++) to_half(xr[k]);
                }
            }
            bar_sync(4, 256);
            if (at < 16) {
                const uint32_t rb = pack_bf(0.f, row_sum(sb + M_RG + at * 32));
                st_gpu32((uint32_t*)p.ex->r + 16 * c + at, ((rb ^ (((int)rb >> 31) | 0x80000000u)) & 0xffff0000u) | tag);
            }
            if (at == 32) mbar_arrive(bars + 8 * B_XF);
            if (at == 0) TSTAMP(8);
#pragma unroll
            for (int k = 8; k < 12; k++) { track(k); to_half(xr[k]); }
            mbar_spin(bars + 8 * (B_S + 3));
            if (at == 0) TSTAMP(9);
#pragma unroll
            for (int k = 12; k < 16; k++) slice(k);
            uint32_t utail = 0;
            if (at < 64 && r >= 5) utail = lds16(sb + OFF_S + 65024 + 96 + (8 - r) * 128 + (((r & 1) ^ h) << 4) + 2 * (at >> 3));
#pragma unroll
            for (int k = 12; k < 16; k++) track(k);
            const uint32_t wm = warp_max16(amax2_bf(mx, utail));
            if (lane == 0) sts32(sb + M_MX + 16 + v * 4, wm);
#pragma unroll
            for (int k = 12; k < 16; k++) to_half(xr[k]);
            mbar_spin(bars + 8 * B_KD);
            const uint32_t uo = sb + OFF_U + g * U_CH + t * U_PL;
#pragma unroll
            for (int k = 0; k < 16; k++) sts128(uo + (8 + 4 * v + 16 * (k >> 2) + (k & 3)) * 16, xr[k][0], xr[k][1], xr[k][2], xr[k][3]);
            sts128(uo + v * 32, 0, 0, 0, 0); sts128(uo + v * 32 + 16, 0, 0, 0, 0);
            bar_sync(1, 128);
            const uint32_t ea = cta_exp(sb + M_MX + 16);
            if (ea > eu) {
                eu = ea;
                set_scale();
#pragma unroll 1
                for (int k = 0; k < 16; k++) {
                    uint32_t q[4];
                    ldsm4t(src(k), q[0], q[1], q[2], q[3]);
                    to_half(q);
                    sts128(uo + (8 + 4 * v + 16 * (k >> 2) + (k & 3)) * 16, q[0], q[1], q[2], q[3]);
                }
            }
            if (at < 64) sts16(sb + OFF_U + (at >> 3) * U_CH + 72 * 16 + r * 2, pack_h(bf_lo(utail) * bf_lo((257u - eu) << 7), 0.f));
            __syncwarp();
            if (lane == 0) mbar_arrive(bars + 8 * B_U);
#pragma unroll
            for (int cb = 0; cb < 4; cb++) gw[cb] = lds128(go + 128 * cb);
            gate(3);
            bar_sync(1, 128);
            if (at < 16) st_gpu32((uint32_t*)p.ex->g + 1024 * h + 16 * (8 * (pr & 7) + (pr >> 3)) + 4 * ((at & 3) ^ (pr >> 4)) + (at >> 2),
                                  (pack_bf(sigmoid_f(bf_round(row_sum(sb + M_RG + 512 + at * 32))), 0.f) & 0xffffu) | (tag << 16));
            if (at == 0) TSTAMP(23);
        }
        const int ct = v & 1, kh = v >> 1;
        uint32_t wa[GU_PRE][4][4];
        uint32_t ta, tb;
        {
            const int krow0 = 8 * (mi >> 1) + r;
            const uint32_t off0 = krow0 * 64 + (((2 * ct + (mi & 1)) ^ ((krow0 >> 1) & 3)) << 4);
            ta = sb + OFF_RING + kh * 2048 + off0 + p.swap_gu; tb = ta + 4096 - 2 * p.swap_gu;
        }
        auto gu_load = [&](uint32_t (&a)[4][4], int s) {
            const uint32_t o = (s % NSLOT) * 8192 + (s % NSLOT >= ALT_SLOT ? dalt : 0);
            ldsm4t(ta + o, a[0][0], a[0][1], a[0][2], a[0][3]);
            ldsm4t(tb + o, a[1][0], a[1][1], a[1][2], a[1][3]);
            ldsm4t(ta + o + 1024, a[2][0], a[2][1], a[2][2], a[2][3]);
            ldsm4t(tb + o + 1024, a[3][0], a[3][1], a[3][2], a[3][3]);
        };
        auto gu_release = [&](const uint32_t (&a)[4][4], int s) {
            if (s < B_S - B_EMPTY && lane == 0) mbar_arrive(bars + 8 * (B_EMPTY + s) + (a[0][0] & a[1][0] & a[2][0] & a[3][0] & p.zero));
        };
        auto gu_park = [&](auto S0, auto N) {
            constexpr int s0 = decltype(S0)::value, n = decltype(N)::value;
            if (c < NGU_CTA) {
                mbar_wait_n<n, 8>(bars + 8 * s0);
#pragma unroll
                for (int s = s0; s < s0 + n; s++) gu_load(wa[s], s);
#pragma unroll
                for (int s = s0; s < s0 + n; s++) gu_release(wa[s], s);
            }
        };
        gu_park(IC<0>(), IC<4>());
        asm volatile("barrier.cluster.wait.acquire.aligned;" ::: "memory");
        mbar_wait(bars + 8 * B_TS);
#pragma unroll 1
        for (int i = 0; i < 2; i++) {
            const int es = group_tables(sb + OFF_TAB + (v + 4 * i) * T_CH, lane) + (int)eu;
            if (lane < 2) { const uint32_t o = mapa(sb, lane); st_async4(o + M_SC + (8 * h + v + 4 * i) * 4, (uint32_t)min(max(es, 1), 254) * 0x800080u, o + M_BARS + 8 * B_SC); }
        }
        __syncwarp();
        if (lane == 0) mbar_arrive(bars + 8 * B_TD);
        gu_park(IC<4>(), IC<GU_PRE - 4>());
        if (c < NGU_CTA) {
            float dgt[4] = {0.f, 0.f, 0.f, 0.f}, dup[4] = {0.f, 0.f, 0.f, 0.f}, dg2[4] = {0.f, 0.f, 0.f, 0.f}, du2[4] = {0.f, 0.f, 0.f, 0.f};
            const uint32_t xo = sb + OFF_XSEL + r * XS_ROW + 64 * kh + 16 * mi;
            auto gu_mma = [&](const uint32_t (&a)[4][4], const uint32_t (&b)[4]) {
                mma_bf(dgt, a[0][0], a[0][1], a[0][2], a[0][3], b[0], b[1]);
                mma_bf(dup, a[1][0], a[1][1], a[1][2], a[1][3], b[0], b[1]);
                mma_bf(dg2, a[2][0], a[2][1], a[2][2], a[2][3], b[2], b[3]);
                mma_bf(du2, a[3][0], a[3][1], a[3][2], a[3][3], b[2], b[3]);
            };
            auto gu_batch = [&](auto S0, auto N) {
                constexpr int s0 = decltype(S0)::value, n = decltype(N)::value;
                uint32_t b[n][4];
                mbar_wait_n<n, 8>(bars + 8 * s0);
#pragma unroll
                for (int i = 0; i < n; i++) { ldsm4(xo + 128 * (s0 + i), b[i][0], b[i][1], b[i][2], b[i][3]); gu_load(wa[i], s0 + i); }
#pragma unroll
                for (int i = 0; i < n; i++) gu_mma(wa[i], b[i]);
#pragma unroll
                for (int i = 0; i < n; i++) gu_release(wa[n - 1], s0 + i);
            };
            mbar_spin(bars + 8 * B_XS);
            if (at == 0) TSTAMP(12);
#pragma unroll
            for (int s = 0; s < GU_PRE; s++) { uint32_t b[4]; ldsm4(xo + 128 * s, b[0], b[1], b[2], b[3]); gu_mma(wa[s], b); }
            gu_batch(IC<6>(), IC<2>());
            mbar_spin(bars + 8 * (B_XS + 1));
            gu_batch(IC<8>(), IC<4>()); gu_batch(IC<12>(), IC<3>()); gu_batch(IC<15>(), IC<1>());
#pragma unroll
            for (int i = 0; i < 4; i++) { dgt[i] += dg2[i]; dup[i] += du2[i]; }
            if (at == 0) TSTAMP(13);
            const uint32_t red = sb + M_RG, hs = sb + OFF_XSEL;
            sts128(red + ((v ^ 2) * 32 + lane) * 16, __float_as_uint(kh ? dgt[0] : dgt[2]), __float_as_uint(kh ? dgt[1] : dgt[3]),
                   __float_as_uint(kh ? dup[0] : dup[2]), __float_as_uint(kh ? dup[1] : dup[3]));
            bar_sync(1, 128);
            const uint4 oth = lds128(red + at * 16);
#pragma unroll
            for (int i = 0; i < 2; i++) {
                const float gv = bf_round((kh ? dgt[2 + i] : dgt[i]) + __uint_as_float(i ? oth.y : oth.x));
                const float uv = bf_round((kh ? dup[2 + i] : dup[i]) + __uint_as_float(i ? oth.w : oth.z));
                const float sl = bf_round(gv * sigmoid_f(gv));
                uint32_t hv = pack_bf(sl * uv, 0.f) & 0xffffu;
                hv = (hv == 0x8000u) ? 0x8000u : (hv ^ 0x8000u);
                sts16(hs + (2 * t + i) * 64 + (g >> 1) * 16 + (2 * ct + kh) * 4 + (g & 1) * 2, hv);
            }
            bar_sync(1, 128);
            if (v == 0) st_gpu128(&p.ex->h[32 * c + lane], lds128(hs + lane * 16));
        }
        else mbar_wait(bars + 8 * (B_XS + 1));
        if (at == 0) TSTAMP(14);
        {
            mbar_wait(bars + 8 * B_G);
            const int row = (int)lds32(sb + M_IDX + ftok * 4);
            const int w = row & 7, jj = (row >> 3) & 7;
            const uint32_t xa = sb + OFF_S + h * 32768 + (row >> 9) * 8192 + (w & 4) * 1024 + ((row >> 5) & 7) * 512 + (w & 3) * 128 + (jj & 3) * 32 + (((fch >> 3) ^ (w & 1)) << 4) + (fch & 7) * 2;
            const float xv = bf_lo(lds16(xa));
            const uint32_t gp = lds32(sb + OFF_GP + (8 * w + jj) * 64 + (((row >> 6) & 3) ^ (jj >> 1)) * 16 + (row >> 9) * 4);
            const uint32_t ya = sb + (((fch >> 3) == h) ? OFF_TAB + (fch & 7) * T_CH : (h ? ALT1 : ALT0) + A_YIN + (fch & 7) * Y_CH) + (row >> 9) * 512 + (4 * w + ((row >> 6) & 3)) * 16 + jj * 2;
            const float rs = bf_round(sigmoid_f(ldsf(sb + M_RSEL + ftok * 4)));
            uint4 hq[14];
            {
                const uint4* hsrc = &p.ex->h[(56 * h + 2 * v) * 32 + lane];
                mbar_wait(bars + 8 * (B_FULL + NST_GU + H_WAIT));
                if (at == 0) TSTAMP(15);
#pragma unroll
                for (int i = 0; i < 14; i++) hq[i] = ld_gpu128(hsrc + (8 * (i >> 1) + (i & 1)) * 32);
                bool ok = false;
#pragma unroll 1
                for (int it = 0; it < (1 << 22); it++) {
                    uint32_t mn = 0xffffffffu;
#pragma unroll
                    for (int i = 0; i < 14; i++) mn = min(mn, hq[i].x);
                    ok = __all_sync(0xffffffffu, mn != 0);
                    if (ok) break;
                    if (PSLEEP > 0) __nanosleep(PSLEEP);
#pragma unroll
                    for (int i = 0; i < 14; i++) if (hq[i].x == 0) hq[i] = ld_gpu128(hsrc + (8 * (i >> 1) + (i & 1)) * 32);
                }
                if (!ok) __trap();
            }
            if (at == 0) TSTAMP(16);
            mbar_wait_n<DN_PRE, 8>(bars + 8 * (B_FULL + NST_GU));
            float dd[4][4];
#pragma unroll
            for (int j = 0; j < 4; j++) { dd[j][0] = dd[j][1] = dd[j][2] = dd[j][3] = 0.f; }
            const int krow0 = 64 * (v & 1) + 8 * (mi >> 1) + r;
            const uint32_t td = sb + OFF_RING + (v >> 1) * 4096 + krow0 * 32 + (((mi & 1) ^ ((krow0 >> 2) & 1)) << 4);
#pragma unroll
            for (int s = 0; s < 7; s++) {
                if (s >= DN_PRE) mbar_spin(bars + 8 * (B_FULL + NST_GU + s));
                const uint32_t tile = td + ((NST_GU + s) % NSLOT) * 8192 + ((NST_GU + s) % NSLOT >= ALT_SLOT ? dalt : 0);
                uint32_t a[4][4];
#pragma unroll
                for (int j = 0; j < 4; j++) ldsm4t(tile + j * 512, a[j][0], a[j][1], a[j][2], a[j][3]);
                mma_bf(dd[0], a[0][0], a[0][1], a[0][2], a[0][3], hq[2 * s].x, hq[2 * s].y);
                mma_bf(dd[1], a[1][0], a[1][1], a[1][2], a[1][3], hq[2 * s].z, hq[2 * s].w);
                mma_bf(dd[2], a[2][0], a[2][1], a[2][2], a[2][3], hq[2 * s + 1].x, hq[2 * s + 1].y);
                mma_bf(dd[3], a[3][0], a[3][1], a[3][2], a[3][3], hq[2 * s + 1].z, hq[2 * s + 1].w);
            }
            uint32_t ds[4];
#pragma unroll
            for (int j = 0; j < 4; j++) ds[j] = __float_as_uint((dd[0][j] + dd[1][j]) + (dd[2][j] + dd[3][j]));
            if (at == 0) TSTAMP(17);
            const uint32_t o = mapa(sb, h ^ 1);
            st_async16(o + OFF_DP + (128 * h + at) * 16, ds[0], ds[1], ds[2], ds[3], o + M_BARS + 8 * B_DP);
            sts128(sb + OFF_DP + (128 * h + at) * 16, ds[0], ds[1], ds[2], ds[3]);
            __syncwarp();
            if (lane == 0) mbar_arrive(bars + 8 * B_DP);
            mbar_spin(bars + 8 * B_DP);
            float pt[8];
#pragma unroll
            for (int k = 0; k < 8; k++) pt[k] = ldsf(sb + OFF_DP + k * 512 + at * 4);
            const float tot = -(((pt[0] + pt[1]) + (pt[2] + pt[3])) + ((pt[4] + pt[5]) + (pt[6] + pt[7])));
            const float eb = bf_round(bf_hi(gp) * bf_round(xv + bf_round(bf_round(tot) * rs)));
            mbar_wait_n<4, 8>(bars + 8 * B_Y);
            if (((row >> 8) & 1) == h) p.out[(size_t)row * D_ + 16 * pr + fch] = __float2bfloat16_rn(fmaf(bf_lo(gp), bf_lo(lds16(ya)), eb));
        }
        if (at == 0) { TSTAMP(18); TSDUMP(c < NGU_CTA ? 0x0087f300u : 0x0087c300u); if (c == 0) *(volatile unsigned*)&p.ex->epoch = epoch + 1; }
    } else {
        const uint32_t t_start = now_ns();
        asm volatile("setmaxnreg.dec.sync.aligned.u32 " HELP_REGS ";");
        if (pw != 12) {
            if (pw >= 14) {
#pragma unroll
                for (int k = 0; k < 5; k++) {
                    const int w = 1 + 2 * k, e = (tid & 63) - 32;
                    sts32(sb + OFF_BAND + k * 256 + (tid & 63) * 4, ((e >= 0 && e < w) ? 0x3C00u : 0u) | ((e + 1 >= 0 && e + 1 < w) ? 0x3C000000u : 0u));
                }
            } else {
                sts32(sb + M_BMAP + lane * 4, 0);
                if (c < NGU_CTA) {
                    st_gpu128(&p.ex->h[32 * c + lane], make_uint4(0, 0, 0, 0));
                    if (ld_gpu128(&p.ex->h[32 * c + lane]).x != 0) __trap();
                }
            }
        } else {
            if (lane == 0) {
#pragma unroll
                for (int k = B_S; k < NBAR; k++) mbar_init(bars + 8 * k, (k >= B_Y && k < B_KD) ? 9 : (k == B_KD || k == B_TS) ? 8 : (k == B_TD || k == B_U) ? 4 : k == B_XS + 1 ? 2 : k == B_DP ? 5 : 1);
#pragma unroll
                for (int k = B_S; k < B_XS; k++) mbar_expect(bars + 8 * k, 16384);
                asm volatile("fence.proxy.async.shared::cta;" ::: "memory");
                asm volatile("fence.mbarrier_init.release.cluster;" ::: "memory");
            }
            __syncwarp();
            asm volatile("barrier.cluster.arrive.relaxed.aligned;" ::: "memory");
            auto rows = [&](int i) {
                mbar_expect(bars + 8 * (B_X + i), 8192);
                tma4d(sb + OFF_XROW + i * 8192, &tm_r, 0, 0, 8 * i + 4 * h, pr, bars + 8 * (B_X + i));
            };
            if (lane == 0) {
                asm volatile("prefetch.tensormap [%0];" :: "l"(&tm_x) : "memory");
                rows(0);
            }
            __syncwarp();
            bar_arrive(7, 160);
            asm volatile("barrier.cluster.wait.acquire.aligned;" ::: "memory");
            if (lane == 0) {
                TSTAMP(20);
#pragma unroll 1
                for (int i = 0; i < 4; i++) {
                    tma4d_both(sb + OFF_S + (4 * h + i) * 8192, &tm_x, 16 * pr, 0, 0, 16 * i + 8 * h, bars + 8 * (B_S + i));
                    tma4d_both(sb + OFF_S + (4 * h + i) * 8192 + 4096, &tm_x, 16 * pr, 0, 4, 16 * i + 8 * h, bars + 8 * (B_S + i));
                    if (i < 3) rows(i + 1);
                }
                TSTAMP(24);
                asm volatile("prefetch.tensormap [%0];" :: "l"(&tm_gu) : "memory");
                asm volatile("prefetch.tensormap [%0];" :: "l"(&tm_down) : "memory");
                asm volatile("prefetch.tensormap [%0];" :: "l"(&tm_o) : "memory");
#pragma unroll
                for (int k = 0; k < B_S; k++) mbar_init(bars + 8 * k, k < B_EMPTY ? 1 : 4);
#pragma unroll
                for (int k = 0; k < B_EMPTY; k++) mbar_expect(bars + 8 * k, 8192);
#pragma unroll
                for (int k = B_XS; k < B_KD; k++) if (k != B_TD && k != B_G) mbar_expect(bars + 8 * k, k < B_TD ? (c < NGU_CTA ? 8192 : 0) : k == B_SC ? 64 : k == B_DP ? 2048 : 4096);
                asm volatile("fence.proxy.async.shared::cta;" ::: "memory");
            }
            __syncwarp();
        }
        bar_arrive(4, 256);
        bar_sync(6, 128);
        if (pw == 15) {
            const unsigned tag = (ld_epoch(p.ex) + 1) & 0xffffu;
            const int tok = lane & 7;
            uint32_t top = 0;
            bool ok = false;
            mbar_wait(bars + 8 * B_XF);
#pragma unroll 1
            for (int it = 0; it < (1 << 22); it++) {
                uint32_t tg;
                asm volatile("ld.relaxed.gpu.global.v2.u32 {%0,%1}, [%2];" : "=r"(top), "=r"(tg) : "l"(&p.ex->top[tok]) : "memory");
                ok = __all_sync(0xffffffffu, tg == tag);
                if (ok) break;
            }
            if (!ok) __trap();
            if (lane == 0) TSTAMP(25);
            const int row = 2047 - (int)(top & 0xffffu);
            if (c < NGU_CTA) {
#pragma unroll
                for (int k = 0; k < 8; k++) {
                    const int tk = 4 * h + ((k + pr) & 3), hf = k >> 2;
                    bulk_load_both(sb + OFF_XSEL + tk * XS_ROW + 1024 * hf, p.u + (size_t)__shfl_sync(0xffffffffu, row, tk) * D_ + 512 * hf, 1024, bars + 8 * (B_XS + hf));
                }
            }
            if (lane == 0) TSTAMP(21);
            if (lane < 8) {
                const uint32_t ord = top >> 16;
                sts32(sb + M_RSEL + tok * 4, ((ord & 0x8000u) ? (ord & 0x7fffu) : (~ord & 0xffffu)) << 16);
                sts32(sb + M_IDX + tok * 4, (uint32_t)row);
                if (((row >> 8) & 1) == h) asm volatile("red.shared.or.b32 [%0], %1;" :: "r"(sb + M_BMAP + ((row >> 6) & 3) * 32 + (row & 4) * 4 + ((row >> 4) & 3) * 4),
                                                   "r"(1u << (4 * (row >> 9) + (row & 3) + 2 * (row & 8))) : "memory");
            }
            __syncwarp();
            if (lane == 0) { mbar_arrive(bars + 8 * (B_XS + 1)); TSDUMP(0x02200000u); }
            mbar_wait_n<2, 8>(bars + 8 * (B_XS + 1));
            if (lane == 0) bulk_load(sb + OFF_GP, &p.ex->g[256 * h], 4096, bars + 8 * B_GL);
            __syncwarp();
            mbar_wait(bars + 8 * B_GL);
#pragma unroll 2
            for (int i = lane; i < 256; i += 32) {
                uint4 a = lds128(sb + OFF_GP + i * 16);
#pragma unroll 1
                for (int it = 0; (((a.x ^ (tag << 16)) | (a.y ^ (tag << 16)) | (a.z ^ (tag << 16)) | (a.w ^ (tag << 16))) >> 16) != 0; it++) {
                    if (it > (1 << 22)) __trap();
                    a = ld_gpu128(&p.ex->g[256 * h + i]);
                }
                auto both = [](uint32_t w) { return (w & 0xffffu) | (pack_bf(1.f - bf_lo(w), 0.f) << 16); };
                sts128(sb + OFF_GP + i * 16, both(a.x), both(a.y), both(a.z), both(a.w));
            }
            __syncwarp();
            if (lane == 0) { TSTAMP(30); TSDUMP(1u << 30); }
            if (lane == 0) mbar_arrive(bars + 8 * B_G);
            return;
        }
        const int s0 = c < NGU_CTA ? 0 : NST_GU;
        const uint32_t t0 = __shfl_sync(0xffffffffu, t_start, 0) + T_W + h * (DT_G / 2);
#pragma unroll 1
        for (int s = s0 + __shfl_sync(0xffffffffu, pw, 0) - 12; s < NST; s += 3) {
            const int slot = s < NSLOT ? s : s < 2 * NSLOT ? s - NSLOT : s - 2 * NSLOT;
            const uint32_t full = bars + 8 * (B_FULL + s), dst = sb + OFF_RING + slot * 8192 + (slot >= ALT_SLOT ? (h ? ALT1 : ALT0) + A_SLOT - ALT_SLOT * 8192 : 0);
            const uint32_t due = (t0 + DT_G * s + (s > NST_GU ? (DT_D - DT_G) * (s - NST_GU) : 0)) & ~63u;
#pragma unroll 1
            for (int n = 0; n < 1000; n++) {
                const uint32_t now = now_ns();
                if ((int)(due - now) <= 0) break;
                __nanosleep(min((now ^ due) >> 1, 1023u));
            }
            if (s >= X_SLOT) mbar_spin(bars + 8 * ((s >= s0 + NSLOT) ? B_EMPTY + s - NSLOT : slot >= ALT_SLOT ? B_U : B_XF));
            const int depth = s < NST_GU ? DEPTH_G : DEPTH_D;
            if (s >= s0 + depth) mbar_spin(full - 8 * depth);
            if (s < NST_GU) tma3d_warp(dst, &tm_gu, 32 * c, 64 * s, 0, full);
            else tma2d_warp(dst, &tm_down, 16 * pr, 1792 * h + 256 * (s - NST_GU), full);
        }
    }
}

typedef CUresult (*EncodeFn)(CUtensorMap*, CUtensorMapDataType, cuuint32_t, void*, const cuuint64_t*, const cuuint64_t*,
                             const cuuint32_t*, const cuuint32_t*, CUtensorMapInterleave, CUtensorMapSwizzle,
                             CUtensorMapL2promotion, CUtensorMapFloatOOBfill);

void make_map(EncodeFn f, CUtensorMap* m, const void* ptr, int rank, const cuuint64_t* dims, const cuuint64_t* strides, const cuuint32_t* box, CUtensorMapSwizzle sw) {
    const cuuint32_t es[4] = {1, 1, 1, 1};
    f(m, CU_TENSOR_MAP_DATA_TYPE_BFLOAT16, rank, (void*)ptr, dims, strides, box, es, CU_TENSOR_MAP_INTERLEAVE_NONE, sw,
      CU_TENSOR_MAP_L2_PROMOTION_L2_128B, CU_TENSOR_MAP_FLOAT_OOB_FILL_NONE);
}

}

extern "C" void kernel_launch(void* const* d_in, const int* in_sizes, int n_in, void* d_out, int out_size) {
    static EncodeFn enc = nullptr;
    static void* ex = nullptr;
    if (!enc) {
        void* fn = nullptr;
        cudaDriverEntryPointQueryResult qr;
        cudaGetDriverEntryPoint("cuTensorMapEncodeTiled", &fn, cudaEnableDefault, &qr);
        enc = (EncodeFn)fn;
        cudaFuncSetAttribute(fused_kernel, cudaFuncAttributeMaxDynamicSharedMemorySize, SMEM_BYTES);
        cudaGetSymbolAddress(&ex, g_ex);
    }
    CUtensorMap tgu, td, tx, tr, to;
    const char *wg = (const char*)d_in[9], *wu = (const char*)d_in[10];
    const bool swap = wu < wg;
    {
        const cuuint64_t dims[3] = {F_, D_, 2}, str[2] = {F_ * 2, (cuuint64_t)(swap ? wg - wu : wu - wg)};
        const cuuint32_t box[3] = {32, 64, 2};
        make_map(enc, &tgu, swap ? wu : wg, 3, dims, str, box, CU_TENSOR_MAP_SWIZZLE_64B);
    }
    {
        const cuuint64_t dims[2] = {D_, F_}, str[1] = {D_ * 2};
        const cuuint32_t box[2] = {16, 256};
        make_map(enc, &td, d_in[11], 2, dims, str, box, CU_TENSOR_MAP_SWIZZLE_32B);
    }
    {
        const cuuint64_t dims[4] = {D_, 4, 8, L_ / 32}, str[3] = {D_ * 2 * 8, D_ * 2, D_ * 2 * 32};
        const cuuint32_t box[4] = {16, 4, 4, 8}, obox[4] = {16, 4, 4, 2};
        make_map(enc, &tx, d_in[0], 4, dims, str, box, CU_TENSOR_MAP_SWIZZLE_32B);
        make_map(enc, &to, d_out, 4, dims, str, obox, CU_TENSOR_MAP_SWIZZLE_32B);
    }
    {
        const cuuint64_t dims[4] = {256, 4, L_ / 64, 64}, str[3] = {512, D_ * 2 * 64, D_ * 2};
        const cuuint32_t box[4] = {256, 4, 4, 1};
        make_map(enc, &tr, d_in[0], 4, dims, str, box, CU_TENSOR_MAP_SWIZZLE_NONE);
    }
    Params p;
    p.u = (const bf16*)d_in[0]; p.logA = (const bf16*)d_in[1]; p.Aim = (const bf16*)d_in[2];
    p.Cre = (const bf16*)d_in[3]; p.Cim = (const bf16*)d_in[4]; p.logdt = (const bf16*)d_in[5];
    p.Dskip = (const bf16*)d_in[6]; p.wr = (const bf16*)d_in[8]; p.gatew = (const bf16*)d_in[12];
    p.out = (bf16*)d_out;
    p.ex = (Exchange*)ex;
    p.zero = 0;
    p.swap_gu = swap ? 4096 : 0;
    fused_kernel<<<NCTA, NTHREADS, SMEM_BYTES>>>(p, tgu, td, tx, tr, to);
}
```

```cpp
#include <cuda_runtime.h>
#include <cuda_bf16.h>
#include <cuda_fp16.h>
#include <cuda.h>
#include <stdint.h>

typedef __nv_bfloat16 bf16;

namespace {

constexpr int L_ = 2048, D_ = 1024, F_ = 3584;
constexpr int NCTA = 130;
constexpr int NTHREADS = 512;
constexpr int MAIN_W0 = 4;
#define T_W 1600
#define DT_G 316
#define DT_D 344
#define DEPTH_G 5
#define DEPTH_D 3
#define H_WAIT 2
#define DN_PRE 5
#define PSLEEP 0
#define GU_BATCH 0
#define FENCES 16
#define MIX0_AT 2
#define MIX1_AT 4
#define SEND_FENCE 1
#define A_REUSE 0
#define MAIN_REGS "176"
#define HELP_REGS "32"
constexpr int GU_PRE = 6;
constexpr int NGU_CTA = 112;

constexpr int NSLOT    = 10;
constexpr int NST_GU   = 16, NST = 23;
constexpr int OFF_RING = 0;
constexpr int OFF_XROW = 53248, X_SLOT = 6;
constexpr int OFF_XSEL = 69632, XS_ROW = 2064;
constexpr int OFF_DP   = OFF_XSEL + 8192;
constexpr int OFF_S    = 87040;
constexpr int ALT0     = OFF_S + 32768, ALT1 = OFF_S - 512;
constexpr int A_YIN    = 32, Y_CH = 2064;
constexpr int A_SLOT   = 16896, ALT_SLOT = 8;
constexpr int U_PL     = 1184;
constexpr int U_CH     = 4752;
constexpr int OFF_U    = 153088;
constexpr int T_CH     = 4112;
constexpr int OFF_TAB  = 191104;
constexpr int T_R2     = 2176, T2_S = 208;
constexpr int T_R3     = 3040, T3_S = 336;
constexpr int OFF_GP   = 224000;
constexpr int OFF_BAND = 228096;
constexpr int OFF_MISC = 229376;
constexpr int M_BARS   = OFF_MISC;
constexpr int M_IDX    = OFF_MISC + 704;
constexpr int M_RSEL   = OFF_MISC + 736;
constexpr int M_BMAP   = OFF_MISC + 768;
constexpr int M_MX     = OFF_MISC + 896;
constexpr int M_SC     = OFF_MISC + 960;
constexpr int M_RG     = OFF_MISC + 1024;
constexpr int SMEM_BYTES = OFF_MISC + 3072;

constexpr int B_FULL = 0, B_EMPTY = NST, B_S = B_EMPTY + NST - NSLOT, B_XS = B_S + 4, B_TD = B_XS + 2, B_SC = B_TD + 1, B_G = B_SC + 1, B_GL = B_G + 1, B_NONE = B_GL + 1, B_DP = B_NONE + 1, B_Y = B_DP + 1,
              B_SD = B_Y + 4, B_KD = B_SD + 1, B_U = B_KD + 1, B_TS = B_U + 1, B_XF = B_TS + 1, B_X = B_XF + 1, NBAR = B_X + 4;
static_assert(NBAR <= 84, "barrier area");

struct Exchange {
    unsigned epoch, pad[31];
    uint4 h[8 * F_ / 8];
    uint4 r[L_ / 4];
    uint4 g[L_ / 4];
    uint2 top[16];
};
__device__ __align__(128) Exchange g_ex;

struct Params {
    const bf16 *u, *logA, *Aim, *Cre, *Cim, *logdt, *Dskip, *wr, *gatew;
    bf16* out;
    Exchange* ex;
    uint32_t zero;
    uint32_t swap_gu;
};

#define TSTAMP(i) do {} while (0)
#define CSTAMP(i) do {} while (0)
#define TSDUMP(mask) do {} while (0)
#define DBG_PARAMS
#define DBG_ARGS

__device__ __forceinline__ uint32_t smem_u32(const void* p) { return (uint32_t)__cvta_generic_to_shared(p); }
__device__ __forceinline__ void mbar_init(uint32_t b, uint32_t c) { asm volatile("mbarrier.init.shared::cta.b64 [%0], %1;" :: "r"(b), "r"(c) : "memory"); }
__device__ __forceinline__ void mbar_expect(uint32_t b, uint32_t tx) { asm volatile("mbarrier.arrive.expect_tx.shared::cta.b64 _, [%0], %1;" :: "r"(b), "r"(tx) : "memory"); }
__device__ __forceinline__ void mbar_arrive(uint32_t b) { asm volatile("mbarrier.arrive.shared::cta.b64 _, [%0];" :: "r"(b) : "memory"); }
#define WSLEEP "40"
__device__ __forceinline__ void mbar_wait(uint32_t b) {
    asm volatile("{\n\t.reg .pred p, q;\n\t.reg .u32 n;\n\tmov.u32 n, 0;\n"
                 "W%=:\n\tmbarrier.try_wait.parity.shared::cta.b64 p, [%0], 0;\n\t"
                 "@p bra D%=;\n\tnanosleep.u32 " WSLEEP ";\n\tadd.u32 n, n, 1;\n\tsetp.lt.u32 q, n, 4194304;\n\t@q bra W%=;\n"
                 "D%=:\n\t}" :: "r"(b) : "memory");
}
__device__ __forceinline__ void mbar_spin(uint32_t b) {
    asm volatile("{\n\t.reg .pred p, q;\n\t.reg .u32 n;\n\tmov.u32 n, 0;\n"
                 "W%=:\n\tmbarrier.try_wait.parity.shared::cta.b64 p, [%0], 0;\n\t"
                 "@p bra D%=;\n\tadd.u32 n, n, 1;\n\tsetp.lt.u32 q, n, 4194304;\n\t@q bra W%=;\n"
                 "D%=:\n\t}" :: "r"(b) : "memory");
}
__device__ __forceinline__ void mbar_wait2(uint32_t a, uint32_t b) {
    asm volatile("{\n\t.reg .pred p, q;\n\t.reg .u32 n;\n\tmov.u32 n, 0;\n"
                 "W%=:\n\tmbarrier.try_wait.parity.shared::cta.b64 p, [%0], 0;\n\tmbarrier.try_wait.parity.shared::cta.b64 q, [%1], 0;\n\tand.pred p, p, q;\n\t"
                 "@p bra D%=;\n\tadd.u32 n, n, 1;\n\tsetp.lt.u32 q, n, 4194304;\n\t@q bra W%=;\n"
                 "D%=:\n\t}" :: "r"(a), "r"(b) : "memory");
}
template <int N, int STEP>
__device__ __forceinline__ void mbar_wait_n(uint32_t b) {
#pragma unroll 1
    for (int n = 0; n < 4194304; n++) {
        uint32_t ok = 1;
#pragma unroll
        for (int i = 0; i < N; i++) {
            uint32_t d;
            asm volatile("{ .reg .pred p; mbarrier.try_wait.parity.shared::cta.b64 p, [%1], 0; selp.u32 %0, 1, 0, p; }" : "=r"(d) : "r"(b + STEP * i) : "memory");
            ok &= d;
        }
        if (ok) break;
    }
}
__device__ __forceinline__ unsigned ld_epoch(const Exchange* e) { unsigned v; asm volatile("ld.volatile.global.u32 %0, [%1];" : "=r"(v) : "l"(e) : "memory"); return v; }
__device__ __forceinline__ uint32_t now_ns() { uint32_t t; asm volatile("mov.u32 %0, %globaltimer_lo;" : "=r"(t)); return t; }
__device__ __forceinline__ uint32_t mapa(uint32_t addr, uint32_t rank) { uint32_t r; asm("mapa.shared::cluster.u32 %0, %1, %2;" : "=r"(r) : "r"(addr), "r"(rank)); return r; }
__device__ __forceinline__ void bulk_load(uint32_t dst, const void* src, uint32_t bytes, uint32_t bar) {
    asm volatile("cp.async.bulk.shared::cluster.global.mbarrier::complete_tx::bytes [%0], [%1], %2, [%3];" :: "r"(dst), "l"(src), "r"(bytes), "r"(bar) : "memory");
}
__device__ __forceinline__ void bulk_load_both(uint32_t dst, const void* src, uint32_t bytes, uint32_t bar) {
    asm volatile("{ .reg .pred p; elect.sync _|p, 0xffffffff;\n\t@p cp.async.bulk.shared::cluster.global.mbarrier::complete_tx::bytes.multicast::cluster [%0], [%1], %2, [%3], %4; }"
                 :: "r"(dst), "l"(src), "r"(bytes), "r"(bar), "h"((unsigned short)3) : "memory");
}
__device__ __forceinline__ void tma3d(uint32_t dst, const CUtensorMap* tm, int c0, int c1, int c2, uint32_t bar) {
    asm volatile("cp.async.bulk.tensor.3d.shared::cluster.global.mbarrier::complete_tx::bytes [%0], [%1, {%3, %4, %5}], [%2];"
        :: "r"(dst), "l"(tm), "r"(bar), "r"(c0), "r"(c1), "r"(c2) : "memory");
}
__device__ __forceinline__ void tma4d(uint32_t dst, const CUtensorMap* tm, int c0, int c1, int c2, int c3, uint32_t bar) {
    asm volatile("cp.async.bulk.tensor.4d.shared::cluster.global.mbarrier::complete_tx::bytes [%0], [%1, {%3, %4, %5, %6}], [%2];"
        :: "r"(dst), "l"(tm), "r"(bar), "r"(c0), "r"(c1), "r"(c2), "r"(c3) : "memory");
}
__device__ __forceinline__ void tma5d_both(uint32_t dst, const CUtensorMap* tm, int c0, int c3, uint32_t bar) {
    asm volatile("cp.async.bulk.tensor.5d.shared::cluster.global.mbarrier::complete_tx::bytes.multicast::cluster [%0], [%1, {%3, %5, %5, %4, %5}], [%2], %6;"
        :: "r"(dst), "l"(tm), "r"(bar), "r"(c0), "r"(c3), "r"(0), "h"((unsigned short)3) : "memory");
}
__device__ __forceinline__ void st_async16(uint32_t dst, uint32_t x, uint32_t y, uint32_t z, uint32_t w, uint32_t bar) {
    asm volatile("st.async.weak.shared::cluster.mbarrier::complete_tx::bytes.v4.b32 [%0], {%1,%2,%3,%4}, [%5];"
                 :: "r"(dst), "r"(x), "r"(y), "r"(z), "r"(w), "r"(bar) : "memory");
}
__device__ __forceinline__ void st_async4(uint32_t dst, uint32_t v, uint32_t bar) {
    asm volatile("st.async.weak.shared::cluster.mbarrier::complete_tx::bytes.b32 [%0], %1, [%2];" :: "r"(dst), "r"(v), "r"(bar) : "memory");
}
__device__ __forceinline__ void bar_sync(int id, int n) { asm volatile("bar.sync %0, %1;" :: "r"(id), "r"(n) : "memory"); }
__device__ __forceinline__ void bar_arrive(int id, int n) { asm volatile("bar.arrive %0, %1;" :: "r"(id), "r"(n) : "memory"); }
__device__ __forceinline__ void cp16(uint32_t dst, const void* src) { asm volatile("cp.async.cg.shared.global [%0], [%1], 16;" :: "r"(dst), "l"(src) : "memory"); }
__device__ __forceinline__ void cp_wait_all() { asm volatile("cp.async.wait_all;" ::: "memory"); }
__device__ __forceinline__ uint32_t ldg16(const void* p) { uint32_t v; asm volatile("ld.global.nc.u16 %0, [%1];" : "=r"(v) : "l"(p)); return v; }
__device__ __forceinline__ uint2 ldg64(const void* p) { uint2 v; asm volatile("ld.global.nc.v2.u32 {%0,%1}, [%2];" : "=r"(v.x), "=r"(v.y) : "l"(p)); return v; }
__device__ __forceinline__ uint4 ldg128(const void* p) { uint4 v; asm volatile("ld.global.nc.v4.u32 {%0,%1,%2,%3}, [%4];" : "=r"(v.x), "=r"(v.y), "=r"(v.z), "=r"(v.w) : "l"(p)); return v; }
__device__ __forceinline__ uint4 ld_gpu128(const void* p) { uint4 v; asm volatile("ld.relaxed.gpu.global.v4.u32 {%0,%1,%2,%3}, [%4];" : "=r"(v.x), "=r"(v.y), "=r"(v.z), "=r"(v.w) : "l"(p) : "memory"); return v; }
__device__ __forceinline__ void st_gpu32(void* p, uint32_t v) { asm volatile("st.relaxed.gpu.global.u32 [%0], %1;" :: "l"(p), "r"(v) : "memory"); }
__device__ __forceinline__ void st_gpu128(void* p, const uint4& v) { asm volatile("st.relaxed.gpu.global.v4.u32 [%0], {%1,%2,%3,%4};" :: "l"(p), "r"(v.x), "r"(v.y), "r"(v.z), "r"(v.w) : "memory"); }

__device__ __forceinline__ void ldsm4(uint32_t a, uint32_t& r0, uint32_t& r1, uint32_t& r2, uint32_t& r3) {
    asm volatile("ldmatrix.sync.aligned.m8n8.x4.shared.b16 {%0,%1,%2,%3}, [%4];" : "=r"(r0), "=r"(r1), "=r"(r2), "=r"(r3) : "r"(a) : "memory");
}
__device__ __forceinline__ void ldsm2(uint32_t a, uint32_t& r0, uint32_t& r1) {
    asm volatile("ldmatrix.sync.aligned.m8n8.x2.shared.b16 {%0,%1}, [%2];" : "=r"(r0), "=r"(r1) : "r"(a) : "memory");
}
__device__ __forceinline__ void ldsm4t(uint32_t a, uint32_t& r0, uint32_t& r1, uint32_t& r2, uint32_t& r3) {
    asm volatile("ldmatrix.sync.aligned.m8n8.x4.trans.shared.b16 {%0,%1,%2,%3}, [%4];" : "=r"(r0), "=r"(r1), "=r"(r2), "=r"(r3) : "r"(a) : "memory");
}
__device__ __forceinline__ uint32_t lds16(uint32_t a) { uint32_t v; asm volatile("ld.shared.u16 %0, [%1];" : "=r"(v) : "r"(a) : "memory"); return v; }
__device__ __forceinline__ uint32_t lds32(uint32_t a) { uint32_t v; asm volatile("ld.shared.u32 %0, [%1];" : "=r"(v) : "r"(a) : "memory"); return v; }
__device__ __forceinline__ uint2 lds64(uint32_t a) { uint2 v; asm volatile("ld.shared.v2.u32 {%0,%1}, [%2];" : "=r"(v.x), "=r"(v.y) : "r"(a) : "memory"); return v; }
__device__ __forceinline__ uint4 lds128(uint32_t a) { uint4 v; asm volatile("ld.shared.v4.u32 {%0,%1,%2,%3}, [%4];" : "=r"(v.x), "=r"(v.y), "=r"(v.z), "=r"(v.w) : "r"(a) : "memory"); return v; }
__device__ __forceinline__ void sts16(uint32_t a, uint32_t v) { asm volatile("st.shared.u16 [%0], %1;" :: "r"(a), "r"(v) : "memory"); }
__device__ __forceinline__ void sts32(uint32_t a, uint32_t v) { asm volatile("st.shared.u32 [%0], %1;" :: "r"(a), "r"(v) : "memory"); }
__device__ __forceinline__ void sts64(uint32_t a, uint32_t x, uint32_t y) { asm volatile("st.shared.v2.u32 [%0], {%1,%2};" :: "r"(a), "r"(x), "r"(y) : "memory"); }
__device__ __forceinline__ void sts128(uint32_t a, uint32_t x, uint32_t y, uint32_t z, uint32_t w) { asm volatile("st.shared.v4.u32 [%0], {%1,%2,%3,%4};" :: "r"(a), "r"(x), "r"(y), "r"(z), "r"(w) : "memory"); }
__device__ __forceinline__ void sts16_if(bool p, uint32_t a, uint32_t v) { asm volatile("{ .reg .pred q; setp.ne.u32 q, %2, 0; @q st.shared.u16 [%0], %1; }" :: "r"(a), "h"((unsigned short)v), "r"((uint32_t)p) : "memory"); }
__device__ __forceinline__ void sts128_if(bool p, uint32_t a, uint32_t x, uint32_t y, uint32_t z, uint32_t w) {
    asm volatile("{ .reg .pred q; setp.ne.u32 q, %5, 0; @q st.shared.v4.u32 [%0], {%1,%2,%3,%4}; }" :: "r"(a), "r"(x), "r"(y), "r"(z), "r"(w), "r"((uint32_t)p) : "memory");
}
__device__ __forceinline__ void stsf(uint32_t a, float v) { asm volatile("st.shared.f32 [%0], %1;" :: "r"(a), "f"(v) : "memory"); }
__device__ __forceinline__ float ldsf(uint32_t a) { float v; asm volatile("ld.shared.f32 %0, [%1];" : "=f"(v) : "r"(a) : "memory"); return v; }

__device__ __forceinline__ void mma_bf(float (&d)[4], uint32_t a0, uint32_t a1, uint32_t a2, uint32_t a3, uint32_t b0, uint32_t b1) {
    asm volatile("mma.sync.aligned.m16n8k16.row.col.f32.bf16.bf16.f32 {%0,%1,%2,%3}, {%4,%5,%6,%7}, {%8,%9}, {%0,%1,%2,%3};"
        : "+f"(d[0]), "+f"(d[1]), "+f"(d[2]), "+f"(d[3]) : "r"(a0), "r"(a1), "r"(a2), "r"(a3), "r"(b0), "r"(b1));
}
__device__ __forceinline__ void widen_bf(float (&d)[4], uint32_t a0, uint32_t a1, uint32_t b) {
    asm volatile("mma.sync.aligned.m16n8k8.row.col.f32.bf16.bf16.f32 {%0,%1,%2,%3}, {%4,%5}, {%6}, {%7,%7,%7,%7};"
        : "=f"(d[0]), "=f"(d[1]), "=f"(d[2]), "=f"(d[3]) : "r"(a0), "r"(a1), "r"(b), "f"(0.f));
}
__device__ __forceinline__ void widen_h(float (&d)[4], const uint32_t (&a)[2], uint32_t b) {
    asm volatile("mma.sync.aligned.m16n8k8.row.col.f32.f16.f16.f32 {%0,%1,%2,%3}, {%4,%5}, {%6}, {%7,%7,%7,%7};"
        : "=f"(d[0]), "=f"(d[1]), "=f"(d[2]), "=f"(d[3]) : "r"(a[0]), "r"(a[1]), "r"(b), "f"(0.f));
}
__device__ __forceinline__ void widen_add_h(float (&d)[4], const uint32_t (&a)[2], uint32_t b, const float (&c)[4]) {
    asm volatile("mma.sync.aligned.m16n8k8.row.col.f32.f16.f16.f32 {%0,%1,%2,%3}, {%4,%5}, {%6}, {%7,%8,%9,%10};"
        : "=f"(d[0]), "=f"(d[1]), "=f"(d[2]), "=f"(d[3]) : "r"(a[0]), "r"(a[1]), "r"(b), "f"(c[0]), "f"(c[1]), "f"(c[2]), "f"(c[3]));
}
__device__ __forceinline__ void mma_h(uint32_t (&d)[2], const uint32_t (&a)[4], uint32_t b0, uint32_t b1) {
    asm volatile("mma.sync.aligned.m16n8k16.row.col.f16.f16.f16.f16 {%0,%1}, {%2,%3,%4,%5}, {%6,%7}, {%0,%1};"
        : "+r"(d[0]), "+r"(d[1]) : "r"(a[0]), "r"(a[1]), "r"(a[2]), "r"(a[3]), "r"(b0), "r"(b1));
}
__device__ __forceinline__ void mma_h_z(uint32_t& d0, uint32_t& d1, const uint32_t (&a)[4], uint32_t b0, uint32_t b1) {
    asm volatile("mma.sync.aligned.m16n8k16.row.col.f16.f16.f16.f16 {%0,%1}, {%2,%3,%4,%5}, {%6,%7}, {%8,%8};"
        : "=r"(d0), "=r"(d1) : "r"(a[0]), "r"(a[1]), "r"(a[2]), "r"(a[3]), "r"(b0), "r"(b1), "r"(0u));
}
__device__ __forceinline__ void mma_h2(uint32_t& d0, uint32_t& d1, const uint32_t (&a)[4], uint32_t b0, uint32_t b1) {
    asm volatile("mma.sync.aligned.m16n8k16.row.col.f16.f16.f16.f16 {%0,%1}, {%2,%3,%4,%5}, {%6,%7}, {%0,%1};"
        : "+r"(d0), "+r"(d1) : "r"(a[0]), "r"(a[1]), "r"(a[2]), "r"(a[3]), "r"(b0), "r"(b1));
}
__device__ __forceinline__ void mma_h_k8(uint32_t& d0, uint32_t& d1, uint32_t a0, uint32_t a1, uint32_t b) {
    asm volatile("mma.sync.aligned.m16n8k8.row.col.f16.f16.f16.f16 {%0,%1}, {%2,%3}, {%4}, {%0,%1};" : "+r"(d0), "+r"(d1) : "r"(a0), "r"(a1), "r"(b));
}
__device__ __forceinline__ void mma_h_k8_z(uint32_t (&d)[2], uint32_t a0, uint32_t a1, uint32_t b) {
    asm volatile("mma.sync.aligned.m16n8k8.row.col.f16.f16.f16.f16 {%0,%1}, {%2,%3}, {%4}, {%5,%5};" : "=r"(d[0]), "=r"(d[1]) : "r"(a0), "r"(a1), "r"(b), "r"(0u));
}
__device__ __forceinline__ uint32_t pack_bf(float lo, float hi) { uint32_t r; asm("cvt.rn.bf16x2.f32 %0, %1, %2;" : "=r"(r) : "f"(hi), "f"(lo)); return r; }
__device__ __forceinline__ uint32_t pack_h(float lo, float hi) { uint32_t r; asm("cvt.rn.f16x2.f32 %0, %1, %2;" : "=r"(r) : "f"(hi), "f"(lo)); return r; }
__device__ __forceinline__ float bf_lo(uint32_t v) { return __uint_as_float(v << 16); }
__device__ __forceinline__ float bf_hi(uint32_t v) { return __uint_as_float(v & 0xffff0000u); }
__device__ __forceinline__ float bf_round(float x) { return __uint_as_float(pack_bf(0.f, x) & 0xffff0000u); }
__device__ __forceinline__ uint32_t hmul2_bf(uint32_t a, uint32_t b) { uint32_t r; asm("mul.rn.bf16x2 %0, %1, %2;" : "=r"(r) : "r"(a), "r"(b)); return r; }
__device__ __forceinline__ uint32_t hadd2_bf(uint32_t a, uint32_t b) { uint32_t r; asm("add.rn.bf16x2 %0, %1, %2;" : "=r"(r) : "r"(a), "r"(b)); return r; }
__device__ __forceinline__ uint32_t hfma2_bf(uint32_t a, uint32_t b, uint32_t c) { uint32_t r; asm("fma.rn.bf16x2 %0, %1, %2, %3;" : "=r"(r) : "r"(a), "r"(b), "r"(c)); return r; }
__device__ __forceinline__ uint32_t hi_mul_bf(uint32_t a, uint32_t b) { uint32_t r; asm("{ .reg .b16 l, h; .reg .b32 t; mov.b32 {l, h}, %1; mov.b32 t, {h, h}; mul.rn.bf16x2 %0, t, %2; }" : "=r"(r) : "r"(a), "r"(b)); return r; }
__device__ __forceinline__ uint32_t lo_fma_bf(uint32_t a, uint32_t b, uint32_t c) { uint32_t r; asm("{ .reg .b16 l, h; .reg .b32 t; mov.b32 {l, h}, %1; mov.b32 t, {l, l}; fma.rn.bf16x2 %0, t, %2, %3; }" : "=r"(r) : "r"(a), "r"(b), "r"(c)); return r; }
__device__ __forceinline__ uint32_t amax2_bf(uint32_t m, uint32_t v) { uint32_t r; asm("max.xorsign.abs.bf16x2 %0, %1, %2;" : "=r"(r) : "r"(m), "r"(v)); return r; }
__device__ __forceinline__ uint32_t amax2_h(uint32_t m, uint32_t v) { uint32_t r; asm("max.xorsign.abs.f16x2 %0, %1, %2;" : "=r"(r) : "r"(m), "r"(v)); return r; }
__device__ __forceinline__ uint32_t hadd(uint32_t a, uint32_t b) { uint32_t r; asm("add.rn.f16x2 %0, %1, %2;" : "=r"(r) : "r"(a), "r"(b)); return r; }
__device__ __forceinline__ uint32_t hsub(uint32_t a, uint32_t b) { uint32_t r; asm("sub.rn.f16x2 %0, %1, %2;" : "=r"(r) : "r"(a), "r"(b)); return r; }
__device__ __forceinline__ uint32_t hsub2(uint32_t a, uint32_t b) { uint32_t r; asm("sub.rn.ftz.f16x2 %0, %1, %2;" : "=r"(r) : "r"(a), "r"(b)); return r; }
__device__ __forceinline__ uint32_t hmul(uint32_t a, uint32_t b) { uint32_t r; asm("mul.rn.f16x2 %0, %1, %2;" : "=r"(r) : "r"(a), "r"(b)); return r; }
__device__ __forceinline__ uint32_t hfma(uint32_t a, uint32_t b, uint32_t c) { uint32_t r; asm("fma.rn.f16x2 %0, %1, %2, %3;" : "=r"(r) : "r"(a), "r"(b), "r"(c)); return r; }
__device__ __forceinline__ uint32_t hfms(uint32_t a, uint32_t b, uint32_t c) { uint32_t r; asm("{ .reg .b32 t; neg.f16x2 t, %3; fma.rn.f16x2 %0, %1, %2, t; }" : "=r"(r) : "r"(a), "r"(b), "r"(c)); return r; }
__device__ __forceinline__ uint32_t warp_max16(uint32_t m) { return __reduce_max_sync(0xffffffffu, max(m & 0x7fffu, (m >> 16) & 0x7fffu)); }
__device__ __forceinline__ float ex2f(float x) { float r; asm("ex2.approx.ftz.f32 %0, %1;" : "=f"(r) : "f"(x)); return r; }

__device__ __forceinline__ float exp_acc(float x) {
    const float t = x * 1.4426950216293335f;
    const float r = fmaf(x, 1.4426950216293335f, -t) + x * 1.9259629911266175e-8f;
    return ex2f(t) * fmaf(r, 0.6931471805599453f, 1.f);
}
__device__ __forceinline__ float sigmoid_f(float x) { return __fdividef(1.f, 1.f + ex2f(-x * 1.4426950408889634f)); }
__device__ __forceinline__ void cexp(float l2, float th, float& zr, float& zi) {
    const float mag = ex2f(l2);
    const float k = (th * 0.15915494309189535f + 12582912.f) - 12582912.f;
    float r = fmaf(-k, 6.2831854820251465f, th);
    r = fmaf(-k, -1.7484555314695172e-7f, r);
    zr = mag * __cosf(r);
    zi = mag * __sinf(r);
}
struct hc { uint32_t re, im; };
__device__ __forceinline__ hc cmul(const hc& a, const hc& b) { return {hfms(a.re, b.re, hmul(a.im, b.im)), hfma(a.re, b.im, hmul(a.im, b.re))}; }
__device__ __forceinline__ hc cmulc(const hc& a, const hc& b) { return {hfma(a.re, b.re, hmul(a.im, b.im)), hfms(a.im, b.re, hmul(a.re, b.im))}; }
struct fc2 { float r[2], i[2]; };
__device__ __forceinline__ void csq(fc2& z) {
#pragma unroll
    for (int m = 0; m < 2; m++) {
        const float r = fmaf(z.r[m], z.r[m], -(z.i[m] * z.i[m]));
        asm("{ .reg .f32 t; mul.f32 t, %0, %1; mul.f32 %0, t, 0f40000000; }" : "+f"(z.i[m]) : "f"(z.r[m]));
        z.r[m] = r;
    }
}
__device__ __forceinline__ hc pk(const fc2& z) { return {pack_h(z.r[0], z.r[1]), pack_h(z.i[0], z.i[1])}; }
__device__ __forceinline__ void csq_conj(fc2& z) {
#pragma unroll
    for (int m = 0; m < 2; m++) {
        const float r = fmaf(z.r[m], z.r[m], -(z.i[m] * z.i[m]));
        asm("{ .reg .f32 t, n; neg.f32 n, %1; mul.f32 t, %0, n; mul.f32 %0, t, 0f40000000; }" : "+f"(z.i[m]) : "f"(z.r[m]));
        z.r[m] = r;
    }
}

struct Powers { hc C, z1, z2, z4, c8, c16, c32, c64, z128, z256, z512, z1024; };
__device__ __forceinline__ void kg_powers(Powers& q, uint32_t la, uint32_t ai, uint32_t cr, uint32_t ci, float dt, float cf) {
    fc2 z, y;
    const float dtl = -dt * 1.4426950408889634f;
    const uint32_t eb = pack_bf(ex2f(bf_lo(la) * 1.4426950408889634f), ex2f(bf_hi(la) * 1.4426950408889634f));
    const float l2[2] = {bf_lo(eb) * dtl, bf_hi(eb) * dtl}, th[2] = {bf_lo(ai) * dt, bf_hi(ai) * dt};
#pragma unroll
    for (int m = 0; m < 2; m++) { cexp(l2[m], th[m], z.r[m], z.i[m]); cexp(l2[m] * 128.f, th[m] * 128.f, y.r[m], y.i[m]); }
    q.C.re = pack_h(bf_lo(cr) * cf, bf_hi(cr) * cf);
    q.C.im = pack_h(bf_lo(ci) * cf, bf_hi(ci) * cf);
    q.z1 = pk(z); csq(z); q.z128 = pk(y); csq(y);
    q.z2 = pk(z); csq(z); q.z256 = pk(y); csq(y);
    q.z4 = pk(z); csq_conj(z); q.z512 = pk(y); csq(y);
    q.c8 = pk(z); csq(z); q.z1024 = pk(y);
    q.c16 = pk(z); csq(z);
    q.c32 = pk(z); csq(z);
    q.c64 = pk(z);
}
struct Rows { hc ta[8], tb[8], tc[8], pp[8]; };
#define PUT(a0, a1, row, a, b) sts128((((row) & 1) ? (a1) : (a0)) + (row) * 512, (a).re, (a).im, (b).re, (b).im)
template <bool FIRST>
__device__ __forceinline__ void kg_rows(Rows& w, const Powers& q, uint32_t t0, uint32_t t1, uint32_t u0, uint32_t u1, uint32_t uc, uint32_t zr, uint32_t (&Rl)[2]) {
    w.ta[0] = q.C; w.ta[1] = cmul(q.C, q.z1); w.ta[2] = cmul(q.C, q.z2); w.ta[4] = cmul(q.C, q.z4); w.tb[0] = cmul(q.C, q.z256); w.tb[4] = cmul(q.C, q.z512);
    PUT(t0, t1, 0, w.ta[0], w.tb[0]); PUT(t0, t1, 4, w.ta[4], w.tb[4]);
    w.tb[1] = cmul(w.ta[2], q.z256); w.tb[2] = cmul(w.ta[4], q.z256);
    PUT(t0, t1, 1, w.ta[1], w.tb[1]); PUT(t0, t1, 2, w.ta[2], w.tb[2]);
    w.ta[3] = cmul(w.ta[1], q.z2); w.ta[6] = cmul(w.ta[2], q.z4); w.ta[5] = cmul(w.ta[1], q.z4); w.tb[5] = cmul(w.ta[4], q.z512); w.tb[6] = cmul(w.tb[0], q.z512);
    PUT(t0, t1, 5, w.ta[5], w.tb[5]); PUT(t0, t1, 6, w.ta[6], w.tb[6]);
    w.tb[3] = cmul(w.ta[6], q.z256); w.ta[7] = cmul(w.ta[3], q.z4); w.tb[7] = cmul(w.tb[2], q.z512);
    PUT(t0, t1, 3, w.ta[3], w.tb[3]); PUT(t0, t1, 7, w.ta[7], w.tb[7]);
    sts64(uc, q.c64.re, q.c64.im);
    w.pp[0] = hc{0x3C003C00u ^ zr, zr}; w.pp[1] = q.c8; w.pp[2] = q.c16; w.pp[4] = q.c32;
    w.tc[0] = cmul(q.C, q.z1024); w.pp[3] = cmul(q.c8, q.c16); w.pp[5] = cmul(q.c8, q.c32); w.pp[6] = cmul(q.c16, q.c32);
    w.tc[2] = cmul(w.tc[0], q.z128); w.tc[4] = cmul(w.tc[0], q.z256); w.tc[1] = cmul(w.tc[0], q.z512); w.pp[7] = cmul(w.pp[3], q.c32);
    PUT(u0, u1, 0, w.tc[0], w.pp[0]); PUT(u0, u1, 1, w.tc[1], w.pp[1]); PUT(u0, u1, 2, w.tc[2], w.pp[2]); PUT(u0, u1, 4, w.tc[4], w.pp[4]);
    w.tc[6] = cmul(w.tc[2], q.z256); w.tc[3] = cmul(w.tc[2], q.z512); w.tc[5] = cmul(w.tc[4], q.z512);
    PUT(u0, u1, 3, w.tc[3], w.pp[3]); PUT(u0, u1, 5, w.tc[5], w.pp[5]); PUT(u0, u1, 6, w.tc[6], w.pp[6]);
    w.tc[7] = cmul(w.tc[6], q.z512);
    PUT(u0, u1, 7, w.tc[7], w.pp[7]);
    const uint32_t last = hfms(w.tc[0].re, q.z1024.re, hmul(w.tc[0].im, q.z1024.im));
    if (FIRST) mma_h_k8_z(Rl, 0x3C003C00u - zr, 0x3C003C00u + zr, last); else mma_h_k8(Rl[0], Rl[1], 0x3C003C00u - zr, 0x3C003C00u + zr, last);
}
#undef PUT
template <bool FIRST>
__device__ __forceinline__ void kg_products(uint32_t rt0, uint32_t rt1, uint32_t ru0, uint32_t ru1, uint32_t rc, uint32_t zr,
                                            uint32_t (&Ra)[2][2], uint32_t (&Rb)[2][2], uint32_t (&Rc)[2]) {
    uint4 q1[8], q2[8], cw[8];
#pragma unroll
    for (int ks = 0; ks < 8; ks++) {
        q2[ks] = lds128(((ks & 1) ? ru1 : ru0) + (ks >> 1) * 128); if (!(ks & 1)) cw[ks] = lds128(rc + ks * 32); q1[ks] = lds128(((ks & 1) ? rt1 : rt0) + (ks >> 1) * 128);
    }
#pragma unroll
    for (int ks = 0; ks < 8; ks++) {
        const hc p0 = {q2[ks].z, q2[ks].w}, u = (ks & 1) ? hc{cw[ks & 6].z, cw[ks & 6].w} : hc{cw[ks].x, cw[ks].y};
        const hc p1 = cmul(p0, u), p2 = cmul(p1, u), p3 = cmul(p2, u);

        const uint32_t qa[4] = {p0.re ^ zr, p1.re, p0.im ^ zr, p1.im}, qb[4] = {p2.re, p3.re, p2.im, p3.im};
        if (FIRST && ks == 0) {
            mma_h_z(Rc[0], Rc[1], qa, q2[ks].x, q2[ks].y); mma_h_z(Ra[0][0], Ra[0][1], qa, q1[ks].x, q1[ks].y); mma_h_z(Rb[0][0], Rb[0][1], qa, q1[ks].z, q1[ks].w);
            mma_h_z(Ra[1][0], Ra[1][1], qb, q1[ks].x, q1[ks].y); mma_h_z(Rb[1][0], Rb[1][1], qb, q1[ks].z, q1[ks].w);
        } else {
            mma_h(Rc, qa, q2[ks].x, q2[ks].y); mma_h(Ra[0], qa, q1[ks].x, q1[ks].y); mma_h(Rb[0], qa, q1[ks].z, q1[ks].w);
            mma_h(Ra[1], qb, q1[ks].x, q1[ks].y); mma_h(Rb[1], qb, q1[ks].z, q1[ks].w);
        }
    }
}
__device__ __forceinline__ void kernel_gen(const uint2& la, const uint2& ai, const uint2& cr, const uint2& ci, float dt, float cf, uint32_t TB, uint32_t UB,
                                           int lane, uint32_t zr, uint32_t (&Ra)[2][2], uint32_t (&Rb)[2][2], uint32_t (&Rc)[2], uint32_t (&Rl)[2]) {
    const int g = lane >> 2, t = lane & 3;
    const uint32_t w0 = lane << 4, w1 = w0 ^ 64, r0 = g * 512 + (((g & 1) << 6) | (t << 4)), r1 = r0 ^ 64;
    const uint32_t t0 = TB + w0, t1 = TB + w1, u0 = UB + w0, u1 = UB + w1;
    const uint32_t uc = UB + 4096 + (lane >> 3) * 64 + t * 16 + (lane & 4) * 2;
    Powers p0, p1;
    Rows w;
    kg_powers(p0, la.x, ai.x, cr.x, ci.x, dt, cf);
    kg_rows<true>(w, p0, t0, t1, u0, u1, uc, zr, Rl);
    kg_powers(p1, la.y, ai.y, cr.y, ci.y, dt, cf);
    __syncwarp();
    kg_products<true>(TB + r0, TB + r1, UB + r0, UB + r1, UB + 4096 + t * 16, zr, Ra, Rb, Rc);
    __syncwarp();
    kg_rows<false>(w, p1, t0, t1, u0, u1, uc, zr, Rl);
    __syncwarp();
    kg_products<false>(TB + r0, TB + r1, UB + r0, UB + r1, UB + 4096 + t * 16, zr, Ra, Rb, Rc);
    __syncwarp();
}

template <int V> struct IC { static constexpr int value = V; };

#define LANE_VARS \
    int tid_; asm volatile("mov.u32 %0, %%tid.x;" : "=r"(tid_)); \
    [[maybe_unused]] const int lane = tid_ & 31, warp = (tid_ >> 5) - MAIN_W0, g = lane >> 2, t = lane & 3, mi = lane >> 3, r = lane & 7; \
    [[maybe_unused]] const uint32_t TB = sb + OFF_TAB + warp * T_CH, UB = sb + OFF_U + warp * U_CH; \
    [[maybe_unused]] const bool lead = (tid_ == 32 * MAIN_W0)

__device__ __forceinline__ void dense_step(uint32_t (&M)[8][2], uint32_t (&Ye)[8][2], uint32_t (&Yo)[8][2], uint32_t (&X)[8][2],
                                           uint32_t (&F)[8][2], uint32_t (&Bq)[2][4], uint32_t ua, uint32_t ta, uint32_t zr) {
    uint32_t E[8][2], A[2][4], S[2][4], G[8][2];
#pragma unroll
    for (int jp = 0; jp < 4; jp++) ldsm4(ua + jp * 256, E[2 * jp][0], E[2 * jp][1], E[2 * jp + 1][0], E[2 * jp + 1][1]);
#pragma unroll
    for (int h = 0; h < 2; h++) { A[h][0] = A_REUSE ? Bq[h][3] ^ zr : lds32(ta + 1024 * h); A[h][1] = lds32(ta + 1024 * h + 32); A[h][3] = lds32(ta + 1024 * h + 64); A[h][2] = A[h][1] ^ zr; }
#pragma unroll
    for (int J = 0; J < 8; J++) mma_h(Ye[J], Bq[0], F[J][0], F[J][1]);
#pragma unroll
    for (int J = 1; J < 8; J++) mma_h(Ye[J], Bq[1], F[J - 1][0], F[J - 1][1]);
#pragma unroll
    for (int J = 0; J < 8; J++) { G[J][0] = hsub(X[J][0], E[J][0]); G[J][1] = hsub(X[J][1], E[J][1]); }
#pragma unroll
    for (int jp = 0; jp < 4; jp++) ldsm4(ua + 2 * U_PL + jp * 256 - 16, X[2 * jp][0], X[2 * jp][1], X[2 * jp + 1][0], X[2 * jp + 1][1]);
#pragma unroll
    for (int h = 0; h < 2; h++) { Bq[h][1] = lds32(ta + 1024 * h + 96); Bq[h][3] = lds32(ta + 1024 * h + 128); Bq[h][0] = A[h][3] ^ zr; Bq[h][2] = Bq[h][1] ^ zr; }
#pragma unroll
    for (int J = 0; J < 8; J++) mma_h(Yo[J], A[0], G[J][0], G[J][1]);
#pragma unroll
    for (int J = 1; J < 8; J++) mma_h(Yo[J], A[1], G[J - 1][0], G[J - 1][1]);
#pragma unroll
    for (int h = 0; h < 2; h++)
#pragma unroll
        for (int i = 0; i < 4; i++) S[h][i] = hadd(A[h][i], Bq[h][i]);
#pragma unroll
    for (int J = 0; J < 8; J++) mma_h(M[J], S[0], E[J][0], E[J][1]);
#pragma unroll
    for (int J = 1; J < 8; J++) mma_h(M[J], S[1], E[J - 1][0], E[J - 1][1]);
#pragma unroll
    for (int J = 0; J < 8; J++) { F[J][0] = hsub(X[J][0], E[J][0]); F[J][1] = hsub(X[J][1], E[J][1]); }
}

__device__ __forceinline__ int group_tables(uint32_t TB, int lane) {
    const int g = lane >> 2, t = lane & 3;
    const uint4 b4 = lds128(TB + T_R2 + 16 * lane), c4 = lds128(TB + T_R2 + 512 + 16 * lane);
    uint32_t vb[4] = {b4.x, b4.y, b4.z, b4.w}, vc[2] = {c4.x, c4.y};
    const uint32_t k1024 = __shfl_sync(0xffffffffu, vc[0], 0) & 0xffffu;
    uint32_t kl = hadd(c4.z, __byte_perm(c4.z, 0, 0x1032));
    kl = hadd(kl, __shfl_xor_sync(0xffffffffu, kl, 1)); kl = hadd(kl, __shfl_xor_sync(0xffffffffu, kl, 2));
#pragma unroll
    for (int i = 0; i < 3; i++) sts128(TB + T_R2 + 16 * lane + 512 * i, 0, 0, 0, 0);
    if (lane == 2) vb[0] &= 0xffff0000u;
    if (lane == 0) vc[0] &= 0xffff0000u;
    if (lane == 4) vc[0] = hsub(vc[0], k1024);
    __syncwarp();
    if (t >= 2) {
        const uint32_t g1 = TB + T_R2 + T2_S * (g & 3) + 8 * (8 * t - 10 + (g >> 2));
        const uint32_t g0 = TB + T_R2 + T2_S * ((g - 1) & 3) + 8 * (8 * t - 10 + ((g - 1) >> 2)) + 4;
#pragma unroll
        for (int i = 0; i < 4; i++) {
            sts16(g0 + 16 * i, vb[i]); sts16(g0 + 16 * i + 10, vb[i]);
            sts16(g1 + 16 * i, vb[i] >> 16); sts16(g1 + 16 * i + 10, vb[i] >> 16);
        }
    }
    const uint32_t g3 = TB + T_R3 + T3_S * (((g - 1) >> 1) & 1) + 8 * (7 + 4 * t + ((g - 1) >> 2)) + 4 * ((g - 1) & 1);
#pragma unroll
    for (int i = 0; i < 2; i++) {
        sts16(g3 + 16 * i, vc[i]); sts16(g3 + 16 * i + 10, vc[i]);
        sts16(g3 + 16 * i + 128, vc[i] >> 16); sts16(g3 + 16 * i + 138, vc[i] >> 16);
    }
    const uint32_t g4 = (uint32_t)(((uint64_t)(T_R3 + T3_S + 308) << 48 | (uint64_t)(T_R2 + 180) << 32 | (T_R2 + 176) << 16 | (T_R2 + 3 * T2_S + 172)) >> (8 * (lane & 6))) & 0xffffu;
    sts16(TB + g4 + 10 * (lane & 1), (lane & 7) < 6 ? k1024 : kl);
    return (int)c4.w;
}

#define FENCE() do { if (zr) asm volatile("exit;"); } while (0)
struct Chunks { uint32_t c3, c2, c1, c0, cm1, cm2, cm3, cm4, d2, d1, d0, dm1, em2, em3; };
__device__ __forceinline__ void convolve(uint32_t sb, int h, uint32_t zr, int pr, bf16* out, const CUtensorMap* tm_o DBG_PARAMS) {
    const uint32_t bars = sb + M_BARS;
    uint32_t M[8][2], Ye[8][2], Yo[8][2], F[8][2], Bq[2][4];
    {
        LANE_VARS;
        uint32_t X[8][2];
        uint32_t ua = UB + ((mi & 1) ? 0 : U_PL) + (8 + 8 * (mi >> 1) + r) * 16, ta = TB + 4 * (1 + g + 2 * t);
        uint32_t A[3][4], S[2][4];
        __syncwarp();
#pragma unroll
        for (int h2 = 0; h2 < 3; h2++) { A[h2][0] = lds32(ta + 1024 * h2); A[h2][1] = lds32(ta + 1024 * h2 + 32); A[h2][3] = lds32(ta + 1024 * h2 + 64); A[h2][2] = A[h2][1] ^ zr; }
#pragma unroll
        for (int h2 = 0; h2 < 2; h2++) {
            Bq[h2][1] = lds32(ta + 1024 * h2 + 96); Bq[h2][3] = lds32(ta + 1024 * h2 + 128); Bq[h2][0] = A[h2][3] ^ zr; Bq[h2][2] = Bq[h2][1] ^ zr;
#pragma unroll
            for (int i = 0; i < 4; i++) S[h2][i] = hadd(A[h2][i], Bq[h2][i]);
        }
        const uint32_t an = A[0][0] ^ zr, un = UB + (9 + lane) * 16;
        if (lead) TSTAMP(10);
        mbar_spin(bars + 8 * B_U);
        if (lead) { TSTAMP(3); CSTAMP(27); }
        uint32_t E[8][2], N[8], G[8][2];
#pragma unroll
        for (int jp = 0; jp < 4; jp++) ldsm4(ua + jp * 256, E[2 * jp][0], E[2 * jp][1], E[2 * jp + 1][0], E[2 * jp + 1][1]);
#pragma unroll
        for (int jp = 0; jp < 4; jp++) ldsm4(ua + 2 * U_PL + jp * 256, X[2 * jp][0], X[2 * jp][1], X[2 * jp + 1][0], X[2 * jp + 1][1]);
        ldsm4(un, N[0], N[1], N[2], N[3]); ldsm4(un + 512, N[4], N[5], N[6], N[7]);
#pragma unroll
        for (int J = 0; J < 8; J++) mma_h_z(M[J][0], M[J][1], S[0], E[J][0], E[J][1]);
#pragma unroll
        for (int J = 1; J < 8; J++) mma_h(M[J], S[1], E[J - 1][0], E[J - 1][1]);
#pragma unroll
        for (int J = 2; J < 8; J++) mma_h(M[J], A[2], E[J - 2][0], E[J - 2][1]);
        if (FENCES & 32) FENCE();
#pragma unroll
        for (int J = 0; J < 8; J++) mma_h_k8_z(Ye[J], zr, an, X[J][1]);
#pragma unroll
        for (int J = 0; J < 8; J++) mma_h_k8_z(Yo[J], zr, an, N[J]);
#pragma unroll
        for (int J = 0; J < 8; J++) { G[J][0] = hsub(X[J][0], E[J][0]); G[J][1] = hsub(X[J][1], E[J][1]); }
#pragma unroll
        for (int jp = 0; jp < 4; jp++) ldsm4(ua + 2 * U_PL + jp * 256 - 16, X[2 * jp][0], X[2 * jp][1], X[2 * jp + 1][0], X[2 * jp + 1][1]);
#pragma unroll
        for (int J = 0; J < 8; J++) mma_h(Yo[J], A[0], G[J][0], G[J][1]);
#pragma unroll
        for (int J = 1; J < 8; J++) mma_h(Yo[J], A[1], G[J - 1][0], G[J - 1][1]);
#pragma unroll
        for (int J = 2; J < 8; J++) mma_h(Yo[J], A[2], G[J - 2][0], G[J - 2][1]);
#pragma unroll
        for (int J = 0; J < 8; J++) { F[J][0] = hsub(X[J][0], E[J][0]); F[J][1] = hsub(X[J][1], E[J][1]); }
#pragma unroll 1
        for (int k = 1; k < 8; k++) {
            ua -= 16; ta += 128;
            dense_step(M, Ye, Yo, X, F, Bq, ua, ta, zr);
        }
    }
    mbar_wait_n<2, 8>(bars + 8 * B_TD);
    LANE_VARS;
    if (lead) { TSTAMP(4); CSTAMP(28); }
    __syncwarp();
    const uint32_t idh = (g == 2 * t) ? 0x3C00u : (g == 2 * t + 1) ? 0x3C000000u : 0u;
    const uint32_t sbr = mapa(sb, h ^ 1);
    const uint32_t yl = TB + lane * 16, yr = sbr + (h ? ALT0 : ALT1) + A_YIN + warp * Y_CH + lane * 16;
    const uint32_t ys = lds32(sb + M_SC + (8 * h + warp) * 4);
    uint32_t ea[4];
    auto finish = [&](int J) {
        float m[4], e[4], o[4];
        widen_h(m, M[J], idh); widen_add_h(e, Ye[J], idh, m); widen_add_h(o, Yo[J], idh, m);
        const uint32_t y[4] = {hmul2_bf(pack_bf(e[0], e[2]), ys), hmul2_bf(pack_bf(o[0], o[2]), ys), hmul2_bf(pack_bf(e[1], e[3]), ys), hmul2_bf(pack_bf(o[1], o[3]), ys)};
        if (!(J & 1)) {
#pragma unroll
            for (int i = 0; i < 4; i++) ea[i] = y[i];
        } else {
            st_async16(yr + (J >> 1) * 512, h ? ea[0] : y[0], h ? ea[1] : y[1], h ? ea[2] : y[2], h ? ea[3] : y[3], sbr + M_BARS + 8 * (B_Y + (J >> 1)));
            sts128(yl + (J >> 1) * 512, h ? y[0] : ea[0], h ? y[1] : ea[1], h ? y[2] : ea[2], h ? y[3] : ea[3]);
            __syncwarp();
            if (lane == 0) mbar_arrive(bars + 8 * (B_Y + (J >> 1)));
        }
    };
    const uint32_t a1 = UB + (3 - mi) * U_PL + (8 + r) * 16;
    const uint32_t a2 = UB + ((2 - mi) & 3) * U_PL + (8 + r - (mi == 3)) * 16;
    const uint32_t a3 = UB + (2 - (mi & 1)) * U_PL + (7 + r) * 16;
    const uint32_t bt = sb + OFF_BAND + 4 * (32 + g + 2 * t);
    auto load3 = [&](Chunks& u, int j) { ldsm4(a2 + j * 128, u.d2, u.d1, u.d0, u.dm1); ldsm4(a1 + j * 128, u.c3, u.c2, u.c1, u.c0); ldsm2(a3 + j * 128, u.em2, u.em3); };
    auto load2 = [&](Chunks& u, int j) { load3(u, j); ldsm4(a1 + j * 128 - 16, u.cm1, u.cm2, u.cm3, u.cm4); };
    Chunks u;
    uint32_t B35[4];
    uint2 Q[4][3], QS[2][3];
    {
        const uint32_t f7 = lds32(bt + 768 - 36), g7 = lds32(bt + 768 - 4), f9 = lds32(bt + 1024 - 32), g9 = lds32(bt + 1024), h9 = lds32(bt + 1024 + 32);
        const uint32_t f1 = hmul(lds32(bt - 28), lds16(TB + T_R2 + 176) * 0x10001u);
        load3(u, 0);
        const uint32_t tq = TB + T_R3 + 8 * (7 + g - 2 * t);
        uint2 Q0[4], Q1[4], Q2[4];
#pragma unroll
        for (int i = 0; i < 4; i++) { Q0[i] = lds64(tq + 64 * i); Q1[i] = lds64(tq + T3_S + 64 * i); Q2[i] = lds64(tq + T3_S - 8 + 64 * i); }
#pragma unroll
        for (int J = 0; J < 8; J++) mma_h(Ye[J], Bq[0], F[J][0], F[J][1]);
#pragma unroll
        for (int J = 1; J < 8; J++) mma_h(Ye[J], Bq[1], F[J - 1][0], F[J - 1][1]);
        const uint32_t B7[4] = {zr, f7, f7 ^ zr, g7}, B9a[4] = {zr + zr, f9, f9 ^ zr, g9}, B9b[4] = {g9 ^ zr, h9, h9 ^ zr, zr * 3}, B1[4] = {zr * 5, f1, f1 ^ zr, zr * 7};
        const uint32_t g7b = g7 ^ zr, z7 = zr * 9;
        if (FENCES & 1) FENCE();
        uint32_t WE[2][4], WO[2][4];
#pragma unroll
        for (int j = 0; j < 5; j++) {
            uint32_t (&we)[4] = WE[j & 1], (&wo)[4] = WO[j & 1], (&pe)[4] = WE[~j & 1], (&po)[4] = WO[~j & 1];
            if (j == 3) {
                const uint32_t t2 = TB + T_R2 + 8 * (6 + g - 2 * t);
                B35[0] = lds32(bt + 256 - 28); B35[1] = lds32(bt + 512 - 40); B35[2] = lds32(bt + 256 + 4); B35[3] = lds32(bt + 512 - 8);
#pragma unroll
                for (int i = 0; i < 3; i++)
#pragma unroll
                    for (int s = 0; s < 4; s++) Q[s][i] = lds64(t2 + T2_S * s + 64 * i);
            }
            if (j < 4) {
                mma_h_z(we[2], we[3], B9a, u.d0, u.dm1); mma_h_z(wo[2], wo[3], B9a, u.d2, u.d1);
                mma_h_z(we[0], we[1], B7, u.c1, u.c0); mma_h_z(wo[0], wo[1], B7, u.c3, u.c2);
            }
            if (j == 0) { finish(0); finish(1); }
#pragma unroll
            for (int i = 0; i < 5 - j && j > 0; i++) { mma_h(Ye[j + 3 + i], pe, Q0[i].x, Q0[i].y); mma_h(Yo[j + 3 + i], pe, Q1[i].x, Q1[i].y); }
            if (j < 4) {
                mma_h2(we[2], we[3], B9b, u.em2, u.em3); mma_h2(wo[2], wo[3], B9b, u.d0, u.dm1);
                mma_h_k8(we[0], we[1], g7b, z7, u.dm1); mma_h_k8(wo[0], wo[1], g7b, z7, u.c1);
                mma_h(Ye[j + 4], B1, u.d0, u.dm1); mma_h(Yo[j + 4], B1, u.d2, u.d1);
                if (j < 3) load3(u, j + 1); else load2(u, 0);
            }
#pragma unroll
            for (int i = 0; i < 5 - j && j > 0; i++) { mma_h(Ye[j + 3 + i], po, Q2[i].x, Q2[i].y); mma_h(Yo[j + 3 + i], po, Q0[i].x, Q0[i].y); }
            if (j == 3) {
#pragma unroll
                for (int i = 0; i < 3; i++)
#pragma unroll
                    for (int s = 0; s < 2; s++) { QS[s][i].x = hadd(Q[s][i].x, Q[s + 2][i].x); QS[s][i].y = hadd(Q[s][i].y, Q[s + 2][i].y); }
            }
            if (j < 3 ? ((FENCES & 2) || (j == 2 && (FENCES & 4))) : (j == 4 && (FENCES & 8))) FENCE();
        }
    }
    uint32_t xo, go, ya, sel, any, wu, oo;
    auto mix_setup = [&]() {
        LANE_VARS;
        const int pos = 2 * (warp & 3) + (t >> 1);
        xo = sb + OFF_S + h * 32768 + (warp & 3) * 2048 + (warp >> 2) * 1024 + (g >> 1) * 128 + (t >> 1) * 64 + (g & 1) * 32 + (((t ^ (g >> 1)) & 1) << 4);
        go = sb + OFF_GP + (8 * pos + g) * 64 + ((warp >> 2) ^ (g >> 1) ^ (2 * (t & 2))) * 8;
        const int ch = 2 * mi + (r & 1);
        ya = sb + ((((r >> 1) & 1) == h) ? OFF_TAB + ch * T_CH : (h ? ALT1 : ALT0) + A_YIN + ch * Y_CH) + (8 * (warp & 3) + (r & 4) + 2 * (warp >> 2)) * 16;
        sel = lds16(sb + M_BMAP + (8 * warp + g) * 2);
        any = __reduce_or_sync(0xffffffffu, sel);
        sel >>= t >> 1;
        oo = (128 * (warp >> 2) + 8 * g + pos) * D_ + 8 * (t & 1);
        wu = __shfl_sync(0xffffffffu, warp, 0);
    };
    struct MixIn { uint32_t gp[2]; uint4 e[2]; };
    auto mix_load = [&](MixIn& q, int J) {
        const uint2 g2 = lds64(go ^ (16 * J));
        q.gp[0] = g2.x; q.gp[1] = g2.y;
#pragma unroll
        for (int k = 0; k < 2; k++) {
            const uint4 x = lds128(xo + J * 8192 + k * 512);
            q.e[k] = make_uint4(hi_mul_bf(q.gp[k], x.x), hi_mul_bf(q.gp[k], x.y), hi_mul_bf(q.gp[k], x.z), hi_mul_bf(q.gp[k], x.w));
        }
    };
    auto mix_calc = [&](MixIn& q, int J) {
#pragma unroll
        for (int k = 0; k < 2; k++) {
            uint32_t y[4];
            ldsm4t(ya + J * 512 + k * 16, y[0], y[1], y[2], y[3]);
            q.e[k] = make_uint4(lo_fma_bf(q.gp[k], y[0], q.e[k].x), lo_fma_bf(q.gp[k], y[1], q.e[k].y), lo_fma_bf(q.gp[k], y[2], q.e[k].z), lo_fma_bf(q.gp[k], y[3], q.e[k].w));
            if (J < 2) sts128_if(!((sel >> (4 * J + 2 * k)) & 1u), xo + J * 8192 + k * 512, q.e[k].x, q.e[k].y, q.e[k].z, q.e[k].w);
        }
    };
    auto mix_send = [&](const MixIn& q, int J) {
        if (J >= 2 && ((any >> (4 * J)) & 15u)) {
#pragma unroll
            for (int k = 0; k < 2; k++) if (!((sel >> (4 * J + 2 * k)) & 1u)) *(uint4*)(out + (size_t)(512 * J + 256 * h + 64 * k) * D_ + 16 * pr + oo) = q.e[k];
        } else {
#pragma unroll
            for (int k = 0; k < 2 && J >= 2; k++) sts128(xo + J * 8192 + k * 512, q.e[k].x, q.e[k].y, q.e[k].z, q.e[k].w);
            asm volatile("fence.proxy.async.shared::cta;" ::: "memory");
            __syncwarp();
            asm volatile("{ .reg .pred p; elect.sync _|p, 0xffffffff;\n\t@p cp.async.bulk.tensor.5d.global.shared::cta.bulk_group [%0, {%2, %3, %3, %4, %5}], [%1]; }"
                         :: "l"(tm_o), "r"(sb + OFF_S + h * 32768 + J * 8192 + (wu & 3) * 2048 + (wu >> 2) * 1024),
                            "r"(16 * pr), "r"(0), "r"(32 * J + 16 * h + 8 * (wu >> 2)), "r"(wu & 3) : "memory");
        }
    };
    MixIn q, q2, q3;
    const uint32_t zq = zr + zr;
#pragma unroll
    for (int j = 0; j < 6; j++) {
        if (j == MIX0_AT + 1) mix_send(q, 0);
        if (j == MIX1_AT + 1) mix_send(q, 1);
        if (j == MIX0_AT) mbar_wait_n<2, 8 * (B_Y - B_G)>(bars + 8 * B_G);
        else if (j == MIX1_AT) mbar_spin(bars + 8 * (B_Y + 1));
        else if (j > 0 && (FENCES & 16) && (SEND_FENCE || (j != MIX0_AT + 1 && j != MIX1_AT + 1))) FENCE();
        uint32_t H[7][2];
        mma_h_z(H[3][0], H[3][1], B35, u.d0, u.dm1); mma_h_z(H[4][0], H[4][1], B35, u.c1, u.c0);
        mma_h_z(H[5][0], H[5][1], B35, u.d2, u.d1); mma_h_z(H[6][0], H[6][1], B35, u.c3, u.c2);
        mma_h_z(H[2][0], H[2][1], B35, u.cm1, u.cm2); mma_h_z(H[1][0], H[1][1], B35, u.em2, u.em3); mma_h_z(H[0][0], H[0][1], B35, u.cm3, u.cm4);
        if (j < 5) load2(u, j + 1);
        if (j > 0) finish(j + 1);
        if (j == MIX0_AT) { mix_setup(); mix_load(q, 0); mix_calc(q, 0); }
        if (j == MIX1_AT) { mix_load(q, 1); mix_calc(q, 1); }
        if (j == 5) { mix_load(q2, 2); mix_load(q3, 3); }
        const int n = j < 4 ? 3 : 6 - j;
#pragma unroll
        for (int s = 0; s < 2; s++) {
            const int o = 3 - s;
            const uint32_t qe[4] = {H[o][0] ^ zr, H[o + 1][0] ^ zq, H[o][1] ^ zr, H[o + 1][1] ^ zq};
            const uint32_t qg[4] = {hsub(H[o + 2][0], H[o][0]), hsub2(H[o + 3][0], H[o + 1][0]), hsub(H[o + 2][1], H[o][1]), hsub2(H[o + 3][1], H[o + 1][1])};
            const uint32_t qf[4] = {hsub(H[o - 2][0], H[o][0]), hsub2(H[o - 1][0], H[o + 1][0]), hsub(H[o - 2][1], H[o][1]), hsub2(H[o - 1][1], H[o + 1][1])};
#pragma unroll
            for (int i = 0; i < n; i++) mma_h(M[j + 2 + i], qe, QS[s][i].x, QS[s][i].y);
#pragma unroll
            for (int i = 0; i < n; i++) mma_h(Yo[j + 2 + i], qg, Q[s][i].x, Q[s][i].y);
#pragma unroll
            for (int i = 0; i < n; i++) mma_h(Ye[j + 2 + i], qf, Q[s + 2][i].x, Q[s + 2][i].y);
        }
    }
    finish(7);
    if (lead) { TSTAMP(5); CSTAMP(29); }
    if (MIX1_AT == 5) mix_send(q, 1);
    mbar_spin(bars + 8 * (B_Y + 2));
    asm volatile("cp.async.bulk.commit_group;" ::: "memory");
    mix_calc(q2, 2);
    mix_send(q2, 2);
    asm volatile("cp.async.bulk.wait_group 0;" ::: "memory");
    __syncwarp();
    if (lane == 0) mbar_arrive(bars + 8 * B_SD);
    mbar_spin(bars + 8 * (B_Y + 3));
    if (lead) TSTAMP(6);
    mix_calc(q3, 3);
    mix_send(q3, 3);
    asm volatile("cp.async.bulk.commit_group;" ::: "memory");
    asm volatile("cp.async.bulk.wait_group.read 0;" ::: "memory");
}

__global__ void __cluster_dims__(2, 1, 1) __launch_bounds__(NTHREADS, 1)
fused_kernel(const Params p, const __grid_constant__ CUtensorMap tm_gu, const __grid_constant__ CUtensorMap tm_down, const __grid_constant__ CUtensorMap tm_x,
             const __grid_constant__ CUtensorMap tm_r, const __grid_constant__ CUtensorMap tm_o) {
    extern __shared__ __align__(1024) unsigned char smem[];
    const uint32_t sb = __shfl_sync(0xffffffffu, smem_u32(smem), 0);
    int tid;
    asm volatile("mov.u32 %0, %%tid.x;" : "=r"(tid));
    const int pw = tid >> 5, lane = tid & 31;
    const int kc = ((blockIdx.x >> 1) + 60) & 63, lo = kc < 32, kq = lo ? kc >> 3 : ((kc - 32) * 37) >> 8;
    const int h = blockIdx.x & 1;
    const int pr = kc < 60 ? 4 * kc - (lo ? 31 : 27) * kq - (lo ? 0 : 96) : kc;
    const int c = 2 * pr + h;
    const uint32_t bars = sb + M_BARS;

    if (blockIdx.x >= 128) {
        if (blockIdx.x != 128) return;
        const unsigned tag = (ld_epoch(p.ex) + 1) & 0xffffu;
        const uint32_t idx0 = 2047 - (512 * (tid & 3) + (tid >> 3) + 256 * ((tid >> 2) & 1));
        const uint32_t list = sb + 128;
#pragma unroll 1
        for (int pass = 0; pass < 2; pass++) {
            if (tid == 0) sts32(sb + 64, 0);
            sts128(list + 16 * tid, 0, 0, 0, 0);
            uint4 a = make_uint4(lane == 0 ? 0x10000u : 0u, 0, 0, 0);
            bool ok = pass == 0;
#pragma unroll 1
            for (int it = 0; it < (1 << 22) && !ok; it++) {
                a = ld_gpu128(&p.ex->r[tid]);
                ok = (((a.x ^ tag) | (a.y ^ tag) | (a.z ^ tag) | (a.w ^ tag)) & 0xffffu) == 0;
            }
            if (!ok) __trap();
            const uint32_t key[4] = {(a.x & 0xffff0000u) | idx0, (a.y & 0xffff0000u) | (idx0 - 64), (a.z & 0xffff0000u) | (idx0 - 128), (a.w & 0xffff0000u) | (idx0 - 192)};
            const uint32_t wm = __reduce_max_sync(0xffffffffu, max(max(key[0], key[1]), max(key[2], key[3])));
            if (lane == 0) sts32(sb + pw * 4, wm);
            __syncthreads();
            const uint2 q = lds64(sb + 8 * (lane & 7));
            const uint32_t thr = __reduce_min_sync(0xffffffffu, max(q.x, q.y));
            if (tid == 0) TSTAMP(0);
            const uint32_t n = (key[0] >= thr) + (key[1] >= thr) + (key[2] >= thr) + (key[3] >= thr);
            if (n) {
                uint32_t pos;
                asm volatile("atom.shared.add.u32 %0, [%1], %2;" : "=r"(pos) : "r"(sb + 64), "r"(n) : "memory");
#pragma unroll
                for (int i = 0; i < 4; i++) if (key[i] >= thr) { sts32(list + 4 * pos, key[i]); pos++; }
            }
            __syncthreads();
            const int ncand = (int)lds32(sb + 64);
            const uint2 l0 = lds64(list + 8 * lane);
#pragma unroll 1
            for (int j = pw; j < ncand; j += 16) {
                const uint32_t mine = lds32(list + 4 * j);
                int rank = __popc(__ballot_sync(0xffffffffu, l0.x > mine)) + __popc(__ballot_sync(0xffffffffu, l0.y > mine));
#pragma unroll 1
                for (int i = 64; i < ncand; i += 32) rank += __popc(__ballot_sync(0xffffffffu, lds32(list + 4 * (i + lane)) > mine));
                if (rank < 8 && lane == 0) asm volatile("st.relaxed.gpu.global.v2.u32 [%0], {%1, %2};" :: "l"(&p.ex->top[rank]), "r"(mine), "r"(pass ? tag : tag ^ 0x8000u) : "memory");
            }
            if (tid == 0) TSTAMP(1);
            __syncthreads();
        }
        if (tid == 0) TSDUMP(3u);
        return;
    }

    if (pw != 12) asm volatile("barrier.cluster.arrive.relaxed.aligned;" ::: "memory");

    if (pw >= MAIN_W0 && pw < MAIN_W0 + 8) {
        const int warp = pw - MAIN_W0;
        const uint32_t po = (8 * c + warp) * 128 + 4 * lane;
        uint2 v_la = ldg64(p.logA + po), v_ai = ldg64(p.Aim + po), v_cr = ldg64(p.Cre + po), v_ci = ldg64(p.Cim + po);
        const uint32_t ldt16 = ldg16(p.logdt + 8 * c + warp), dsk16 = ldg16(p.Dskip + 8 * c + warp);
        [[maybe_unused]] const bool lead = (tid == 32 * MAIN_W0);
        asm volatile("setmaxnreg.inc.sync.aligned.u32 " MAIN_REGS ";");
        [[maybe_unused]] const int d = 8 * c + warp;
        const int g = lane >> 2, t = lane & 3, mi = lane >> 3, r = lane & 7;
        const uint32_t TB = sb + OFF_TAB + warp * T_CH;
        const uint32_t UB = sb + OFF_U + warp * U_CH;
        const uint32_t zr = p.zero;

        uint32_t Ra[2][2], Rb[2][2], Rc[2], Rl[2];
        int esum;
        {
            const float dt = bf_round(exp_acc(__uint_as_float(ldt16 << 16)));
            const uint32_t ec = max(warp_max16(amax2_bf(amax2_bf(v_cr.x, v_cr.y), amax2_bf(v_ci.x, v_ci.y))) >> 7, 6u);
            const float cf = __uint_as_float((__float_as_uint(dt) & 0x7fffffu) | ((260u - ec) << 23));
            esum = (int)ec + (int)(__float_as_uint(dt) >> 23) - 274;
            kernel_gen(v_la, v_ai, v_cr, v_ci, dt, cf, TB, UB, lane, zr, Ra, Rb, Rc, Rl);
        }
        asm volatile("barrier.cluster.wait.acquire.aligned;" ::: "memory");
        if (lane == 0) mbar_arrive(bars + 8 * B_KD + (Rc[0] & zr));
        if (lead) TSTAMP(2);

        {
            uint32_t mk = amax2_h(amax2_h(amax2_h(Ra[0][0], Ra[0][1]), amax2_h(Ra[1][0], Ra[1][1])), amax2_h(amax2_h(Rb[0][0], Rb[0][1]), amax2_h(Rb[1][0], Rb[1][1])));
            mk = amax2_h(amax2_h(mk, hmul(Rl[0], 0x34003400u)), amax2_h(Rc[0], Rc[1]));
            const int eb = (dsk16 >> 7) & 0xff, ek = max((int)(warp_max16(mk) >> 10), eb ? eb - 127 - esum : 0), en = eb - esum - 3 - ek;
            const float ds = (lane == 0 && eb && en > 0) ? __uint_as_float(((dsk16 & 0x807fu) << 16) | (en << 23)) : 0.f;
            const float fs = __uint_as_float(max(139 - ek, 1) << 23);
            const uint32_t ks = pack_h(fs, fs);
            uint32_t va[4], vb[4];
#pragma unroll
            for (int i = 0; i < 4; i++) { va[i] = hmul(Ra[i >> 1][i & 1], ks); vb[i] = hmul(Rb[i >> 1][i & 1], ks); }
            va[0] = hadd(va[0], pack_h(ds, 0.f));
            const uint32_t k512 = __shfl_sync(0xffffffffu, vb[0], 2) & 0xffffu, k255 = __shfl_sync(0xffffffffu, va[3], 31);
#pragma unroll
            for (int i = 0; i < 4; i++) {
                const uint32_t pv = __shfl_sync(0xffffffffu, lane == 31 ? (i ? va[i - 1] : 0u) : va[i], lane - 1);
                sts64(TB + 48 + 256 * i + 8 * lane, __byte_perm(pv, va[i], 0x5432), va[i]);
            }
#pragma unroll
            for (int i = 0; i < 4; i++) {
                const uint32_t nx = __shfl_sync(0xffffffffu, lane == 0 ? (i < 3 ? vb[i + (i < 3)] : k512) : vb[i], lane + 1 + 2 * (lane & 1));
                const uint32_t aa = __byte_perm(vb[i], 0, 0x1010);
                sts128_if(t < 2, TB + 1072 + 256 * i + 32 * g + 16 * t, (i == 0 && lane == 0) ? __byte_perm(k255, aa, 0x5432) : aa ^ zr, aa, vb[i] ^ zr, __byte_perm(vb[i], nx, 0x5432));
            }
            const uint32_t k0 = lane == 3 ? k512 : 0u, kk = k0 * 0x10001u;
            sts128_if(lane < 8, TB + 16 * lane + (lane < 3 ? 0 : 2048), kk, kk ^ zr, kk + zr, k0);
            esum += (int)ek;
            sts128(TB + T_R2 + 16 * lane, vb[0], vb[1], vb[2], vb[3]);
            sts128(TB + T_R2 + 512 + 16 * lane, hmul(Rc[0], ks), hmul(Rc[1], ks), hmul(Rl[0], ks), (uint32_t)esum);
            __syncwarp();
            if (lane == 0) mbar_arrive(bars + 8 * B_TS);
        }
        if (lead) TSTAMP(11);

        convolve(sb, h, zr, pr, p.out, &tm_o DBG_ARGS);
        { LANE_VARS; if (lead) { TSTAMP(7); TSDUMP(0x3c000cffu); } }
    } else if (pw < 4) {
        const int v = pw, at = tid;
        const int g = lane >> 2, t = lane & 3, mi = lane >> 3, r = lane & 7;
        const uint32_t dalt = (h ? ALT1 : ALT0) + A_SLOT - ALT_SLOT * 8192;
        cp16(sb + OFF_GP + tid * 16, p.wr + tid * 8);
        cp16(sb + OFF_GP + 2048 + tid * 16, p.gatew + tid * 8);
        const unsigned epoch = ld_epoch(p.ex);
        if (tid == 0) sts128(sb + OFF_S - 16, 0, 0, 0, 0);
        const unsigned tag = (epoch + 1) & 0xffffu;
        const int ftok = 2 * ((at >> 2) & 3) + (at & 1), fch = (at >> 4) + 8 * ((at >> 1) & 1);
        uint32_t eu;
        {
            cp_wait_all();
            bar_sync(7, 160);
            const uint32_t wo = sb + OFF_GP + 512 * v + 64 * ((g >> 1) & 1) + 16 * t + 4 * (g & 1);
            uint32_t w0[4], w1[4];
#pragma unroll
            for (int cb = 0; cb < 4; cb++) { w0[cb] = lds32(wo + 128 * cb); w1[cb] = lds32(wo + 128 * cb + 8); }
            const uint32_t go = sb + OFF_GP + 2048 + 512 * v + 64 * (g & 1) + 16 * t;
            const uint32_t ro = sb + M_RG + (g >> 1) * 32 + (2 * v + (g & 1)) * 4;
            const uint32_t xo = sb + OFF_XROW + (g >> 1) * 2048 + 512 * v + 64 * (g & 1) + 16 * t;
            const uint32_t one0 = 0x3F803F80u ^ p.zero, one1 = 0x3F803F80u + p.zero;
            auto row_sum = [&](uint32_t a) {
                const uint4 x = lds128(a), y = lds128(a + 16);
                return ((__uint_as_float(x.x) + __uint_as_float(x.y)) + (__uint_as_float(x.z) + __uint_as_float(x.w)))
                     + ((__uint_as_float(y.x) + __uint_as_float(y.y)) + (__uint_as_float(y.z) + __uint_as_float(y.w)));
            };
            const int dl = 8 * (r >> 1) + 4 - 2 * mi - (r & 1);
            const uint32_t so = sb + OFF_S + (v >> 1) * 32768 + (dl & 6) * 1024 + (8 * (v & 1) + (dl >> 4)) * 128 + (dl & 1) * 64 + (dl & 8) * 4 + ((dl & 16) ^ (h << 4));
            const uint32_t so2 = so + (dl >= 0 ? 0 : v == 2 ? -30720 : v == 0 ? 26624 : 0), so1 = (dl < 0 && v == 0) ? sb + OFF_S - 16 : so2;
            auto src = [&](int k) { return (k == 0 ? so1 : (k & 3) == 0 ? so2 : so) + (k >> 2) * 8192 + (k & 3) * 256; };
            uint32_t xr[16][4], mx = 0, idb = 0;
            auto slice = [&](int k) { ldsm4t(src(k), xr[k][0], xr[k][1], xr[k][2], xr[k][3]); };
            auto to_half = [&](uint32_t (&q)[4]) {
                float f0[4], f1[4];
                widen_bf(f0, q[0], q[1], idb); widen_bf(f1, q[2], q[3], idb);
                q[0] = pack_h(f0[0], f0[1]); q[1] = pack_h(f0[2], f0[3]); q[2] = pack_h(f1[0], f1[1]); q[3] = pack_h(f1[2], f1[3]);
            };
            auto track = [&](int k) { mx = amax2_bf(amax2_bf(mx, amax2_bf(xr[k][0], xr[k][1])), amax2_bf(xr[k][2], xr[k][3])); };
            auto cta_exp = [&](uint32_t slot) {
                const uint4 m4 = lds128(slot);
                return max(max(m4.x, m4.y), max(m4.z, m4.w)) >> 7;
            };
            auto set_scale = [&]() { const uint32_t sc = (257u - eu) << 7; idb = (g == 2 * t) ? sc : (g == 2 * t + 1) ? sc << 16 : 0u; };
            uint4 x[4], gw[4];
#pragma unroll
            for (int cb = 0; cb < 4; cb++) gw[cb] = lds128(go + 128 * cb);
            auto gate = [&](int i) {
                float e0[4] = {0.f, 0.f, 0.f, 0.f}, e1[4] = {0.f, 0.f, 0.f, 0.f};
#pragma unroll
                for (int cb = 0; cb < 4; cb++)
                    mma_bf((cb & 1) ? e1 : e0, hmul2_bf(x[cb].x, gw[cb].x), hmul2_bf(x[cb].y, gw[cb].y), hmul2_bf(x[cb].z, gw[cb].z), hmul2_bf(x[cb].w, gw[cb].w), one0, one1);
                if (t == 0) stsf(ro + 512 + 128 * i, (e0[0] + e0[3]) + (e1[0] + e1[3]));
            };
#pragma unroll
            for (int i = 0; i < 4; i++) {
                if (i == 0) mbar_spin(bars + 8 * B_X); else mbar_wait_n<2, 8 * (B_X - B_S + 1)>(bars + 8 * (B_S + i - 1));
#pragma unroll
                for (int cb = 0; cb < 4; cb++) x[cb] = lds128(xo + 8192 * i + 128 * cb);
#pragma unroll
                for (int k = max(4 * i - 4, 0); k < 4 * i; k++) slice(k);
                float d0[4] = {0.f, 0.f, 0.f, 0.f}, d1[4] = {0.f, 0.f, 0.f, 0.f};
#pragma unroll
                for (int cb = 0; cb < 4; cb++) mma_bf((cb & 1) ? d1 : d0, x[cb].x, x[cb].y, x[cb].z, x[cb].w, w0[cb], w1[cb]);
                if (t == (g & 1)) stsf(ro + 128 * i, (d0[0] + d0[3]) + (d1[0] + d1[3]));
                if (i == 3) break;
                gate(i);
#pragma unroll
                for (int k = max(4 * i - 4, 0); k < 4 * i; k++) track(k);
                if (i == 2) {
                    const uint32_t wm = warp_max16(mx);
                    if (lane == 0) sts32(sb + M_MX + v * 4, wm);
                    bar_sync(1, 128);
                    eu = min(cta_exp(sb + M_MX) + 3u, 255u);
                    set_scale();
#pragma unroll
                    for (int k = 0; k < 8; k++) to_half(xr[k]);
                }
            }
            bar_sync(4, 256);
            if (at < 16) {
                const uint32_t rb = pack_bf(0.f, row_sum(sb + M_RG + at * 32));
                st_gpu32((uint32_t*)p.ex->r + 16 * c + at, ((rb ^ (((int)rb >> 31) | 0x80000000u)) & 0xffff0000u) | tag);
            }
            if (at == 32) mbar_arrive(bars + 8 * B_XF);
            if (at == 0) TSTAMP(8);
#pragma unroll
            for (int k = 8; k < 12; k++) { track(k); to_half(xr[k]); }
            mbar_spin(bars + 8 * (B_S + 3));
            if (at == 0) TSTAMP(9);
#pragma unroll
            for (int k = 12; k < 16; k++) slice(k);
            uint32_t utail = 0;
            if (at < 64 && r >= 5) utail = lds16(sb + OFF_S + 57344 + 1952 + ((12 - r) & 6) * 1024 + (r & 1) * 64 + ((h ^ 1) << 4) + 2 * (at >> 3));
#pragma unroll
            for (int k = 12; k < 16; k++) track(k);
            const uint32_t wm = warp_max16(amax2_bf(mx, utail));
            if (lane == 0) sts32(sb + M_MX + 16 + v * 4, wm);
#pragma unroll
            for (int k = 12; k < 16; k++) to_half(xr[k]);
            mbar_spin(bars + 8 * B_KD);
            const uint32_t uo = sb + OFF_U + g * U_CH + t * U_PL;
#pragma unroll
            for (int k = 0; k < 16; k++) sts128(uo + (8 + 4 * v + 16 * (k >> 2) + (k & 3)) * 16, xr[k][0], xr[k][1], xr[k][2], xr[k][3]);
            sts128(uo + v * 32, 0, 0, 0, 0); sts128(uo + v * 32 + 16, 0, 0, 0, 0);
            bar_sync(1, 128);
            const uint32_t ea = cta_exp(sb + M_MX + 16);
            if (ea > eu) {
                eu = ea;
                set_scale();
#pragma unroll 1
                for (int k = 0; k < 16; k++) {
                    uint32_t q[4];
                    ldsm4t(src(k), q[0], q[1], q[2], q[3]);
                    to_half(q);
                    sts128(uo + (8 + 4 * v + 16 * (k >> 2) + (k & 3)) * 16, q[0], q[1], q[2], q[3]);
                }
            }
            if (at < 64) sts16(sb + OFF_U + (at >> 3) * U_CH + 72 * 16 + r * 2, pack_h(bf_lo(utail) * bf_lo((257u - eu) << 7), 0.f));
            __syncwarp();
            if (lane == 0) mbar_arrive(bars + 8 * B_U);
#pragma unroll
            for (int cb = 0; cb < 4; cb++) gw[cb] = lds128(go + 128 * cb);
            gate(3);
            bar_sync(1, 128);
            if (at < 16) st_gpu32((uint32_t*)p.ex->g + 1024 * h + 16 * (8 * (pr & 7) + (pr >> 3)) + (at ^ (2 * (pr >> 4) + 8 * (pr & 1))),
                                  (pack_bf(sigmoid_f(bf_round(row_sum(sb + M_RG + 512 + at * 32))), 0.f) & 0xffffu) | (tag << 16));
            if (at == 0) TSTAMP(23);
        }
        const int ct = v & 1, kh = v >> 1;
        uint32_t wa[GU_PRE][4][4];
        uint32_t ta, tb;
        {
            const int krow0 = 8 * (mi >> 1) + r;
            const uint32_t off0 = krow0 * 64 + (((2 * ct + (mi & 1)) ^ ((krow0 >> 1) & 3)) << 4);
            ta = sb + OFF_RING + kh * 2048 + off0 + p.swap_gu; tb = ta + 4096 - 2 * p.swap_gu;
        }
        auto gu_load = [&](uint32_t (&a)[4][4], int s) {
            const uint32_t o = (s % NSLOT) * 8192 + (s % NSLOT >= ALT_SLOT ? dalt : 0);
            ldsm4t(ta + o, a[0][0], a[0][1], a[0][2], a[0][3]);
            ldsm4t(tb + o, a[1][0], a[1][1], a[1][2], a[1][3]);
            ldsm4t(ta + o + 1024, a[2][0], a[2][1], a[2][2], a[2][3]);
            ldsm4t(tb + o + 1024, a[3][0], a[3][1], a[3][2], a[3][3]);
        };
        auto gu_release = [&](const uint32_t (&a)[4][4], int s) {
            if (s < B_S - B_EMPTY && lane == 0) mbar_arrive(bars + 8 * (B_EMPTY + s) + (a[0][0] & a[1][0] & a[2][0] & a[3][0] & p.zero));
        };
        auto gu_park = [&](auto S0, auto N) {
            constexpr int s0 = decltype(S0)::value, n = decltype(N)::value;
            if (c < NGU_CTA) {
                mbar_wait_n<n, 8>(bars + 8 * s0);
#pragma unroll
                for (int s = s0; s < s0 + n; s++) gu_load(wa[s], s);
#pragma unroll
                for (int s = s0; s < s0 + n; s++) gu_release(wa[s], s);
            }
        };
        gu_park(IC<0>(), IC<4>());
        asm volatile("barrier.cluster.wait.acquire.aligned;" ::: "memory");
        mbar_wait(bars + 8 * B_TS);
#pragma unroll 1
        for (int i = 0; i < 2; i++) {
            const int es = group_tables(sb + OFF_TAB + (v + 4 * i) * T_CH, lane) + (int)eu;
            if (lane < 2) { const uint32_t o = mapa(sb, lane); st_async4(o + M_SC + (8 * h + v + 4 * i) * 4, (uint32_t)min(max(es, 1), 254) * 0x800080u, o + M_BARS + 8 * B_SC); }
        }
        __syncwarp();
        if (lane == 0) mbar_arrive(bars + 8 * B_TD);
        gu_park(IC<4>(), IC<GU_PRE - 4>());
        if (c < NGU_CTA) {
            float dgt[4] = {0.f, 0.f, 0.f, 0.f}, dup[4] = {0.f, 0.f, 0.f, 0.f}, dg2[4] = {0.f, 0.f, 0.f, 0.f}, du2[4] = {0.f, 0.f, 0.f, 0.f};
            const uint32_t xo = sb + OFF_XSEL + r * XS_ROW + 64 * kh + 16 * mi;
            auto gu_mma = [&](const uint32_t (&a)[4][4], const uint32_t (&b)[4]) {
                mma_bf(dgt, a[0][0], a[0][1], a[0][2], a[0][3], b[0], b[1]);
                mma_bf(dup, a[1][0], a[1][1], a[1][2], a[1][3], b[0], b[1]);
                mma_bf(dg2, a[2][0], a[2][1], a[2][2], a[2][3], b[2], b[3]);
                mma_bf(du2, a[3][0], a[3][1], a[3][2], a[3][3], b[2], b[3]);
            };
            auto gu_batch = [&](auto S0, auto N) {
                constexpr int s0 = decltype(S0)::value, n = decltype(N)::value;
                uint32_t b[n][4];
                mbar_wait_n<n, 8>(bars + 8 * s0);
#pragma unroll
                for (int i = 0; i < n; i++) { ldsm4(xo + 128 * (s0 + i), b[i][0], b[i][1], b[i][2], b[i][3]); gu_load(wa[i], s0 + i); }
#pragma unroll
                for (int i = 0; i < n; i++) gu_mma(wa[i], b[i]);
#pragma unroll
                for (int i = 0; i < n; i++) gu_release(wa[n - 1], s0 + i);
            };
            mbar_spin(bars + 8 * B_XS);
            if (at == 0) TSTAMP(12);
#pragma unroll
            for (int s = 0; s < GU_PRE; s++) { uint32_t b[4]; ldsm4(xo + 128 * s, b[0], b[1], b[2], b[3]); gu_mma(wa[s], b); }
            gu_batch(IC<6>(), IC<2>());
            mbar_spin(bars + 8 * (B_XS + 1));
            gu_batch(IC<8>(), IC<4>()); gu_batch(IC<12>(), IC<3>()); gu_batch(IC<15>(), IC<1>());
#pragma unroll
            for (int i = 0; i < 4; i++) { dgt[i] += dg2[i]; dup[i] += du2[i]; }
            if (at == 0) TSTAMP(13);
            const uint32_t red = sb + M_RG, hs = sb + OFF_XSEL;
            sts128(red + ((v ^ 2) * 32 + lane) * 16, __float_as_uint(kh ? dgt[0] : dgt[2]), __float_as_uint(kh ? dgt[1] : dgt[3]),
                   __float_as_uint(kh ? dup[0] : dup[2]), __float_as_uint(kh ? dup[1] : dup[3]));
            bar_sync(1, 128);
            const uint4 oth = lds128(red + at * 16);
#pragma unroll
            for (int i = 0; i < 2; i++) {
                const float gv = bf_round((kh ? dgt[2 + i] : dgt[i]) + __uint_as_float(i ? oth.y : oth.x));
                const float uv = bf_round((kh ? dup[2 + i] : dup[i]) + __uint_as_float(i ? oth.w : oth.z));
                const float sl = bf_round(gv * sigmoid_f(gv));
                uint32_t hv = pack_bf(sl * uv, 0.f) & 0xffffu;
                hv = (hv == 0x8000u) ? 0x8000u : (hv ^ 0x8000u);
                sts16(hs + (2 * t + i) * 64 + (g >> 1) * 16 + (2 * ct + kh) * 4 + (g & 1) * 2, hv);
            }
            bar_sync(1, 128);
            if (v == 0) st_gpu128(&p.ex->h[32 * c + lane], lds128(hs + lane * 16));
        }
        else mbar_wait(bars + 8 * (B_XS + 1));
        if (at == 0) TSTAMP(14);
        {
            mbar_wait(bars + 8 * B_G);
            const int row = (int)lds32(sb + M_IDX + ftok * 4);
            const int w = row & 7, jj = (row >> 3) & 7;
            const uint32_t xa = sb + OFF_S + h * 32768 + (row >> 9) * 8192 + (w & 6) * 1024 + ((row >> 4) & 15) * 128 + (w & 1) * 64 + (jj & 1) * 32 + ((2 * fch) ^ (row & 16));
            const float xv = bf_lo(lds16(xa));
            const uint32_t gp = lds32(sb + OFF_GP + (8 * w + jj) * 64 + ((4 * (row >> 9) + ((row >> 6) & 3)) ^ ((jj & 6) + 8 * (w & 1))) * 4);
            const uint32_t ya = sb + (((fch >> 3) == h) ? OFF_TAB + (fch & 7) * T_CH : (h ? ALT1 : ALT0) + A_YIN + (fch & 7) * Y_CH) + (row >> 9) * 512 + (4 * w + ((row >> 6) & 3)) * 16 + jj * 2;
            const float rs = bf_round(sigmoid_f(ldsf(sb + M_RSEL + ftok * 4)));
            uint4 hq[14];
            {
                const uint4* hsrc = &p.ex->h[(56 * h + 2 * v) * 32 + lane];
                mbar_wait(bars + 8 * (B_FULL + NST_GU + H_WAIT));
                if (at == 0) TSTAMP(15);
#pragma unroll
                for (int i = 0; i < 14; i++) hq[i] = ld_gpu128(hsrc + (8 * (i >> 1) + (i & 1)) * 32);
                bool ok = false;
#pragma unroll 1
                for (int it = 0; it < (1 << 22); it++) {
                    uint32_t mn = 0xffffffffu;
#pragma unroll
                    for (int i = 0; i < 14; i++) mn = min(mn, hq[i].x);
                    ok = __all_sync(0xffffffffu, mn != 0);
                    if (ok) break;
                    if (PSLEEP > 0) __nanosleep(PSLEEP);
#pragma unroll
                    for (int i = 0; i < 14; i++) if (hq[i].x == 0) hq[i] = ld_gpu128(hsrc + (8 * (i >> 1) + (i & 1)) * 32);
                }
                if (!ok) __trap();
            }
            if (at == 0) TSTAMP(16);
            mbar_wait_n<DN_PRE, 8>(bars + 8 * (B_FULL + NST_GU));
            float dd[4][4];
#pragma unroll
            for (int j = 0; j < 4; j++) { dd[j][0] = dd[j][1] = dd[j][2] = dd[j][3] = 0.f; }
            const int krow0 = 64 * (v & 1) + 8 * (mi >> 1) + r;
            const uint32_t td = sb + OFF_RING + (v >> 1) * 4096 + krow0 * 32 + (((mi & 1) ^ ((krow0 >> 2) & 1)) << 4);
#pragma unroll
            for (int s = 0; s < 7; s++) {
                if (s >= DN_PRE) mbar_spin(bars + 8 * (B_FULL + NST_GU + s));
                const uint32_t tile = td + ((NST_GU + s) % NSLOT) * 8192 + ((NST_GU + s) % NSLOT >= ALT_SLOT ? dalt : 0);
                uint32_t a[4][4];
#pragma unroll
                for (int j = 0; j < 4; j++) ldsm4t(tile + j * 512, a[j][0], a[j][1], a[j][2], a[j][3]);
                mma_bf(dd[0], a[0][0], a[0][1], a[0][2], a[0][3], hq[2 * s].x, hq[2 * s].y);
                mma_bf(dd[1], a[1][0], a[1][1], a[1][2], a[1][3], hq[2 * s].z, hq[2 * s].w);
                mma_bf(dd[2], a[2][0], a[2][1], a[2][2], a[2][3], hq[2 * s + 1].x, hq[2 * s + 1].y);
                mma_bf(dd[3], a[3][0], a[3][1], a[3][2], a[3][3], hq[2 * s + 1].z, hq[2 * s + 1].w);
            }
            uint32_t ds[4];
#pragma unroll
            for (int j = 0; j < 4; j++) ds[j] = __float_as_uint((dd[0][j] + dd[1][j]) + (dd[2][j] + dd[3][j]));
            if (at == 0) TSTAMP(17);
            const uint32_t o = mapa(sb, h ^ 1);
            st_async16(o + OFF_DP + (128 * h + at) * 16, ds[0], ds[1], ds[2], ds[3], o + M_BARS + 8 * B_DP);
            sts128(sb + OFF_DP + (128 * h + at) * 16, ds[0], ds[1], ds[2], ds[3]);
            __syncwarp();
            if (lane == 0) mbar_arrive(bars + 8 * B_DP);
            mbar_spin(bars + 8 * B_DP);
            float pt[8];
#pragma unroll
            for (int k = 0; k < 8; k++) pt[k] = ldsf(sb + OFF_DP + k * 512 + at * 4);
            const float tot = -(((pt[0] + pt[1]) + (pt[2] + pt[3])) + ((pt[4] + pt[5]) + (pt[6] + pt[7])));
            const float eb = bf_round(bf_hi(gp) * bf_round(xv + bf_round(bf_round(tot) * rs)));
            mbar_wait_n<3, 8>(bars + 8 * (B_Y + 2));
            if (((row >> 8) & 1) == h) p.out[(size_t)row * D_ + 16 * pr + fch] = __float2bfloat16_rn(fmaf(bf_lo(gp), bf_lo(lds16(ya)), eb));
        }
        if (at == 0) { TSTAMP(18); TSDUMP(c < NGU_CTA ? 0x0087f300u : 0x0087c300u); if (c == 0) *(volatile unsigned*)&p.ex->epoch = epoch + 1; }
    } else {
        const uint32_t t_start = now_ns();
        asm volatile("setmaxnreg.dec.sync.aligned.u32 " HELP_REGS ";");
        if (pw != 12) {
            if (pw >= 14) {
#pragma unroll
                for (int k = 0; k < 5; k++) {
                    const int w = 1 + 2 * k, e = (tid & 63) - 32;
                    sts32(sb + OFF_BAND + k * 256 + (tid & 63) * 4, ((e >= 0 && e < w) ? 0x3C00u : 0u) | ((e + 1 >= 0 && e + 1 < w) ? 0x3C000000u : 0u));
                }
            } else {
                sts32(sb + M_BMAP + lane * 4, 0);
                if (c < NGU_CTA) {
                    st_gpu128(&p.ex->h[32 * c + lane], make_uint4(0, 0, 0, 0));
                    if (ld_gpu128(&p.ex->h[32 * c + lane]).x != 0) __trap();
                }
            }
        } else {
            if (lane == 0) {
#pragma unroll
                for (int k = B_S; k < NBAR; k++) mbar_init(bars + 8 * k, (k >= B_Y && k < B_SD) ? 9 : (k == B_KD || k == B_TS || k == B_SD) ? 8 : (k == B_TD || k == B_U) ? 4 : k == B_XS + 1 ? 2 : k == B_DP ? 5 : 1);
#pragma unroll
                for (int k = B_S; k < B_XS; k++) mbar_expect(bars + 8 * k, 16384);
                asm volatile("fence.proxy.async.shared::cta;" ::: "memory");
                asm volatile("fence.mbarrier_init.release.cluster;" ::: "memory");
            }
            __syncwarp();
            asm volatile("barrier.cluster.arrive.relaxed.aligned;" ::: "memory");
            auto rows = [&](int i) {
                mbar_expect(bars + 8 * (B_X + i), 8192);
                tma4d(sb + OFF_XROW + i * 8192, &tm_r, 0, 0, 8 * i + 4 * h, pr, bars + 8 * (B_X + i));
            };
            if (lane == 0) {
                asm volatile("prefetch.tensormap [%0];" :: "l"(&tm_x) : "memory");
                rows(0);
            }
            __syncwarp();
            bar_arrive(7, 160);
            asm volatile("barrier.cluster.wait.acquire.aligned;" ::: "memory");
            if (lane == 0) {
                TSTAMP(20);
#pragma unroll 1
                for (int i = 0; i < 4; i++) {
                    tma5d_both(sb + OFF_S + (4 * h + i) * 8192, &tm_x, 16 * pr, 32 * i + 16 * h, bars + 8 * (B_S + i));
                    if (i < 3) rows(i + 1);
                }
                TSTAMP(24);
                asm volatile("prefetch.tensormap [%0];" :: "l"(&tm_gu) : "memory");
                asm volatile("prefetch.tensormap [%0];" :: "l"(&tm_down) : "memory");
                asm volatile("prefetch.tensormap [%0];" :: "l"(&tm_o) : "memory");
#pragma unroll
                for (int k = 0; k < B_S; k++) mbar_init(bars + 8 * k, k < B_EMPTY ? 1 : 4);
#pragma unroll
                for (int k = 0; k < B_EMPTY; k++) mbar_expect(bars + 8 * k, 8192);
#pragma unroll
                for (int k = B_XS; k < B_SD; k++) if (k != B_TD && k != B_G) mbar_expect(bars + 8 * k, k < B_TD ? (c < NGU_CTA ? 8192 : 0) : k == B_SC ? 64 : k == B_DP ? 2048 : k == B_NONE ? 0 : 4096);
                asm volatile("fence.proxy.async.shared::cta;" ::: "memory");
            }
            __syncwarp();
        }
        bar_arrive(4, 256);
        bar_sync(6, 128);
        if (pw == 15) {
            const unsigned tag = (ld_epoch(p.ex) + 1) & 0xffffu;
            const int tok = lane & 7;
            uint32_t top = 0;
            bool ok = false;
            mbar_wait(bars + 8 * B_XF);
#pragma unroll 1
            for (int it = 0; it < (1 << 22); it++) {
                uint32_t tg;
                asm volatile("ld.relaxed.gpu.global.v2.u32 {%0,%1}, [%2];" : "=r"(top), "=r"(tg) : "l"(&p.ex->top[tok]) : "memory");
                ok = __all_sync(0xffffffffu, tg == tag);
                if (ok) break;
            }
            if (!ok) __trap();
            if (lane == 0) TSTAMP(25);
            const int row = 2047 - (int)(top & 0xffffu);
            if (c < NGU_CTA) {
#pragma unroll
                for (int k = 0; k < 8; k++) {
                    const int tk = 4 * h + ((k + pr) & 3), hf = k >> 2;
                    bulk_load_both(sb + OFF_XSEL + tk * XS_ROW + 1024 * hf, p.u + (size_t)__shfl_sync(0xffffffffu, row, tk) * D_ + 512 * hf, 1024, bars + 8 * (B_XS + hf));
                }
            }
            if (lane == 0) TSTAMP(21);
            if (lane < 8) {
                const uint32_t ord = top >> 16;
                sts32(sb + M_RSEL + tok * 4, ((ord & 0x8000u) ? (ord & 0x7fffu) : (~ord & 0xffffu)) << 16);
                sts32(sb + M_IDX + tok * 4, (uint32_t)row);
                if (((row >> 8) & 1) == h) asm volatile("red.shared.or.b32 [%0], %1;" :: "r"(sb + M_BMAP + ((row >> 7) & 1) * 64 + (row & 6) * 8 + ((row >> 4) & 3) * 4),
                                                   "r"(1u << (4 * (row >> 9) + ((row >> 5) & 2) + (row & 1) + 2 * (row & 8))) : "memory");
            }
            __syncwarp();
            if (lane == 0) { mbar_arrive(bars + 8 * (B_XS + 1)); TSDUMP(0x02200000u); }
            mbar_wait_n<2, 8>(bars + 8 * (B_XS + 1));
            if (lane == 0) bulk_load(sb + OFF_GP, &p.ex->g[256 * h], 4096, bars + 8 * B_GL);
            __syncwarp();
            mbar_wait(bars + 8 * B_GL);
#pragma unroll 2
            for (int i = lane; i < 256; i += 32) {
                uint4 a = lds128(sb + OFF_GP + i * 16);
#pragma unroll 1
                for (int it = 0; (((a.x ^ (tag << 16)) | (a.y ^ (tag << 16)) | (a.z ^ (tag << 16)) | (a.w ^ (tag << 16))) >> 16) != 0; it++) {
                    if (it > (1 << 22)) __trap();
                    a = ld_gpu128(&p.ex->g[256 * h + i]);
                }
                auto both = [](uint32_t w) { return (w & 0xffffu) | (pack_bf(1.f - bf_lo(w), 0.f) << 16); };
                sts128(sb + OFF_GP + i * 16, both(a.x), both(a.y), both(a.z), both(a.w));
            }
            __syncwarp();
            if (lane == 0) { TSTAMP(30); TSDUMP(1u << 30); }
            if (lane == 0) mbar_arrive(bars + 8 * B_G);
            return;
        }
        const int s0 = c < NGU_CTA ? 0 : NST_GU, s = lane, dn = s >= NST_GU;
        const int slot = s < NSLOT ? s : s < 2 * NSLOT ? s - NSLOT : s - 2 * NSLOT, depth = dn ? DEPTH_D : DEPTH_G;
        const uint32_t dst = sb + OFF_RING + slot * 8192 + (slot >= ALT_SLOT ? (h ? ALT1 : ALT0) + A_SLOT - ALT_SLOT * 8192 : 0);
        const uint32_t due = (t_start + T_W + h * (DT_G / 2) + DT_G * s + (dn ? (DT_D - DT_G) * (s - NST_GU) : 0)) & ~63u;
        const uint32_t w_slot = bars + 8 * (s >= s0 + NSLOT ? B_EMPTY + s - NSLOT : slot >= ALT_SLOT ? B_U : s >= X_SLOT ? B_XF : B_NONE);
        const uint32_t w_depth = bars + 8 * (s >= s0 + depth ? B_FULL + s - depth : B_NONE);
        const CUtensorMap* tm = dn ? &tm_down : &tm_gu;
        const int cx = dn ? 16 * pr : 32 * c, cy = dn ? 1792 * h + 256 * (s - NST_GU) : 64 * s;
#pragma unroll 1
        for (int k = s0 + pw - 12; k < NST; k += 3) {
            if (lane == k) {
#pragma unroll 1
                for (int n = 0; n < 1000; n++) {
                    const uint32_t now = now_ns();
                    if ((int)(due - now) <= 0) break;
                    __nanosleep(min((now ^ due) >> 1, 1023u));
                }
                mbar_wait2(w_slot, w_depth);
                tma3d(dst, tm, cx, cy, 0, bars + 8 * (B_FULL + s));
            }
            __syncwarp();
        }
    }
}

typedef CUresult (*EncodeFn)(CUtensorMap*, CUtensorMapDataType, cuuint32_t, void*, const cuuint64_t*, const cuuint64_t*,
                             const cuuint32_t*, const cuuint32_t*, CUtensorMapInterleave, CUtensorMapSwizzle,
                             CUtensorMapL2promotion, CUtensorMapFloatOOBfill);

void make_map(EncodeFn f, CUtensorMap* m, const void* ptr, int rank, const cuuint64_t* dims, const cuuint64_t* strides, const cuuint32_t* box, CUtensorMapSwizzle sw) {
    const cuuint32_t es[5] = {1, 1, 1, 1, 1};
    f(m, CU_TENSOR_MAP_DATA_TYPE_BFLOAT16, rank, (void*)ptr, dims, strides, box, es, CU_TENSOR_MAP_INTERLEAVE_NONE, sw,
      CU_TENSOR_MAP_L2_PROMOTION_L2_128B, CU_TENSOR_MAP_FLOAT_OOB_FILL_NONE);
}

}

extern "C" void kernel_launch(void* const* d_in, const int* in_sizes, int n_in, void* d_out, int out_size) {
    static EncodeFn enc = nullptr;
    static void* ex = nullptr;
    if (!enc) {
        void* fn = nullptr;
        cudaDriverEntryPointQueryResult qr;
        cudaGetDriverEntryPoint("cuTensorMapEncodeTiled", &fn, cudaEnableDefault, &qr);
        enc = (EncodeFn)fn;
        cudaFuncSetAttribute(fused_kernel, cudaFuncAttributeMaxDynamicSharedMemorySize, SMEM_BYTES);
        cudaGetSymbolAddress(&ex, g_ex);
    }
    CUtensorMap tgu, td, tx, tr, to;
    const char *wg = (const char*)d_in[9], *wu = (const char*)d_in[10];
    const bool swap = wu < wg;
    {
        const cuuint64_t dims[3] = {F_, D_, 2}, str[2] = {F_ * 2, (cuuint64_t)(swap ? wg - wu : wu - wg)};
        const cuuint32_t box[3] = {32, 64, 2};
        make_map(enc, &tgu, swap ? wu : wg, 3, dims, str, box, CU_TENSOR_MAP_SWIZZLE_64B);
    }
    {
        const cuuint64_t dims[3] = {D_, F_, 1}, str[2] = {D_ * 2, (cuuint64_t)D_ * 2 * F_};
        const cuuint32_t box[3] = {16, 256, 1};
        make_map(enc, &td, d_in[11], 3, dims, str, box, CU_TENSOR_MAP_SWIZZLE_32B);
    }
    {
        const cuuint64_t dims[5] = {D_, 2, 2, L_ / 16, 4}, str[4] = {D_ * 2 * 8, D_ * 2, D_ * 2 * 16, D_ * 2 * 2};
        const cuuint32_t box[5] = {16, 2, 2, 16, 4}, obox[5] = {16, 2, 2, 8, 1};
        make_map(enc, &tx, d_in[0], 5, dims, str, box, CU_TENSOR_MAP_SWIZZLE_32B);
        make_map(enc, &to, d_out, 5, dims, str, obox, CU_TENSOR_MAP_SWIZZLE_32B);
    }
    {
        const cuuint64_t dims[4] = {256, 4, L_ / 64, 64}, str[3] = {512, D_ * 2 * 64, D_ * 2};
        const cuuint32_t box[4] = {256, 4, 4, 1};
        make_map(enc, &tr, d_in[0], 4, dims, str, box, CU_TENSOR_MAP_SWIZZLE_NONE);
    }
    Params p;
    p.u = (const bf16*)d_in[0]; p.logA = (const bf16*)d_in[1]; p.Aim = (const bf16*)d_in[2];
    p.Cre = (const bf16*)d_in[3]; p.Cim = (const bf16*)d_in[4]; p.logdt = (const bf16*)d_in[5];
    p.Dskip = (const bf16*)d_in[6]; p.wr = (const bf16*)d_in[8]; p.gatew = (const bf16*)d_in[12];
    p.out = (bf16*)d_out;
    p.ex = (Exchange*)ex;
    p.zero = 0;
    p.swap_gu = swap ? 4096 : 0;
    fused_kernel<<<NCTA, NTHREADS, SMEM_BYTES>>>(p, tgu, td, tx, tr, to);
}
```

```cpp
#include <cuda_runtime.h>
#include <cuda_bf16.h>
#include <cuda_fp16.h>
#include <cuda.h>
#include <stdint.h>

typedef __nv_bfloat16 bf16;

namespace {

constexpr int L_ = 2048, D_ = 1024, F_ = 3584;
constexpr int NCTA = 130;
constexpr int NTHREADS = 512;
constexpr int MAIN_W0 = 4;
#define T_W 1600
#define DT_G 316
#define DT_D 344
#define DEPTH_G 5
#define DEPTH_D 3
#define H_WAIT 2
#define DN_PRE 5
#define PSLEEP 0
#define GU_BATCH 0
#define FENCES 16
#define MIX0_AT 2
#define MIX1_AT 4
#define SEND_FENCE 1
#define DUP_MOV 2
#define KD_AT 7
#define KD_ORDER 0
#define A_REUSE 0
#define MAIN_REGS "176"
#define HELP_REGS "32"
constexpr int GU_PRE = 6;
constexpr int NGU_CTA = 112;

constexpr int NSLOT    = 10;
constexpr int NST_GU   = 16, NST = 23;
constexpr int OFF_RING = 0;
constexpr int OFF_XROW = 53248, X_SLOT = 6;
constexpr int OFF_XSEL = 69632, XS_ROW = 2064;
constexpr int OFF_DP   = OFF_XSEL + 8192;
constexpr int OFF_S    = 87040;
constexpr int ALT0     = OFF_S + 32768, ALT1 = OFF_S - 512;
constexpr int A_YIN    = 32, Y_CH = 2064;
constexpr int A_SLOT   = 16896, ALT_SLOT = 8;
constexpr int U_PL     = 1184;
constexpr int U_CH     = 4752;
constexpr int OFF_U    = 153088;
constexpr int T_CH     = 4112;
constexpr int OFF_TAB  = 191104;
constexpr int T_R2     = 2176, T2_S = 208;
constexpr int T_R3     = 3040, T3_S = 336;
constexpr int OFF_GP   = 224000;
constexpr int OFF_BAND = 228096;
constexpr int OFF_MISC = 229376;
constexpr int M_BARS   = OFF_MISC;
constexpr int M_IDX    = OFF_MISC + 704;
constexpr int M_RSEL   = OFF_MISC + 736;
constexpr int M_BMAP   = OFF_MISC + 768;
constexpr int M_MX     = OFF_MISC + 896;
constexpr int M_SC     = OFF_MISC + 960;
constexpr int M_RG     = OFF_MISC + 1024;
constexpr int SMEM_BYTES = OFF_MISC + 3072;

constexpr int B_FULL = 0, B_EMPTY = NST, B_S = B_EMPTY + NST - NSLOT, B_XS = B_S + 4, B_TD = B_XS + 2, B_SC = B_TD + 1, B_G = B_SC + 1, B_GL = B_G + 1, B_NONE = B_GL + 1, B_DP = B_NONE + 1, B_Y = B_DP + 1,
              B_SD = B_Y + 4, B_KD = B_SD + 1, B_U = B_KD + 1, B_TS = B_U + 1, B_XF = B_TS + 1, B_X = B_XF + 1, NBAR = B_X + 4;
static_assert(NBAR <= 84, "barrier area");

struct Exchange {
    unsigned epoch, pad[31];
    uint4 h[8 * F_ / 8];
    uint4 r[L_ / 4];
    uint4 g[L_ / 4];
    uint2 top[16];
};
__device__ __align__(128) Exchange g_ex;

struct Params {
    const bf16 *logA, *Aim, *Cre, *Cim, *logdt, *Dskip, *u, *wr, *gatew;
    bf16* out;
    Exchange* ex;
    uint32_t zero;
    uint32_t swap_gu;
};

#define TSTAMP(i) do {} while (0)
#define CSTAMP(i) do {} while (0)
#define TSDUMP(mask) do {} while (0)
#define DBG_PARAMS
#define DBG_ARGS

__device__ __forceinline__ uint32_t smem_u32(const void* p) { return (uint32_t)__cvta_generic_to_shared(p); }
__device__ __forceinline__ void mbar_init(uint32_t b, uint32_t c) { asm volatile("mbarrier.init.shared::cta.b64 [%0], %1;" :: "r"(b), "r"(c) : "memory"); }
__device__ __forceinline__ void mbar_expect(uint32_t b, uint32_t tx) { asm volatile("mbarrier.arrive.expect_tx.shared::cta.b64 _, [%0], %1;" :: "r"(b), "r"(tx) : "memory"); }
__device__ __forceinline__ void mbar_arrive(uint32_t b) { asm volatile("mbarrier.arrive.shared::cta.b64 _, [%0];" :: "r"(b) : "memory"); }
#define WSLEEP "40"
__device__ __forceinline__ void mbar_wait(uint32_t b) {
    asm volatile("{\n\t.reg .pred p, q;\n\t.reg .u32 n;\n\tmov.u32 n, 0;\n"
                 "W%=:\n\tmbarrier.try_wait.parity.shared::cta.b64 p, [%0], 0;\n\t"
                 "@p bra D%=;\n\tnanosleep.u32 " WSLEEP ";\n\tadd.u32 n, n, 1;\n\tsetp.lt.u32 q, n, 4194304;\n\t@q bra W%=;\n"
                 "D%=:\n\t}" :: "r"(b) : "memory");
}
__device__ __forceinline__ void mbar_spin(uint32_t b) {
    asm volatile("{\n\t.reg .pred p, q;\n\t.reg .u32 n;\n\tmov.u32 n, 0;\n"
                 "W%=:\n\tmbarrier.try_wait.parity.shared::cta.b64 p, [%0], 0;\n\t"
                 "@p bra D%=;\n\tadd.u32 n, n, 1;\n\tsetp.lt.u32 q, n, 4194304;\n\t@q bra W%=;\n"
                 "D%=:\n\t}" :: "r"(b) : "memory");
}
__device__ __forceinline__ void mbar_wait2(uint32_t a, uint32_t b) {
    asm volatile("{\n\t.reg .pred p, q;\n\t.reg .u32 n;\n\tmov.u32 n, 0;\n"
                 "W%=:\n\tmbarrier.try_wait.parity.shared::cta.b64 p, [%0], 0;\n\tmbarrier.try_wait.parity.shared::cta.b64 q, [%1], 0;\n\tand.pred p, p, q;\n\t"
                 "@p bra D%=;\n\tadd.u32 n, n, 1;\n\tsetp.lt.u32 q, n, 4194304;\n\t@q bra W%=;\n"
                 "D%=:\n\t}" :: "r"(a), "r"(b) : "memory");
}
template <int N, int STEP>
__device__ __forceinline__ void mbar_wait_n(uint32_t b) {
#pragma unroll 1
    for (int n = 0; n < 4194304; n++) {
        uint32_t ok = 1;
#pragma unroll
        for (int i = 0; i < N; i++) {
            uint32_t d;
            asm volatile("{ .reg .pred p; mbarrier.try_wait.parity.shared::cta.b64 p, [%1], 0; selp.u32 %0, 1, 0, p; }" : "=r"(d) : "r"(b + STEP * i) : "memory");
            ok &= d;
        }
        if (ok) break;
    }
}
__device__ __forceinline__ unsigned ld_epoch(const Exchange* e) { unsigned v; asm volatile("ld.volatile.global.u32 %0, [%1];" : "=r"(v) : "l"(e) : "memory"); return v; }
__device__ __forceinline__ uint32_t now_ns() { uint32_t t; asm volatile("mov.u32 %0, %globaltimer_lo;" : "=r"(t)); return t; }
__device__ __forceinline__ uint32_t mapa(uint32_t addr, uint32_t rank) { uint32_t r; asm("mapa.shared::cluster.u32 %0, %1, %2;" : "=r"(r) : "r"(addr), "r"(rank)); return r; }
__device__ __forceinline__ void bulk_load(uint32_t dst, const void* src, uint32_t bytes, uint32_t bar) {
    asm volatile("cp.async.bulk.shared::cluster.global.mbarrier::complete_tx::bytes [%0], [%1], %2, [%3];" :: "r"(dst), "l"(src), "r"(bytes), "r"(bar) : "memory");
}
__device__ __forceinline__ void bulk_load_both(uint32_t dst, const void* src, uint32_t bytes, uint32_t bar) {
    asm volatile("{ .reg .pred p; elect.sync _|p, 0xffffffff;\n\t@p cp.async.bulk.shared::cluster.global.mbarrier::complete_tx::bytes.multicast::cluster [%0], [%1], %2, [%3], %4; }"
                 :: "r"(dst), "l"(src), "r"(bytes), "r"(bar), "h"((unsigned short)3) : "memory");
}
__device__ __forceinline__ void tma3d(uint32_t dst, const CUtensorMap* tm, int c0, int c1, int c2, uint32_t bar) {
    asm volatile("cp.async.bulk.tensor.3d.shared::cluster.global.mbarrier::complete_tx::bytes [%0], [%1, {%3, %4, %5}], [%2];"
        :: "r"(dst), "l"(tm), "r"(bar), "r"(c0), "r"(c1), "r"(c2) : "memory");
}
__device__ __forceinline__ void tma4d_warp(uint32_t dst, const CUtensorMap* tm, int c2, int c3, uint32_t bar) {
    asm volatile("{ .reg .pred p; elect.sync _|p, 0xffffffff;\n\t@p cp.async.bulk.tensor.4d.shared::cluster.global.mbarrier::complete_tx::bytes [%0], [%1, {%5, %5, %3, %4}], [%2]; }"
        :: "r"(dst), "l"(tm), "r"(bar), "r"(c2), "r"(c3), "r"(0) : "memory");
}
__device__ __forceinline__ void tma5d_both(uint32_t dst, const CUtensorMap* tm, int c0, int c3, uint32_t bar) {
    asm volatile("{ .reg .pred p; elect.sync _|p, 0xffffffff;\n\t@p cp.async.bulk.tensor.5d.shared::cluster.global.mbarrier::complete_tx::bytes.multicast::cluster [%0], [%1, {%3, %5, %5, %4, %5}], [%2], %6; }"
        :: "r"(dst), "l"(tm), "r"(bar), "r"(c0), "r"(c3), "r"(0), "h"((unsigned short)3) : "memory");
}
__device__ __forceinline__ void cluster_next() { asm volatile("barrier.cluster.wait.acquire.aligned;\n\tbarrier.cluster.arrive.relaxed.aligned;" ::: "memory"); }
__device__ __forceinline__ void st_async16(uint32_t dst, uint32_t x, uint32_t y, uint32_t z, uint32_t w, uint32_t bar) {
    asm volatile("st.async.weak.shared::cluster.mbarrier::complete_tx::bytes.v4.b32 [%0], {%1,%2,%3,%4}, [%5];"
                 :: "r"(dst), "r"(x), "r"(y), "r"(z), "r"(w), "r"(bar) : "memory");
}
__device__ __forceinline__ void st_async4(uint32_t dst, uint32_t v, uint32_t bar) {
    asm volatile("st.async.weak.shared::cluster.mbarrier::complete_tx::bytes.b32 [%0], %1, [%2];" :: "r"(dst), "r"(v), "r"(bar) : "memory");
}
__device__ __forceinline__ void bar_sync(int id, int n) { asm volatile("bar.sync %0, %1;" :: "r"(id), "r"(n) : "memory"); }
__device__ __forceinline__ void bar_arrive(int id, int n) { asm volatile("bar.arrive %0, %1;" :: "r"(id), "r"(n) : "memory"); }
__device__ __forceinline__ void cp16(uint32_t dst, const void* src) { asm volatile("cp.async.cg.shared.global [%0], [%1], 16;" :: "r"(dst), "l"(src) : "memory"); }
__device__ __forceinline__ void cp_wait_all() { asm volatile("cp.async.wait_all;" ::: "memory"); }
__device__ __forceinline__ uint32_t ldg16(const void* p) { uint32_t v; asm volatile("ld.global.nc.u16 %0, [%1];" : "=r"(v) : "l"(p)); return v; }
__device__ __forceinline__ uint2 ldg64(const void* p) { uint2 v; asm volatile("ld.global.nc.v2.u32 {%0,%1}, [%2];" : "=r"(v.x), "=r"(v.y) : "l"(p)); return v; }
__device__ __forceinline__ uint4 ldg128(const void* p) { uint4 v; asm volatile("ld.global.nc.v4.u32 {%0,%1,%2,%3}, [%4];" : "=r"(v.x), "=r"(v.y), "=r"(v.z), "=r"(v.w) : "l"(p)); return v; }
__device__ __forceinline__ uint4 ld_gpu128(const void* p) { uint4 v; asm volatile("ld.relaxed.gpu.global.v4.u32 {%0,%1,%2,%3}, [%4];" : "=r"(v.x), "=r"(v.y), "=r"(v.z), "=r"(v.w) : "l"(p) : "memory"); return v; }
__device__ __forceinline__ void st_gpu32(void* p, uint32_t v) { asm volatile("st.relaxed.gpu.global.u32 [%0], %1;" :: "l"(p), "r"(v) : "memory"); }
__device__ __forceinline__ void st_gpu128(void* p, const uint4& v) { asm volatile("st.relaxed.gpu.global.v4.u32 [%0], {%1,%2,%3,%4};" :: "l"(p), "r"(v.x), "r"(v.y), "r"(v.z), "r"(v.w) : "memory"); }

__device__ __forceinline__ void ldsm4(uint32_t a, uint32_t& r0, uint32_t& r1, uint32_t& r2, uint32_t& r3) {
    asm volatile("ldmatrix.sync.aligned.m8n8.x4.shared.b16 {%0,%1,%2,%3}, [%4];" : "=r"(r0), "=r"(r1), "=r"(r2), "=r"(r3) : "r"(a) : "memory");
}
__device__ __forceinline__ void ldsm2(uint32_t a, uint32_t& r0, uint32_t& r1) {
    asm volatile("ldmatrix.sync.aligned.m8n8.x2.shared.b16 {%0,%1}, [%2];" : "=r"(r0), "=r"(r1) : "r"(a) : "memory");
}
__device__ __forceinline__ void ldsm4t(uint32_t a, uint32_t& r0, uint32_t& r1, uint32_t& r2, uint32_t& r3) {
    asm volatile("ldmatrix.sync.aligned.m8n8.x4.trans.shared.b16 {%0,%1,%2,%3}, [%4];" : "=r"(r0), "=r"(r1), "=r"(r2), "=r"(r3) : "r"(a) : "memory");
}
__device__ __forceinline__ uint32_t lds16(uint32_t a) { uint32_t v; asm volatile("ld.shared.u16 %0, [%1];" : "=r"(v) : "r"(a) : "memory"); return v; }
__device__ __forceinline__ uint32_t lds32(uint32_t a) { uint32_t v; asm volatile("ld.shared.u32 %0, [%1];" : "=r"(v) : "r"(a) : "memory"); return v; }
__device__ __forceinline__ uint2 lds64(uint32_t a) { uint2 v; asm volatile("ld.shared.v2.u32 {%0,%1}, [%2];" : "=r"(v.x), "=r"(v.y) : "r"(a) : "memory"); return v; }
__device__ __forceinline__ uint4 lds128(uint32_t a) { uint4 v; asm volatile("ld.shared.v4.u32 {%0,%1,%2,%3}, [%4];" : "=r"(v.x), "=r"(v.y), "=r"(v.z), "=r"(v.w) : "r"(a) : "memory"); return v; }
__device__ __forceinline__ void sts16(uint32_t a, uint32_t v) { asm volatile("st.shared.u16 [%0], %1;" :: "r"(a), "r"(v) : "memory"); }
__device__ __forceinline__ void sts32(uint32_t a, uint32_t v) { asm volatile("st.shared.u32 [%0], %1;" :: "r"(a), "r"(v) : "memory"); }
__device__ __forceinline__ void sts64(uint32_t a, uint32_t x, uint32_t y) { asm volatile("st.shared.v2.u32 [%0], {%1,%2};" :: "r"(a), "r"(x), "r"(y) : "memory"); }
__device__ __forceinline__ void sts128(uint32_t a, uint32_t x, uint32_t y, uint32_t z, uint32_t w) { asm volatile("st.shared.v4.u32 [%0], {%1,%2,%3,%4};" :: "r"(a), "r"(x), "r"(y), "r"(z), "r"(w) : "memory"); }
__device__ __forceinline__ void sts16_if(bool p, uint32_t a, uint32_t v) { asm volatile("{ .reg .pred q; setp.ne.u32 q, %2, 0; @q st.shared.u16 [%0], %1; }" :: "r"(a), "h"((unsigned short)v), "r"((uint32_t)p) : "memory"); }
__device__ __forceinline__ void sts128_if(bool p, uint32_t a, uint32_t x, uint32_t y, uint32_t z, uint32_t w) {
    asm volatile("{ .reg .pred q; setp.ne.u32 q, %5, 0; @q st.shared.v4.u32 [%0], {%1,%2,%3,%4}; }" :: "r"(a), "r"(x), "r"(y), "r"(z), "r"(w), "r"((uint32_t)p) : "memory");
}
__device__ __forceinline__ void stsf(uint32_t a, float v) { asm volatile("st.shared.f32 [%0], %1;" :: "r"(a), "f"(v) : "memory"); }
__device__ __forceinline__ float ldsf(uint32_t a) { float v; asm volatile("ld.shared.f32 %0, [%1];" : "=f"(v) : "r"(a) : "memory"); return v; }

__device__ __forceinline__ void mma_bf(float (&d)[4], uint32_t a0, uint32_t a1, uint32_t a2, uint32_t a3, uint32_t b0, uint32_t b1) {
    asm volatile("mma.sync.aligned.m16n8k16.row.col.f32.bf16.bf16.f32 {%0,%1,%2,%3}, {%4,%5,%6,%7}, {%8,%9}, {%0,%1,%2,%3};"
        : "+f"(d[0]), "+f"(d[1]), "+f"(d[2]), "+f"(d[3]) : "r"(a0), "r"(a1), "r"(a2), "r"(a3), "r"(b0), "r"(b1));
}
__device__ __forceinline__ void widen_bf(float (&d)[4], uint32_t a0, uint32_t a1, uint32_t b) {
    asm volatile("mma.sync.aligned.m16n8k8.row.col.f32.bf16.bf16.f32 {%0,%1,%2,%3}, {%4,%5}, {%6}, {%7,%7,%7,%7};"
        : "=f"(d[0]), "=f"(d[1]), "=f"(d[2]), "=f"(d[3]) : "r"(a0), "r"(a1), "r"(b), "f"(0.f));
}
__device__ __forceinline__ void widen_h(float (&d)[4], const uint32_t (&a)[2], uint32_t b) {
    asm volatile("mma.sync.aligned.m16n8k8.row.col.f32.f16.f16.f32 {%0,%1,%2,%3}, {%4,%5}, {%6}, {%7,%7,%7,%7};"
        : "=f"(d[0]), "=f"(d[1]), "=f"(d[2]), "=f"(d[3]) : "r"(a[0]), "r"(a[1]), "r"(b), "f"(0.f));
}
__device__ __forceinline__ void widen_add_h(float (&d)[4], const uint32_t (&a)[2], uint32_t b, const float (&c)[4]) {
    asm volatile("mma.sync.aligned.m16n8k8.row.col.f32.f16.f16.f32 {%0,%1,%2,%3}, {%4,%5}, {%6}, {%7,%8,%9,%10};"
        : "=f"(d[0]), "=f"(d[1]), "=f"(d[2]), "=f"(d[3]) : "r"(a[0]), "r"(a[1]), "r"(b), "f"(c[0]), "f"(c[1]), "f"(c[2]), "f"(c[3]));
}
__device__ __forceinline__ void mma_h(uint32_t (&d)[2], const uint32_t (&a)[4], uint32_t b0, uint32_t b1) {
    asm volatile("mma.sync.aligned.m16n8k16.row.col.f16.f16.f16.f16 {%0,%1}, {%2,%3,%4,%5}, {%6,%7}, {%0,%1};"
        : "+r"(d[0]), "+r"(d[1]) : "r"(a[0]), "r"(a[1]), "r"(a[2]), "r"(a[3]), "r"(b0), "r"(b1));
}
__device__ __forceinline__ void mma_h_z(uint32_t& d0, uint32_t& d1, const uint32_t (&a)[4], uint32_t b0, uint32_t b1) {
    asm volatile("mma.sync.aligned.m16n8k16.row.col.f16.f16.f16.f16 {%0,%1}, {%2,%3,%4,%5}, {%6,%7}, {%8,%8};"
        : "=r"(d0), "=r"(d1) : "r"(a[0]), "r"(a[1]), "r"(a[2]), "r"(a[3]), "r"(b0), "r"(b1), "r"(0u));
}
__device__ __forceinline__ void mma_h2(uint32_t& d0, uint32_t& d1, const uint32_t (&a)[4], uint32_t b0, uint32_t b1) {
    asm volatile("mma.sync.aligned.m16n8k16.row.col.f16.f16.f16.f16 {%0,%1}, {%2,%3,%4,%5}, {%6,%7}, {%0,%1};"
        : "+r"(d0), "+r"(d1) : "r"(a[0]), "r"(a[1]), "r"(a[2]), "r"(a[3]), "r"(b0), "r"(b1));
}
__device__ __forceinline__ void mma_h_k8(uint32_t& d0, uint32_t& d1, uint32_t a0, uint32_t a1, uint32_t b) {
    asm volatile("mma.sync.aligned.m16n8k8.row.col.f16.f16.f16.f16 {%0,%1}, {%2,%3}, {%4}, {%0,%1};" : "+r"(d0), "+r"(d1) : "r"(a0), "r"(a1), "r"(b));
}
__device__ __forceinline__ void mma_h_k8_z(uint32_t (&d)[2], uint32_t a0, uint32_t a1, uint32_t b) {
    asm volatile("mma.sync.aligned.m16n8k8.row.col.f16.f16.f16.f16 {%0,%1}, {%2,%3}, {%4}, {%5,%5};" : "=r"(d[0]), "=r"(d[1]) : "r"(a0), "r"(a1), "r"(b), "r"(0u));
}
__device__ __forceinline__ uint32_t pack_bf(float lo, float hi) { uint32_t r; asm("cvt.rn.bf16x2.f32 %0, %1, %2;" : "=r"(r) : "f"(hi), "f"(lo)); return r; }
__device__ __forceinline__ uint32_t pack_h(float lo, float hi) { uint32_t r; asm("cvt.rn.f16x2.f32 %0, %1, %2;" : "=r"(r) : "f"(hi), "f"(lo)); return r; }
__device__ __forceinline__ float bf_lo(uint32_t v) { return __uint_as_float(v << 16); }
__device__ __forceinline__ float bf_hi(uint32_t v) { return __uint_as_float(v & 0xffff0000u); }
__device__ __forceinline__ float bf_round(float x) { return __uint_as_float(pack_bf(0.f, x) & 0xffff0000u); }
__device__ __forceinline__ uint32_t hmul2_bf(uint32_t a, uint32_t b) { uint32_t r; asm("mul.rn.bf16x2 %0, %1, %2;" : "=r"(r) : "r"(a), "r"(b)); return r; }
__device__ __forceinline__ uint32_t hadd2_bf(uint32_t a, uint32_t b) { uint32_t r; asm("add.rn.bf16x2 %0, %1, %2;" : "=r"(r) : "r"(a), "r"(b)); return r; }
__device__ __forceinline__ uint32_t hfma2_bf(uint32_t a, uint32_t b, uint32_t c) { uint32_t r; asm("fma.rn.bf16x2 %0, %1, %2, %3;" : "=r"(r) : "r"(a), "r"(b), "r"(c)); return r; }
__device__ __forceinline__ uint32_t hi_mul_bf(uint32_t a, uint32_t b) { uint32_t r; asm("{ .reg .b16 l, h; .reg .b32 t; mov.b32 {l, h}, %1; mov.b32 t, {h, h}; mul.rn.bf16x2 %0, t, %2; }" : "=r"(r) : "r"(a), "r"(b)); return r; }
__device__ __forceinline__ uint32_t lo_fma_bf(uint32_t a, uint32_t b, uint32_t c) { uint32_t r; asm("{ .reg .b16 l, h; .reg .b32 t; mov.b32 {l, h}, %1; mov.b32 t, {l, l}; fma.rn.bf16x2 %0, t, %2, %3; }" : "=r"(r) : "r"(a), "r"(b), "r"(c)); return r; }
__device__ __forceinline__ uint32_t amax2_bf(uint32_t m, uint32_t v) { uint32_t r; asm("max.xorsign.abs.bf16x2 %0, %1, %2;" : "=r"(r) : "r"(m), "r"(v)); return r; }
__device__ __forceinline__ uint32_t amax2_h(uint32_t m, uint32_t v) { uint32_t r; asm("max.xorsign.abs.f16x2 %0, %1, %2;" : "=r"(r) : "r"(m), "r"(v)); return r; }
__device__ __forceinline__ uint32_t hadd(uint32_t a, uint32_t b) { uint32_t r; asm("add.rn.f16x2 %0, %1, %2;" : "=r"(r) : "r"(a), "r"(b)); return r; }
__device__ __forceinline__ uint32_t hsub(uint32_t a, uint32_t b) { uint32_t r; asm("sub.rn.f16x2 %0, %1, %2;" : "=r"(r) : "r"(a), "r"(b)); return r; }
__device__ __forceinline__ uint32_t hsub2(uint32_t a, uint32_t b) { uint32_t r; asm("sub.rn.ftz.f16x2 %0, %1, %2;" : "=r"(r) : "r"(a), "r"(b)); return r; }
__device__ __forceinline__ uint32_t hmul(uint32_t a, uint32_t b) { uint32_t r; asm("mul.rn.f16x2 %0, %1, %2;" : "=r"(r) : "r"(a), "r"(b)); return r; }
__device__ __forceinline__ uint32_t hfma(uint32_t a, uint32_t b, uint32_t c) { uint32_t r; asm("fma.rn.f16x2 %0, %1, %2, %3;" : "=r"(r) : "r"(a), "r"(b), "r"(c)); return r; }
__device__ __forceinline__ uint32_t hfms(uint32_t a, uint32_t b, uint32_t c) { uint32_t r; asm("{ .reg .b32 t; neg.f16x2 t, %3; fma.rn.f16x2 %0, %1, %2, t; }" : "=r"(r) : "r"(a), "r"(b), "r"(c)); return r; }
__device__ __forceinline__ uint32_t warp_max16(uint32_t m) { return __reduce_max_sync(0xffffffffu, max(m & 0x7fffu, (m >> 16) & 0x7fffu)); }
__device__ __forceinline__ float ex2f(float x) { float r; asm("ex2.approx.ftz.f32 %0, %1;" : "=f"(r) : "f"(x)); return r; }

__device__ __forceinline__ float exp_acc(float x) {
    const float t = x * 1.4426950216293335f;
    const float r = fmaf(x, 1.4426950216293335f, -t) + x * 1.9259629911266175e-8f;
    return ex2f(t) * fmaf(r, 0.6931471805599453f, 1.f);
}
__device__ __forceinline__ float sigmoid_f(float x) { return __fdividef(1.f, 1.f + ex2f(-x * 1.4426950408889634f)); }
__device__ __forceinline__ void cexp(float l2, float th, float& zr, float& zi) {
    const float mag = ex2f(l2);
    const float k = (th * 0.15915494309189535f + 12582912.f) - 12582912.f;
    float r = fmaf(-k, 6.2831854820251465f, th);
    r = fmaf(-k, -1.7484555314695172e-7f, r);
    zr = mag * __cosf(r);
    zi = mag * __sinf(r);
}
struct hc { uint32_t re, im; };
__device__ __forceinline__ hc cmul(const hc& a, const hc& b) { return {hfms(a.re, b.re, hmul(a.im, b.im)), hfma(a.re, b.im, hmul(a.im, b.re))}; }
__device__ __forceinline__ hc cmulc(const hc& a, const hc& b) { return {hfma(a.re, b.re, hmul(a.im, b.im)), hfms(a.im, b.re, hmul(a.re, b.im))}; }
struct fc2 { float r[2], i[2]; };
__device__ __forceinline__ void csq(fc2& z) {
#pragma unroll
    for (int m = 0; m < 2; m++) {
        const float r = fmaf(z.r[m], z.r[m], -(z.i[m] * z.i[m]));
        asm("{ .reg .f32 t; mul.f32 t, %0, %1; mul.f32 %0, t, 0f40000000; }" : "+f"(z.i[m]) : "f"(z.r[m]));
        z.r[m] = r;
    }
}
__device__ __forceinline__ hc pk(const fc2& z) { return {pack_h(z.r[0], z.r[1]), pack_h(z.i[0], z.i[1])}; }
__device__ __forceinline__ void csq_conj(fc2& z) {
#pragma unroll
    for (int m = 0; m < 2; m++) {
        const float r = fmaf(z.r[m], z.r[m], -(z.i[m] * z.i[m]));
        asm("{ .reg .f32 t, n; neg.f32 n, %1; mul.f32 t, %0, n; mul.f32 %0, t, 0f40000000; }" : "+f"(z.i[m]) : "f"(z.r[m]));
        z.r[m] = r;
    }
}

struct Powers { hc C, z1, z2, z4, c8, c16, c32, c64, z128, z256, z512, z1024; };
__device__ __forceinline__ void kg_powers(Powers& q, uint32_t la, uint32_t ai, uint32_t cr, uint32_t ci, float dt, float cf) {
    fc2 z, y;
    const float dtl = -dt * 1.4426950408889634f;
    const uint32_t eb = pack_bf(ex2f(bf_lo(la) * 1.4426950408889634f), ex2f(bf_hi(la) * 1.4426950408889634f));
    const float l2[2] = {bf_lo(eb) * dtl, bf_hi(eb) * dtl}, th[2] = {bf_lo(ai) * dt, bf_hi(ai) * dt};
#pragma unroll
    for (int m = 0; m < 2; m++) { cexp(l2[m], th[m], z.r[m], z.i[m]); cexp(l2[m] * 128.f, th[m] * 128.f, y.r[m], y.i[m]); }
    q.C.re = pack_h(bf_lo(cr) * cf, bf_hi(cr) * cf);
    q.C.im = pack_h(bf_lo(ci) * cf, bf_hi(ci) * cf);
    q.z1 = pk(z); csq(z); q.z128 = pk(y); csq(y);
    q.z2 = pk(z); csq(z); q.z256 = pk(y); csq(y);
    q.z4 = pk(z); csq_conj(z); q.z512 = pk(y); csq(y);
    q.c8 = pk(z); csq(z); q.z1024 = pk(y);
    q.c16 = pk(z); csq(z);
    q.c32 = pk(z); csq(z);
    q.c64 = pk(z);
}
struct Rows { hc ta[8], tb[8], tc[8], pp[8]; };
#define PUT(a0, a1, row, a, b) sts128((((row) & 1) ? (a1) : (a0)) + (row) * 512, (a).re, (a).im, (b).re, (b).im)
template <bool FIRST>
__device__ __forceinline__ void kg_rows(Rows& w, const Powers& q, uint32_t t0, uint32_t t1, uint32_t u0, uint32_t u1, uint32_t uc, uint32_t zr, uint32_t (&Rl)[2]) {
    w.ta[0] = q.C; w.ta[1] = cmul(q.C, q.z1); w.ta[2] = cmul(q.C, q.z2); w.ta[4] = cmul(q.C, q.z4); w.tb[0] = cmul(q.C, q.z256); w.tb[4] = cmul(q.C, q.z512);
    PUT(t0, t1, 0, w.ta[0], w.tb[0]); PUT(t0, t1, 4, w.ta[4], w.tb[4]);
    w.tb[1] = cmul(w.ta[2], q.z256); w.tb[2] = cmul(w.ta[4], q.z256);
    PUT(t0, t1, 1, w.ta[1], w.tb[1]); PUT(t0, t1, 2, w.ta[2], w.tb[2]);
    w.ta[3] = cmul(w.ta[1], q.z2); w.ta[6] = cmul(w.ta[2], q.z4); w.ta[5] = cmul(w.ta[1], q.z4); w.tb[5] = cmul(w.ta[4], q.z512); w.tb[6] = cmul(w.tb[0], q.z512);
    PUT(t0, t1, 5, w.ta[5], w.tb[5]); PUT(t0, t1, 6, w.ta[6], w.tb[6]);
    w.tb[3] = cmul(w.ta[6], q.z256); w.ta[7] = cmul(w.ta[3], q.z4); w.tb[7] = cmul(w.tb[2], q.z512);
    PUT(t0, t1, 3, w.ta[3], w.tb[3]); PUT(t0, t1, 7, w.ta[7], w.tb[7]);
    sts64(uc, q.c64.re, q.c64.im);
    w.pp[0] = hc{0x3C003C00u ^ zr, zr}; w.pp[1] = q.c8; w.pp[2] = q.c16; w.pp[4] = q.c32;
    w.tc[0] = cmul(q.C, q.z1024); w.pp[3] = cmul(q.c8, q.c16); w.pp[5] = cmul(q.c8, q.c32); w.pp[6] = cmul(q.c16, q.c32);
    w.tc[2] = cmul(w.tc[0], q.z128); w.tc[4] = cmul(w.tc[0], q.z256); w.tc[1] = cmul(w.tc[0], q.z512); w.pp[7] = cmul(w.pp[3], q.c32);
    PUT(u0, u1, 0, w.tc[0], w.pp[0]); PUT(u0, u1, 1, w.tc[1], w.pp[1]); PUT(u0, u1, 2, w.tc[2], w.pp[2]); PUT(u0, u1, 4, w.tc[4], w.pp[4]);
    w.tc[6] = cmul(w.tc[2], q.z256); w.tc[3] = cmul(w.tc[2], q.z512); w.tc[5] = cmul(w.tc[4], q.z512);
    PUT(u0, u1, 3, w.tc[3], w.pp[3]); PUT(u0, u1, 5, w.tc[5], w.pp[5]); PUT(u0, u1, 6, w.tc[6], w.pp[6]);
    w.tc[7] = cmul(w.tc[6], q.z512);
    PUT(u0, u1, 7, w.tc[7], w.pp[7]);
    const uint32_t last = hfms(w.tc[0].re, q.z1024.re, hmul(w.tc[0].im, q.z1024.im));
    if (FIRST) mma_h_k8_z(Rl, 0x3C003C00u - zr, 0x3C003C00u + zr, last); else mma_h_k8(Rl[0], Rl[1], 0x3C003C00u - zr, 0x3C003C00u + zr, last);
}
#undef PUT
template <bool FIRST>
__device__ __forceinline__ void kg_products(uint32_t rt0, uint32_t rt1, uint32_t ru0, uint32_t ru1, uint32_t rc, uint32_t zr, uint32_t done, int lane,
                                            uint32_t (&Ra)[2][2], uint32_t (&Rb)[2][2], uint32_t (&Rc)[2]) {
    uint4 q1[8], q2[8], cw[8];
    if (!FIRST && KD_ORDER) {
#pragma unroll
        for (int ks = 0; ks < 8; ks++) { q2[ks] = lds128(((ks & 1) ? ru1 : ru0) + (ks >> 1) * 128); if (!(ks & 1)) cw[ks] = lds128(rc + ks * 32); if (ks < 2) q1[ks] = lds128(ks ? rt1 : rt0); }
#pragma unroll
        for (int ks = 2; ks < 8; ks++) q1[ks] = lds128(((ks & 1) ? rt1 : rt0) + (ks >> 1) * 128);
    } else
#pragma unroll
    for (int ks = 0; ks < 8; ks++) {
        q2[ks] = lds128(((ks & 1) ? ru1 : ru0) + (ks >> 1) * 128); if (!(ks & 1)) cw[ks] = lds128(rc + ks * 32); q1[ks] = lds128(((ks & 1) ? rt1 : rt0) + (ks >> 1) * 128);
    }
#pragma unroll
    for (int ks = 0; ks < 8; ks++) {
        const hc p0 = {q2[ks].z, q2[ks].w}, u = (ks & 1) ? hc{cw[ks & 6].z, cw[ks & 6].w} : hc{cw[ks].x, cw[ks].y};
        const hc p1 = cmul(p0, u), p2 = cmul(p1, u), p3 = cmul(p2, u);

        const uint32_t qa[4] = {p0.re ^ zr, p1.re, p0.im ^ zr, p1.im}, qb[4] = {p2.re, p3.re, p2.im, p3.im};
        if (!FIRST && ks == KD_AT) {
            uint32_t all = zr;
#pragma unroll
            for (int i = KD_AT; i < 8; i++) all &= q2[i].x & cw[i & 6].x;
            __syncwarp();
            if (lane == 0) mbar_arrive(done + all);
        }
        if (FIRST && ks == 0) {
            mma_h_z(Rc[0], Rc[1], qa, q2[ks].x, q2[ks].y); mma_h_z(Ra[0][0], Ra[0][1], qa, q1[ks].x, q1[ks].y); mma_h_z(Rb[0][0], Rb[0][1], qa, q1[ks].z, q1[ks].w);
            mma_h_z(Ra[1][0], Ra[1][1], qb, q1[ks].x, q1[ks].y); mma_h_z(Rb[1][0], Rb[1][1], qb, q1[ks].z, q1[ks].w);
        } else {
            mma_h(Rc, qa, q2[ks].x, q2[ks].y); mma_h(Ra[0], qa, q1[ks].x, q1[ks].y); mma_h(Rb[0], qa, q1[ks].z, q1[ks].w);
            mma_h(Ra[1], qb, q1[ks].x, q1[ks].y); mma_h(Rb[1], qb, q1[ks].z, q1[ks].w);
        }
    }
}
__device__ __forceinline__ void kernel_gen(const uint2& la, const uint2& ai, const uint2& cr, const uint2& ci, float dt, float cf, uint32_t TB, uint32_t UB, uint32_t done,
                                           int lane, uint32_t zr, uint32_t (&Ra)[2][2], uint32_t (&Rb)[2][2], uint32_t (&Rc)[2], uint32_t (&Rl)[2]) {
    const int g = lane >> 2, t = lane & 3;
    const uint32_t w0 = lane << 4, w1 = w0 ^ 64, r0 = g * 512 + (((g & 1) << 6) | (t << 4)), r1 = r0 ^ 64;
    const uint32_t t0 = TB + w0, t1 = TB + w1, u0 = UB + w0, u1 = UB + w1;
    const uint32_t uc = UB + 4096 + (lane >> 3) * 64 + t * 16 + (lane & 4) * 2;
    Powers p0, p1;
    Rows w;
    kg_powers(p0, la.x, ai.x, cr.x, ci.x, dt, cf);
    kg_rows<true>(w, p0, t0, t1, u0, u1, uc, zr, Rl);
    kg_powers(p1, la.y, ai.y, cr.y, ci.y, dt, cf);
    __syncwarp();
    kg_products<true>(TB + r0, TB + r1, UB + r0, UB + r1, UB + 4096 + t * 16, zr, done, lane, Ra, Rb, Rc);
    __syncwarp();
    asm volatile("barrier.cluster.wait.acquire.aligned;" ::: "memory");
    kg_rows<false>(w, p1, t0, t1, u0, u1, uc, zr, Rl);
    __syncwarp();
    kg_products<false>(TB + r0, TB + r1, UB + r0, UB + r1, UB + 4096 + t * 16, zr, done, lane, Ra, Rb, Rc);
    __syncwarp();
}

template <int V> struct IC { static constexpr int value = V; };

#define LANE_VARS \
    int tid_; asm volatile("mov.u32 %0, %%tid.x;" : "=r"(tid_)); \
    [[maybe_unused]] const int lane = tid_ & 31, warp = (tid_ >> 5) - MAIN_W0, g = lane >> 2, t = lane & 3, mi = lane >> 3, r = lane & 7; \
    [[maybe_unused]] const uint32_t TB = sb + OFF_TAB + warp * T_CH, UB = sb + OFF_U + warp * U_CH; \
    [[maybe_unused]] const bool lead = (tid_ == 32 * MAIN_W0)

__device__ __forceinline__ void dense_step(uint32_t (&M)[8][2], uint32_t (&Ye)[8][2], uint32_t (&Yo)[8][2], uint32_t (&X)[8][2],
                                           uint32_t (&F)[8][2], uint32_t (&Bq)[2][4], uint32_t ua, uint32_t ta, uint32_t zr) {
    uint32_t E[8][2], A[2][4], S[2][4], G[8][2];
#pragma unroll
    for (int jp = 0; jp < 4; jp++) ldsm4(ua + jp * 256, E[2 * jp][0], E[2 * jp][1], E[2 * jp + 1][0], E[2 * jp + 1][1]);
#pragma unroll
    for (int h = 0; h < 2; h++) { A[h][0] = A_REUSE ? Bq[h][3] ^ zr : lds32(ta + 1024 * h); A[h][1] = lds32(ta + 1024 * h + 32); A[h][3] = lds32(ta + 1024 * h + 64); A[h][2] = A[h][1] ^ zr; }
#pragma unroll
    for (int J = 0; J < 8; J++) mma_h(Ye[J], Bq[0], F[J][0], F[J][1]);
#pragma unroll
    for (int J = 1; J < 8; J++) mma_h(Ye[J], Bq[1], F[J - 1][0], F[J - 1][1]);
#pragma unroll
    for (int J = 0; J < 8; J++) { G[J][0] = hsub(X[J][0], E[J][0]); G[J][1] = hsub(X[J][1], E[J][1]); }
#pragma unroll
    for (int jp = 0; jp < 4; jp++) ldsm4(ua + 2 * U_PL + jp * 256 - 16, X[2 * jp][0], X[2 * jp][1], X[2 * jp + 1][0], X[2 * jp + 1][1]);
#pragma unroll
    for (int h = 0; h < 2; h++) { Bq[h][1] = lds32(ta + 1024 * h + 96); Bq[h][3] = lds32(ta + 1024 * h + 128); Bq[h][0] = A[h][3] ^ zr; Bq[h][2] = Bq[h][1] ^ zr; }
#pragma unroll
    for (int J = 0; J < 8; J++) mma_h(Yo[J], A[0], G[J][0], G[J][1]);
#pragma unroll
    for (int J = 1; J < 8; J++) mma_h(Yo[J], A[1], G[J - 1][0], G[J - 1][1]);
#pragma unroll
    for (int h = 0; h < 2; h++)
#pragma unroll
        for (int i = 0; i < 4; i++) S[h][i] = hadd(A[h][i], Bq[h][i]);
#pragma unroll
    for (int J = 0; J < 8; J++) mma_h(M[J], S[0], E[J][0], E[J][1]);
#pragma unroll
    for (int J = 1; J < 8; J++) mma_h(M[J], S[1], E[J - 1][0], E[J - 1][1]);
#pragma unroll
    for (int J = 0; J < 8; J++) { F[J][0] = hsub(X[J][0], E[J][0]); F[J][1] = hsub(X[J][1], E[J][1]); }
}

__device__ __forceinline__ int group_tables(uint32_t TB, int lane) {
    const int g = lane >> 2, t = lane & 3;
    const uint4 b4 = lds128(TB + T_R2 + 16 * lane), c4 = lds128(TB + T_R2 + 512 + 16 * lane);
    uint32_t vb[4] = {b4.x, b4.y, b4.z, b4.w}, vc[2] = {c4.x, c4.y};
    const uint32_t k1024 = __shfl_sync(0xffffffffu, vc[0], 0) & 0xffffu;
    uint32_t kl = hadd(c4.z, __byte_perm(c4.z, 0, 0x1032));
    kl = hadd(kl, __shfl_xor_sync(0xffffffffu, kl, 1)); kl = hadd(kl, __shfl_xor_sync(0xffffffffu, kl, 2));
#pragma unroll
    for (int i = 0; i < 3; i++) sts128(TB + T_R2 + 16 * lane + 512 * i, 0, 0, 0, 0);
    if (lane == 2) vb[0] &= 0xffff0000u;
    if (lane == 0) vc[0] &= 0xffff0000u;
    if (lane == 4) vc[0] = hsub(vc[0], k1024);
    __syncwarp();
    if (t >= 2) {
        const uint32_t g1 = TB + T_R2 + T2_S * (g & 3) + 8 * (8 * t - 10 + (g >> 2));
        const uint32_t g0 = TB + T_R2 + T2_S * ((g - 1) & 3) + 8 * (8 * t - 10 + ((g - 1) >> 2)) + 4;
#pragma unroll
        for (int i = 0; i < 4; i++) {
            sts16(g0 + 16 * i, vb[i]); sts16(g0 + 16 * i + 10, vb[i]);
            sts16(g1 + 16 * i, vb[i] >> 16); sts16(g1 + 16 * i + 10, vb[i] >> 16);
        }
    }
    const uint32_t g3 = TB + T_R3 + T3_S * (((g - 1) >> 1) & 1) + 8 * (7 + 4 * t + ((g - 1) >> 2)) + 4 * ((g - 1) & 1);
#pragma unroll
    for (int i = 0; i < 2; i++) {
        sts16(g3 + 16 * i, vc[i]); sts16(g3 + 16 * i + 10, vc[i]);
        sts16(g3 + 16 * i + 128, vc[i] >> 16); sts16(g3 + 16 * i + 138, vc[i] >> 16);
    }
    const uint32_t g4 = (uint32_t)(((uint64_t)(T_R3 + T3_S + 308) << 48 | (uint64_t)(T_R2 + 180) << 32 | (T_R2 + 176) << 16 | (T_R2 + 3 * T2_S + 172)) >> (8 * (lane & 6))) & 0xffffu;
    sts16(TB + g4 + 10 * (lane & 1), (lane & 7) < 6 ? k1024 : kl);
    return (int)c4.w;
}

#define FENCE() do { if (zr) asm volatile("exit;"); } while (0)
struct Chunks { uint32_t c3, c2, c1, c0, cm1, cm2, cm3, cm4, d2, d1, d0, dm1, em2, em3; };
__device__ __forceinline__ void convolve(uint32_t sb, int h, uint32_t zr, int pr, bf16* out, const CUtensorMap* tm_o DBG_PARAMS) {
    const uint32_t bars = sb + M_BARS;
    uint32_t M[8][2], Ye[8][2], Yo[8][2], F[8][2], Bq[2][4];
    {
        LANE_VARS;
        uint32_t X[8][2];
        uint32_t ua = UB + ((mi & 1) ? 0 : U_PL) + (8 + 8 * (mi >> 1) + r) * 16, ta = TB + 4 * (1 + g + 2 * t);
        uint32_t A[3][4], S[2][4];
        __syncwarp();
#pragma unroll
        for (int h2 = 0; h2 < 3; h2++) { A[h2][0] = lds32(ta + 1024 * h2); A[h2][1] = lds32(ta + 1024 * h2 + 32); A[h2][3] = lds32(ta + 1024 * h2 + 64); A[h2][2] = A[h2][1] ^ zr; }
#pragma unroll
        for (int h2 = 0; h2 < 2; h2++) {
            Bq[h2][1] = lds32(ta + 1024 * h2 + 96); Bq[h2][3] = lds32(ta + 1024 * h2 + 128); Bq[h2][0] = A[h2][3] ^ zr; Bq[h2][2] = Bq[h2][1] ^ zr;
#pragma unroll
            for (int i = 0; i < 4; i++) S[h2][i] = hadd(A[h2][i], Bq[h2][i]);
        }
        const uint32_t an = A[0][0] ^ zr, un = UB + (9 + lane) * 16;
        if (lead) TSTAMP(10);
        mbar_spin(bars + 8 * B_U);
        if (lead) { TSTAMP(3); CSTAMP(27); }
        uint32_t E[8][2], N[8], G[8][2];
#pragma unroll
        for (int jp = 0; jp < 4; jp++) ldsm4(ua + jp * 256, E[2 * jp][0], E[2 * jp][1], E[2 * jp + 1][0], E[2 * jp + 1][1]);
#pragma unroll
        for (int jp = 0; jp < 4; jp++) ldsm4(ua + 2 * U_PL + jp * 256, X[2 * jp][0], X[2 * jp][1], X[2 * jp + 1][0], X[2 * jp + 1][1]);
        ldsm4(un, N[0], N[1], N[2], N[3]); ldsm4(un + 512, N[4], N[5], N[6], N[7]);
#pragma unroll
        for (int J = 0; J < 8; J++) mma_h_z(M[J][0], M[J][1], S[0], E[J][0], E[J][1]);
#pragma unroll
        for (int J = 1; J < 8; J++) mma_h(M[J], S[1], E[J - 1][0], E[J - 1][1]);
#pragma unroll
        for (int J = 2; J < 8; J++) mma_h(M[J], A[2], E[J - 2][0], E[J - 2][1]);
        if (FENCES & 32) FENCE();
#pragma unroll
        for (int J = 0; J < 8; J++) mma_h_k8_z(Ye[J], zr, an, X[J][1]);
#pragma unroll
        for (int J = 0; J < 8; J++) mma_h_k8_z(Yo[J], zr, an, N[J]);
#pragma unroll
        for (int J = 0; J < 8; J++) { G[J][0] = hsub(X[J][0], E[J][0]); G[J][1] = hsub(X[J][1], E[J][1]); }
#pragma unroll
        for (int jp = 0; jp < 4; jp++) ldsm4(ua + 2 * U_PL + jp * 256 - 16, X[2 * jp][0], X[2 * jp][1], X[2 * jp + 1][0], X[2 * jp + 1][1]);
#pragma unroll
        for (int J = 0; J < 8; J++) mma_h(Yo[J], A[0], G[J][0], G[J][1]);
#pragma unroll
        for (int J = 1; J < 8; J++) mma_h(Yo[J], A[1], G[J - 1][0], G[J - 1][1]);
#pragma unroll
        for (int J = 2; J < 8; J++) mma_h(Yo[J], A[2], G[J - 2][0], G[J - 2][1]);
#pragma unroll
        for (int J = 0; J < 8; J++) { F[J][0] = hsub(X[J][0], E[J][0]); F[J][1] = hsub(X[J][1], E[J][1]); }
#pragma unroll 1
        for (int k = 1; k < 8; k++) {
            ua -= 16; ta += 128;
            dense_step(M, Ye, Yo, X, F, Bq, ua, ta, zr);
        }
    }
    mbar_wait_n<2, 8>(bars + 8 * B_TD);
    LANE_VARS;
    if (lead) { TSTAMP(4); CSTAMP(28); }
    __syncwarp();
    const uint32_t idh = (g == 2 * t) ? 0x3C00u : (g == 2 * t + 1) ? 0x3C000000u : 0u;
    const uint32_t sbr = mapa(sb, h ^ 1);
    const uint32_t yl = TB + lane * 16, yr = sbr + (h ? ALT0 : ALT1) + A_YIN + warp * Y_CH + lane * 16;
    const uint32_t ys = lds32(sb + M_SC + (8 * h + warp) * 4);
    uint32_t ea[4];
    auto finish = [&](int J) {
        float m[4], e[4], o[4];
        widen_h(m, M[J], idh); widen_add_h(e, Ye[J], idh, m); widen_add_h(o, Yo[J], idh, m);
        const uint32_t y[4] = {hmul2_bf(pack_bf(e[0], e[2]), ys), hmul2_bf(pack_bf(o[0], o[2]), ys), hmul2_bf(pack_bf(e[1], e[3]), ys), hmul2_bf(pack_bf(o[1], o[3]), ys)};
        if (!(J & 1)) {
#pragma unroll
            for (int i = 0; i < 4; i++) ea[i] = y[i];
        } else {
            st_async16(yr + (J >> 1) * 512, h ? ea[0] : y[0], h ? ea[1] : y[1], h ? ea[2] : y[2], h ? ea[3] : y[3], sbr + M_BARS + 8 * (B_Y + (J >> 1)));
            sts128(yl + (J >> 1) * 512, h ? y[0] : ea[0], h ? y[1] : ea[1], h ? y[2] : ea[2], h ? y[3] : ea[3]);
            __syncwarp();
            if (lane == 0) mbar_arrive(bars + 8 * (B_Y + (J >> 1)));
        }
    };
    const uint32_t a1 = UB + (3 - mi) * U_PL + (8 + r) * 16;
    const uint32_t a2 = UB + ((2 - mi) & 3) * U_PL + (8 + r - (mi == 3)) * 16;
    const uint32_t a3 = UB + (2 - (mi & 1)) * U_PL + (7 + r) * 16;
    const uint32_t bt = sb + OFF_BAND + 4 * (32 + g + 2 * t);
    auto load3 = [&](Chunks& u, int j) { ldsm4(a2 + j * 128, u.d2, u.d1, u.d0, u.dm1); ldsm4(a1 + j * 128, u.c3, u.c2, u.c1, u.c0); ldsm2(a3 + j * 128, u.em2, u.em3); };
    auto load2 = [&](Chunks& u, int j) {
        if (DUP_MOV == 0) load3(u, j);
        else { ldsm4(a1 + j * 128, u.c3, u.c2, u.c1, u.c0); if (DUP_MOV == 1) ldsm4(a2 + j * 128, u.d2, u.d1, u.d0, u.dm1); }
        ldsm4(a1 + j * 128 - 16, u.cm1, u.cm2, u.cm3, u.cm4);
        if (DUP_MOV >= 1) { u.em2 = u.cm2 ^ zr; u.em3 = u.cm3 ^ zr; }
        if (DUP_MOV >= 2) { u.d2 = u.c2 ^ zr; u.d1 = u.c1 ^ zr; u.d0 = u.c0 ^ zr; u.dm1 = u.cm1 ^ zr; }
    };
    Chunks u;
    uint32_t B35[4];
    uint2 Q[4][3], QS[2][3];
    {
        const uint32_t f7 = lds32(bt + 768 - 36), g7 = lds32(bt + 768 - 4), f9 = lds32(bt + 1024 - 32), g9 = lds32(bt + 1024), h9 = lds32(bt + 1024 + 32);
        const uint32_t f1 = hmul(lds32(bt - 28), lds16(TB + T_R2 + 176) * 0x10001u);
        load3(u, 0);
        const uint32_t tq = TB + T_R3 + 8 * (7 + g - 2 * t);
        uint2 Q0[4], Q1[4], Q2[4];
#pragma unroll
        for (int i = 0; i < 4; i++) { Q0[i] = lds64(tq + 64 * i); Q1[i] = lds64(tq + T3_S + 64 * i); Q2[i] = lds64(tq + T3_S - 8 + 64 * i); }
#pragma unroll
        for (int J = 0; J < 8; J++) mma_h(Ye[J], Bq[0], F[J][0], F[J][1]);
#pragma unroll
        for (int J = 1; J < 8; J++) mma_h(Ye[J], Bq[1], F[J - 1][0], F[J - 1][1]);
        const uint32_t B7[4] = {zr, f7, f7 ^ zr, g7}, B9a[4] = {zr + zr, f9, f9 ^ zr, g9}, B9b[4] = {g9 ^ zr, h9, h9 ^ zr, zr * 3}, B1[4] = {zr * 5, f1, f1 ^ zr, zr * 7};
        const uint32_t g7b = g7 ^ zr, z7 = zr * 9;
        if (FENCES & 1) FENCE();
        uint32_t WE[2][4], WO[2][4];
#pragma unroll
        for (int j = 0; j < 5; j++) {
            uint32_t (&we)[4] = WE[j & 1], (&wo)[4] = WO[j & 1], (&pe)[4] = WE[~j & 1], (&po)[4] = WO[~j & 1];
            if (j == 3) {
                const uint32_t t2 = TB + T_R2 + 8 * (6 + g - 2 * t);
                B35[0] = lds32(bt + 256 - 28); B35[1] = lds32(bt + 512 - 40); B35[2] = lds32(bt + 256 + 4); B35[3] = lds32(bt + 512 - 8);
#pragma unroll
                for (int i = 0; i < 3; i++)
#pragma unroll
                    for (int s = 0; s < 4; s++) Q[s][i] = lds64(t2 + T2_S * s + 64 * i);
            }
            if (j < 4) {
                mma_h_z(we[2], we[3], B9a, u.d0, u.dm1); mma_h_z(wo[2], wo[3], B9a, u.d2, u.d1);
                mma_h_z(we[0], we[1], B7, u.c1, u.c0); mma_h_z(wo[0], wo[1], B7, u.c3, u.c2);
            }
            if (j == 0) { finish(0); finish(1); }
#pragma unroll
            for (int i = 0; i < 5 - j && j > 0; i++) { mma_h(Ye[j + 3 + i], pe, Q0[i].x, Q0[i].y); mma_h(Yo[j + 3 + i], pe, Q1[i].x, Q1[i].y); }
            if (j < 4) {
                mma_h2(we[2], we[3], B9b, u.em2, u.em3); mma_h2(wo[2], wo[3], B9b, u.d0, u.dm1);
                mma_h_k8(we[0], we[1], g7b, z7, u.dm1); mma_h_k8(wo[0], wo[1], g7b, z7, u.c1);
                mma_h(Ye[j + 4], B1, u.d0, u.dm1); mma_h(Yo[j + 4], B1, u.d2, u.d1);
                if (j < 3) load3(u, j + 1); else load2(u, 0);
            }
#pragma unroll
            for (int i = 0; i < 5 - j && j > 0; i++) { mma_h(Ye[j + 3 + i], po, Q2[i].x, Q2[i].y); mma_h(Yo[j + 3 + i], po, Q0[i].x, Q0[i].y); }
            if (j == 3) {
#pragma unroll
                for (int i = 0; i < 3; i++)
#pragma unroll
                    for (int s = 0; s < 2; s++) { QS[s][i].x = hadd(Q[s][i].x, Q[s + 2][i].x); QS[s][i].y = hadd(Q[s][i].y, Q[s + 2][i].y); }
            }
            if (j < 3 ? ((FENCES & 2) || (j == 2 && (FENCES & 4))) : (j == 4 && (FENCES & 8))) FENCE();
        }
    }
    uint32_t xo, go, ya, sel, any, wu, oo;
    auto mix_setup = [&]() {
        LANE_VARS;
        const int pos = 2 * (warp & 3) + (t >> 1);
        xo = sb + OFF_S + h * 32768 + (warp & 3) * 2048 + (warp >> 2) * 1024 + (g >> 1) * 128 + (t >> 1) * 64 + (g & 1) * 32 + (((t ^ (g >> 1)) & 1) << 4);
        go = sb + OFF_GP + (8 * pos + g) * 64 + ((warp >> 2) ^ (g >> 1) ^ (2 * (t & 2))) * 8;
        const int ch = 2 * mi + (r & 1);
        ya = sb + ((((r >> 1) & 1) == h) ? OFF_TAB + ch * T_CH : (h ? ALT1 : ALT0) + A_YIN + ch * Y_CH) + (8 * (warp & 3) + (r & 4) + 2 * (warp >> 2)) * 16;
        sel = lds16(sb + M_BMAP + (8 * warp + g) * 2);
        any = __reduce_or_sync(0xffffffffu, sel);
        sel >>= t >> 1;
        oo = (128 * (warp >> 2) + 8 * g + pos) * D_ + 8 * (t & 1);
        wu = __shfl_sync(0xffffffffu, warp, 0);
    };
    struct MixIn { uint32_t gp[2]; uint4 e[2]; };
    auto mix_load = [&](MixIn& q, int J) {
        const uint2 g2 = lds64(go ^ (16 * J));
        q.gp[0] = g2.x; q.gp[1] = g2.y;
#pragma unroll
        for (int k = 0; k < 2; k++) {
            const uint4 x = lds128(xo + J * 8192 + k * 512);
            q.e[k] = make_uint4(hi_mul_bf(q.gp[k], x.x), hi_mul_bf(q.gp[k], x.y), hi_mul_bf(q.gp[k], x.z), hi_mul_bf(q.gp[k], x.w));
        }
    };
    auto mix_calc = [&](MixIn& q, int J) {
#pragma unroll
        for (int k = 0; k < 2; k++) {
            uint32_t y[4];
            ldsm4t(ya + J * 512 + k * 16, y[0], y[1], y[2], y[3]);
            q.e[k] = make_uint4(lo_fma_bf(q.gp[k], y[0], q.e[k].x), lo_fma_bf(q.gp[k], y[1], q.e[k].y), lo_fma_bf(q.gp[k], y[2], q.e[k].z), lo_fma_bf(q.gp[k], y[3], q.e[k].w));
            if (J < 2) sts128_if(!((sel >> (4 * J + 2 * k)) & 1u), xo + J * 8192 + k * 512, q.e[k].x, q.e[k].y, q.e[k].z, q.e[k].w);
        }
    };
    auto mix_send = [&](const MixIn& q, int J) {
        if (J >= 2 && ((any >> (4 * J)) & 15u)) {
#pragma unroll
            for (int k = 0; k < 2; k++) if (!((sel >> (4 * J + 2 * k)) & 1u)) *(uint4*)(out + (size_t)(512 * J + 256 * h + 64 * k) * D_ + 16 * pr + oo) = q.e[k];
        } else {
#pragma unroll
            for (int k = 0; k < 2 && J >= 2; k++) sts128(xo + J * 8192 + k * 512, q.e[k].x, q.e[k].y, q.e[k].z, q.e[k].w);
            asm volatile("fence.proxy.async.shared::cta;" ::: "memory");
            __syncwarp();
            asm volatile("{ .reg .pred p; elect.sync _|p, 0xffffffff;\n\t@p cp.async.bulk.tensor.5d.global.shared::cta.bulk_group [%0, {%2, %3, %3, %4, %5}], [%1]; }"
                         :: "l"(tm_o), "r"(sb + OFF_S + h * 32768 + J * 8192 + (wu & 3) * 2048 + (wu >> 2) * 1024),
                            "r"(16 * pr), "r"(0), "r"(32 * J + 16 * h + 8 * (wu >> 2)), "r"(wu & 3) : "memory");
        }
    };
    MixIn q, q2, q3;
    const uint32_t zq = zr + zr;
#pragma unroll
    for (int j = 0; j < 6; j++) {
        if (j == MIX0_AT + 1) mix_send(q, 0);
        if (j == MIX1_AT + 1) mix_send(q, 1);
        if (j == MIX0_AT) mbar_wait_n<2, 8 * (B_Y - B_G)>(bars + 8 * B_G);
        else if (j == MIX1_AT) mbar_spin(bars + 8 * (B_Y + 1));
        else if (j > 0 && (FENCES & 16) && (SEND_FENCE || (j != MIX0_AT + 1 && j != MIX1_AT + 1))) FENCE();
        uint32_t H[7][2];
        mma_h_z(H[3][0], H[3][1], B35, u.d0, u.dm1); mma_h_z(H[4][0], H[4][1], B35, u.c1, u.c0);
        mma_h_z(H[5][0], H[5][1], B35, u.d2, u.d1); mma_h_z(H[6][0], H[6][1], B35, u.c3, u.c2);
        mma_h_z(H[2][0], H[2][1], B35, u.cm1, u.cm2); mma_h_z(H[1][0], H[1][1], B35, u.em2, u.em3); mma_h_z(H[0][0], H[0][1], B35, u.cm3, u.cm4);
        if (j < 5) load2(u, j + 1);
        if (j > 0) finish(j + 1);
        if (j == MIX0_AT) { mix_setup(); mix_load(q, 0); mix_calc(q, 0); }
        if (j == MIX1_AT) { mix_load(q, 1); mix_calc(q, 1); }
        if (j == 5) { mix_load(q2, 2); mix_load(q3, 3); }
        const int n = j < 4 ? 3 : 6 - j;
#pragma unroll
        for (int s = 0; s < 2; s++) {
            const int o = 3 - s;
            const uint32_t qe[4] = {H[o][0] ^ zr, H[o + 1][0] ^ zq, H[o][1] ^ zr, H[o + 1][1] ^ zq};
            const uint32_t qg[4] = {hsub(H[o + 2][0], H[o][0]), hsub2(H[o + 3][0], H[o + 1][0]), hsub(H[o + 2][1], H[o][1]), hsub2(H[o + 3][1], H[o + 1][1])};
            const uint32_t qf[4] = {hsub(H[o - 2][0], H[o][0]), hsub2(H[o - 1][0], H[o + 1][0]), hsub(H[o - 2][1], H[o][1]), hsub2(H[o - 1][1], H[o + 1][1])};
#pragma unroll
            for (int i = 0; i < n; i++) mma_h(M[j + 2 + i], qe, QS[s][i].x, QS[s][i].y);
#pragma unroll
            for (int i = 0; i < n; i++) mma_h(Yo[j + 2 + i], qg, Q[s][i].x, Q[s][i].y);
#pragma unroll
            for (int i = 0; i < n; i++) mma_h(Ye[j + 2 + i], qf, Q[s + 2][i].x, Q[s + 2][i].y);
        }
    }
    finish(7);
    if (lead) { TSTAMP(5); CSTAMP(29); }
    if (MIX1_AT == 5) mix_send(q, 1);
    mbar_spin(bars + 8 * (B_Y + 2));
    asm volatile("cp.async.bulk.commit_group;" ::: "memory");
    mix_calc(q2, 2);
    mix_send(q2, 2);
    asm volatile("cp.async.bulk.wait_group 0;" ::: "memory");
    __syncwarp();
    if (lane == 0) mbar_arrive(bars + 8 * B_SD);
    mbar_spin(bars + 8 * (B_Y + 3));
    if (lead) TSTAMP(6);
    mix_calc(q3, 3);
    mix_send(q3, 3);
    asm volatile("cp.async.bulk.commit_group;" ::: "memory");
    asm volatile("cp.async.bulk.wait_group.read 0;" ::: "memory");
}

__global__ void __cluster_dims__(2, 1, 1) __launch_bounds__(NTHREADS, 1)
fused_kernel(const Params p, const __grid_constant__ CUtensorMap tm_gu, const __grid_constant__ CUtensorMap tm_down, const __grid_constant__ CUtensorMap tm_x,
             const __grid_constant__ CUtensorMap tm_r, const __grid_constant__ CUtensorMap tm_o) {
    extern __shared__ __align__(1024) unsigned char smem[];
    const uint32_t sb = __shfl_sync(0xffffffffu, smem_u32(smem), 0);
    int tid;
    asm volatile("mov.u32 %0, %%tid.x;" : "=r"(tid));
    const int pw = tid >> 5, lane = tid & 31;
    const int kc = ((blockIdx.x >> 1) + 60) & 63, lo = kc < 32, hi = kc >= 60, kq = lo ? kc >> 3 : ((kc - 32) * 37) >> 8;
    const int h = blockIdx.x & 1;
    const int pr = (hi ? 1 : 4) * kc - (lo ? 31 : hi ? 0 : 27) * kq - ((lo | hi) ? 0 : 96);
    const int c = 2 * pr + h;
    const uint32_t bars = sb + M_BARS;

    uint2 v_la, v_ai, v_cr, v_ci;
    uint32_t ldt16, dsk16;
    {
        const uint32_t ch = 8 * c + pw - MAIN_W0, po = ch * 128 + 4 * lane;
        asm volatile("{ .reg .pred q; setp.ge.u32 q, %16, 8; @q bra.uni L%=;\n\t"
                     "ld.global.nc.v2.u32 {%0,%1}, [%10];\n\tld.global.nc.v2.u32 {%2,%3}, [%11];\n\tld.global.nc.u16 %8, [%14];\n\t"
                     "ld.global.nc.v2.u32 {%4,%5}, [%12];\n\tld.global.nc.v2.u32 {%6,%7}, [%13];\n\tld.global.nc.u16 %9, [%15];\nL%=:\n\t}"
                     : "=r"(v_la.x), "=r"(v_la.y), "=r"(v_ai.x), "=r"(v_ai.y), "=r"(v_cr.x), "=r"(v_cr.y), "=r"(v_ci.x), "=r"(v_ci.y), "=r"(ldt16), "=r"(dsk16)
                     : "l"(p.logA + po), "l"(p.Aim + po), "l"(p.Cre + po), "l"(p.Cim + po), "l"(p.logdt + ch), "l"(p.Dskip + ch), "r"(pw - MAIN_W0));
    }

    if (blockIdx.x >= 128) {
        if (blockIdx.x != 128) return;
        const unsigned tag = (ld_epoch(p.ex) + 1) & 0xffffu;
        const uint32_t idx0 = 2047 - (512 * (tid & 3) + (tid >> 3) + 256 * ((tid >> 2) & 1));
        const uint32_t list = sb + 128;
#pragma unroll 1
        for (int pass = 0; pass < 2; pass++) {
            if (tid == 0) sts32(sb + 64, 0);
            sts128(list + 16 * tid, 0, 0, 0, 0);
            uint4 a = make_uint4(lane == 0 ? 0x10000u : 0u, 0, 0, 0);
            bool ok = pass == 0;
#pragma unroll 1
            for (int it = 0; it < (1 << 22) && !ok; it++) {
                a = ld_gpu128(&p.ex->r[tid]);
                ok = (((a.x ^ tag) | (a.y ^ tag) | (a.z ^ tag) | (a.w ^ tag)) & 0xffffu) == 0;
            }
            if (!ok) __trap();
            const uint32_t key[4] = {(a.x & 0xffff0000u) | idx0, (a.y & 0xffff0000u) | (idx0 - 64), (a.z & 0xffff0000u) | (idx0 - 128), (a.w & 0xffff0000u) | (idx0 - 192)};
            const uint32_t wm = __reduce_max_sync(0xffffffffu, max(max(key[0], key[1]), max(key[2], key[3])));
            if (lane == 0) sts32(sb + pw * 4, wm);
            __syncthreads();
            const uint2 q = lds64(sb + 8 * (lane & 7));
            const uint32_t thr = __reduce_min_sync(0xffffffffu, max(q.x, q.y));
            if (tid == 0) TSTAMP(0);
            const uint32_t n = (key[0] >= thr) + (key[1] >= thr) + (key[2] >= thr) + (key[3] >= thr);
            if (n) {
                uint32_t pos;
                asm volatile("atom.shared.add.u32 %0, [%1], %2;" : "=r"(pos) : "r"(sb + 64), "r"(n) : "memory");
#pragma unroll
                for (int i = 0; i < 4; i++) if (key[i] >= thr) { sts32(list + 4 * pos, key[i]); pos++; }
            }
            __syncthreads();
            const int ncand = (int)lds32(sb + 64);
            const uint2 l0 = lds64(list + 8 * lane);
#pragma unroll 1
            for (int j = pw; j < ncand; j += 16) {
                const uint32_t mine = lds32(list + 4 * j);
                int rank = __popc(__ballot_sync(0xffffffffu, l0.x > mine)) + __popc(__ballot_sync(0xffffffffu, l0.y > mine));
#pragma unroll 1
                for (int i = 64; i < ncand; i += 32) rank += __popc(__ballot_sync(0xffffffffu, lds32(list + 4 * (i + lane)) > mine));
                if (rank < 8 && lane == 0) asm volatile("st.relaxed.gpu.global.v2.u32 [%0], {%1, %2};" :: "l"(&p.ex->top[rank]), "r"(mine), "r"(pass ? tag : tag ^ 0x8000u) : "memory");
            }
            if (tid == 0) TSTAMP(1);
            __syncthreads();
        }
        if (tid == 0) TSDUMP(3u);
        return;
    }

    if (pw != 12) asm volatile("barrier.cluster.arrive.relaxed.aligned;" ::: "memory");

    if (pw >= MAIN_W0 && pw < MAIN_W0 + 8) {
        const int warp = pw - MAIN_W0;
        [[maybe_unused]] const bool lead = (tid == 32 * MAIN_W0);
        asm volatile("setmaxnreg.inc.sync.aligned.u32 " MAIN_REGS ";");
        cluster_next();
        [[maybe_unused]] const int d = 8 * c + warp;
        const int g = lane >> 2, t = lane & 3, mi = lane >> 3, r = lane & 7;
        const uint32_t TB = sb + OFF_TAB + warp * T_CH;
        const uint32_t UB = sb + OFF_U + warp * U_CH;
        const uint32_t zr = p.zero;

        uint32_t Ra[2][2], Rb[2][2], Rc[2], Rl[2];
        int esum;
        {
            const float dt = bf_round(exp_acc(__uint_as_float(ldt16 << 16)));
            const uint32_t ec = max(warp_max16(amax2_bf(amax2_bf(v_cr.x, v_cr.y), amax2_bf(v_ci.x, v_ci.y))) >> 7, 6u);
            const float cf = __uint_as_float((__float_as_uint(dt) & 0x7fffffu) | ((260u - ec) << 23));
            esum = (int)ec + (int)(__float_as_uint(dt) >> 23) - 274;
            kernel_gen(v_la, v_ai, v_cr, v_ci, dt, cf, TB, UB, bars + 8 * B_KD, lane, zr, Ra, Rb, Rc, Rl);
        }
        if (lead) TSTAMP(2);

        {
            uint32_t mk = amax2_h(amax2_h(amax2_h(Ra[0][0], Ra[0][1]), amax2_h(Ra[1][0], Ra[1][1])), amax2_h(amax2_h(Rb[0][0], Rb[0][1]), amax2_h(Rb[1][0], Rb[1][1])));
            mk = amax2_h(amax2_h(mk, hmul(Rl[0], 0x34003400u)), amax2_h(Rc[0], Rc[1]));
            const int eb = (dsk16 >> 7) & 0xff, ek = max((int)(warp_max16(mk) >> 10), eb ? eb - 127 - esum : 0), en = eb - esum - 3 - ek;
            const float ds = (lane == 0 && eb && en > 0) ? __uint_as_float(((dsk16 & 0x807fu) << 16) | (en << 23)) : 0.f;
            const float fs = __uint_as_float(max(139 - ek, 1) << 23);
            const uint32_t ks = pack_h(fs, fs);
            uint32_t va[4], vb[4];
#pragma unroll
            for (int i = 0; i < 4; i++) { va[i] = hmul(Ra[i >> 1][i & 1], ks); vb[i] = hmul(Rb[i >> 1][i & 1], ks); }
            va[0] = hadd(va[0], pack_h(ds, 0.f));
            const uint32_t k512 = __shfl_sync(0xffffffffu, vb[0], 2) & 0xffffu, k255 = __shfl_sync(0xffffffffu, va[3], 31);
#pragma unroll
            for (int i = 0; i < 4; i++) {
                const uint32_t pv = __shfl_sync(0xffffffffu, lane == 31 ? (i ? va[i - 1] : 0u) : va[i], lane - 1);
                sts64(TB + 48 + 256 * i + 8 * lane, __byte_perm(pv, va[i], 0x5432), va[i]);
            }
#pragma unroll
            for (int i = 0; i < 4; i++) {
                const uint32_t nx = __shfl_sync(0xffffffffu, lane == 0 ? (i < 3 ? vb[i + (i < 3)] : k512) : vb[i], lane + 1 + 2 * (lane & 1));
                const uint32_t aa = __byte_perm(vb[i], 0, 0x1010);
                sts128_if(t < 2, TB + 1072 + 256 * i + 32 * g + 16 * t, (i == 0 && lane == 0) ? __byte_perm(k255, aa, 0x5432) : aa ^ zr, aa, vb[i] ^ zr, __byte_perm(vb[i], nx, 0x5432));
            }
            const uint32_t k0 = lane == 3 ? k512 : 0u, kk = k0 * 0x10001u;
            sts128_if(lane < 8, TB + 16 * lane + (lane < 3 ? 0 : 2048), kk, kk ^ zr, kk + zr, k0);
            esum += (int)ek;
            sts128(TB + T_R2 + 16 * lane, vb[0], vb[1], vb[2], vb[3]);
            sts128(TB + T_R2 + 512 + 16 * lane, hmul(Rc[0], ks), hmul(Rc[1], ks), hmul(Rl[0], ks), (uint32_t)esum);
            __syncwarp();
            if (lane == 0) mbar_arrive(bars + 8 * B_TS);
        }
        if (lead) TSTAMP(11);

        convolve(sb, h, zr, pr, p.out, &tm_o DBG_ARGS);
        { LANE_VARS; if (lead) { TSTAMP(7); TSDUMP(0x3c000cffu); } }
    } else if (pw < 4) {
        const int v = pw, at = tid;
        const int g = lane >> 2, t = lane & 3, mi = lane >> 3, r = lane & 7;
        const uint32_t dalt = (h ? ALT1 : ALT0) + A_SLOT - ALT_SLOT * 8192;
        cp16(sb + OFF_GP + tid * 16, p.wr + tid * 8);
        cp16(sb + OFF_GP + 2048 + tid * 16, p.gatew + tid * 8);
        const unsigned epoch = ld_epoch(p.ex);
        if (tid == 0) sts128(sb + OFF_S - 16, 0, 0, 0, 0);
        const unsigned tag = (epoch + 1) & 0xffffu;
        const int ftok = 2 * ((at >> 2) & 3) + (at & 1), fch = (at >> 4) + 8 * ((at >> 1) & 1);
        uint32_t eu;
        {
            cluster_next();
            cp_wait_all();
            bar_sync(1, 128);
            const uint32_t wo = sb + OFF_GP + 512 * v + 64 * ((g >> 1) & 1) + 16 * t + 4 * (g & 1);
            uint32_t w0[4], w1[4];
#pragma unroll
            for (int cb = 0; cb < 4; cb++) { w0[cb] = lds32(wo + 128 * cb); w1[cb] = lds32(wo + 128 * cb + 8); }
            const uint32_t go = sb + OFF_GP + 2048 + 512 * v + 64 * (g & 1) + 16 * t;
            const uint32_t ro = sb + M_RG + (g >> 1) * 32 + (2 * v + (g & 1)) * 4;
            const uint32_t xo = sb + OFF_XROW + (g >> 1) * 2048 + 512 * v + 64 * (g & 1) + 16 * t;
            const uint32_t one0 = 0x3F803F80u ^ p.zero, one1 = 0x3F803F80u + p.zero;
            auto row_sum = [&](uint32_t a) {
                const uint4 x = lds128(a), y = lds128(a + 16);
                return ((__uint_as_float(x.x) + __uint_as_float(x.y)) + (__uint_as_float(x.z) + __uint_as_float(x.w)))
                     + ((__uint_as_float(y.x) + __uint_as_float(y.y)) + (__uint_as_float(y.z) + __uint_as_float(y.w)));
            };
            const int dl = 8 * (r >> 1) + 4 - 2 * mi - (r & 1);
            const uint32_t so = sb + OFF_S + (v >> 1) * 32768 + (dl & 6) * 1024 + (8 * (v & 1) + (dl >> 4)) * 128 + (dl & 1) * 64 + (dl & 8) * 4 + ((dl & 16) ^ (h << 4));
            const uint32_t so2 = so + (dl >= 0 ? 0 : v == 2 ? -30720 : v == 0 ? 26624 : 0), so1 = (dl < 0 && v == 0) ? sb + OFF_S - 16 : so2;
            auto src = [&](int k) { return (k == 0 ? so1 : (k & 3) == 0 ? so2 : so) + (k >> 2) * 8192 + (k & 3) * 256; };
            uint32_t xr[16][4], mx = 0, idb = 0;
            auto slice = [&](int k) { ldsm4t(src(k), xr[k][0], xr[k][1], xr[k][2], xr[k][3]); };
            auto to_half = [&](uint32_t (&q)[4]) {
                float f0[4], f1[4];
                widen_bf(f0, q[0], q[1], idb); widen_bf(f1, q[2], q[3], idb);
                q[0] = pack_h(f0[0], f0[1]); q[1] = pack_h(f0[2], f0[3]); q[2] = pack_h(f1[0], f1[1]); q[3] = pack_h(f1[2], f1[3]);
            };
            auto track = [&](int k) { mx = amax2_bf(amax2_bf(mx, amax2_bf(xr[k][0], xr[k][1])), amax2_bf(xr[k][2], xr[k][3])); };
            auto cta_exp = [&]() {
                const uint32_t wm = warp_max16(mx);
                if (lane == 0) sts32(sb + M_MX + v * 4, wm);
                bar_sync(1, 128);
                const uint4 m4 = lds128(sb + M_MX);
                return max(max(m4.x, m4.y), max(m4.z, m4.w)) >> 7;
            };
            auto set_scale = [&]() { const uint32_t sc = (257u - eu) << 7; idb = (g == 2 * t) ? sc : (g == 2 * t + 1) ? sc << 16 : 0u; };
            uint4 x[4], gw[4];
#pragma unroll
            for (int cb = 0; cb < 4; cb++) gw[cb] = lds128(go + 128 * cb);
            auto gate = [&](int i) {
                float e0[4] = {0.f, 0.f, 0.f, 0.f}, e1[4] = {0.f, 0.f, 0.f, 0.f};
#pragma unroll
                for (int cb = 0; cb < 4; cb++)
                    mma_bf((cb & 1) ? e1 : e0, hmul2_bf(x[cb].x, gw[cb].x), hmul2_bf(x[cb].y, gw[cb].y), hmul2_bf(x[cb].z, gw[cb].z), hmul2_bf(x[cb].w, gw[cb].w), one0, one1);
                if (t == 0) stsf(ro + 512 + 128 * i, (e0[0] + e0[3]) + (e1[0] + e1[3]));
            };
#pragma unroll
            for (int i = 0; i < 4; i++) {
                if (i == 0) mbar_spin(bars + 8 * B_X); else mbar_wait_n<2, 8 * (B_X - B_S + 1)>(bars + 8 * (B_S + i - 1));
#pragma unroll
                for (int cb = 0; cb < 4; cb++) x[cb] = lds128(xo + 8192 * i + 128 * cb);
#pragma unroll
                for (int k = max(4 * i - 4, 0); k < 4 * i; k++) slice(k);
                float d0[4] = {0.f, 0.f, 0.f, 0.f}, d1[4] = {0.f, 0.f, 0.f, 0.f};
#pragma unroll
                for (int cb = 0; cb < 4; cb++) mma_bf((cb & 1) ? d1 : d0, x[cb].x, x[cb].y, x[cb].z, x[cb].w, w0[cb], w1[cb]);
                if (t == (g & 1)) stsf(ro + 128 * i, (d0[0] + d0[3]) + (d1[0] + d1[3]));
                if (i == 3) break;
                gate(i);
#pragma unroll
                for (int k = max(4 * i - 4, 0); k < 4 * i; k++) track(k);
                if (i == 1) {
                    eu = min(cta_exp() + 3u, 255u);
                    set_scale();
                }
#pragma unroll
                for (int k = max(4 * i - 4, 0); k < 4 * i; k++) to_half(xr[k]);
            }
            bar_sync(4, 256);
            if (at < 16) {
                const uint32_t rb = pack_bf(0.f, row_sum(sb + M_RG + at * 32));
                st_gpu32((uint32_t*)p.ex->r + 16 * c + at, ((rb ^ (((int)rb >> 31) | 0x80000000u)) & 0xffff0000u) | tag);
            }
            if (at == 32) mbar_arrive(bars + 8 * B_XF);
            if (at == 0) TSTAMP(8);
#pragma unroll
            for (int k = 8; k < 12; k++) { track(k); to_half(xr[k]); }
            mbar_spin(bars + 8 * (B_S + 3));
            if (at == 0) TSTAMP(9);
#pragma unroll
            for (int k = 12; k < 16; k++) slice(k);
            uint32_t utail = 0;
            if (at < 64 && r >= 5) utail = lds16(sb + OFF_S + 57344 + 1952 + ((12 - r) & 6) * 1024 + (r & 1) * 64 + ((h ^ 1) << 4) + 2 * (at >> 3));
            mbar_spin(bars + 8 * B_KD);
            const uint32_t uo = sb + OFF_U + g * U_CH + t * U_PL;
            auto put = [&](int k, const uint32_t (&q)[4]) { sts128(uo + (8 + 4 * v + 16 * (k >> 2) + (k & 3)) * 16, q[0], q[1], q[2], q[3]); };
            auto put_tail = [&]() { if (at < 64) sts16(sb + OFF_U + (at >> 3) * U_CH + 72 * 16 + r * 2, pack_h(bf_lo(utail) * bf_lo((257u - eu) << 7), 0.f)); };
#pragma unroll
            for (int k = 0; k < 12; k++) put(k, xr[k]);
            sts128(uo + v * 32, 0, 0, 0, 0); sts128(uo + v * 32 + 16, 0, 0, 0, 0);
#pragma unroll
            for (int k = 12; k < 16; k++) { track(k); to_half(xr[k]); put(k, xr[k]); }
            put_tail();
            mx = amax2_bf(mx, utail);
            uint32_t over;
            asm volatile("{ .reg .pred p, q; setp.ne.u32 p, %1, 0; bar.red.or.pred q, 1, 128, p; selp.u32 %0, 1, 0, q; }"
                         : "=r"(over) : "r"((uint32_t)(max(mx & 0x7f80u, (mx >> 16) & 0x7f80u) > (eu << 7))) : "memory");
            if (over) {
                eu = cta_exp();
                set_scale();
#pragma unroll 1
                for (int k = 0; k < 16; k++) {
                    uint32_t q[4];
                    ldsm4t(src(k), q[0], q[1], q[2], q[3]);
                    to_half(q);
                    put(k, q);
                }
                put_tail();
                bar_sync(1, 128);
            }
            if (at == 0) mbar_arrive(bars + 8 * B_U);
#pragma unroll
            for (int cb = 0; cb < 4; cb++) gw[cb] = lds128(go + 128 * cb);
            gate(3);
            bar_sync(1, 128);
            if (at < 16) st_gpu32((uint32_t*)p.ex->g + 1024 * h + 16 * (8 * (pr & 7) + (pr >> 3)) + (at ^ (2 * (pr >> 4) + 8 * (pr & 1))),
                                  (pack_bf(sigmoid_f(bf_round(row_sum(sb + M_RG + 512 + at * 32))), 0.f) & 0xffffu) | (tag << 16));
            if (at == 0) TSTAMP(23);
        }
        const int ct = v & 1, kh = v >> 1;
        uint32_t wa[GU_PRE][4][4];
        uint32_t ta, tb;
        {
            const int krow0 = 8 * (mi >> 1) + r;
            const uint32_t off0 = krow0 * 64 + (((2 * ct + (mi & 1)) ^ ((krow0 >> 1) & 3)) << 4);
            ta = sb + OFF_RING + kh * 2048 + off0 + p.swap_gu; tb = ta + 4096 - 2 * p.swap_gu;
        }
        auto gu_load = [&](uint32_t (&a)[4][4], int s) {
            const uint32_t o = (s % NSLOT) * 8192 + (s % NSLOT >= ALT_SLOT ? dalt : 0);
            ldsm4t(ta + o, a[0][0], a[0][1], a[0][2], a[0][3]);
            ldsm4t(tb + o, a[1][0], a[1][1], a[1][2], a[1][3]);
            ldsm4t(ta + o + 1024, a[2][0], a[2][1], a[2][2], a[2][3]);
            ldsm4t(tb + o + 1024, a[3][0], a[3][1], a[3][2], a[3][3]);
        };
        auto gu_release = [&](const uint32_t (&a)[4][4], int s) {
            if (s < B_S - B_EMPTY && lane == 0) mbar_arrive(bars + 8 * (B_EMPTY + s) + (a[0][0] & a[1][0] & a[2][0] & a[3][0] & p.zero));
        };
        auto gu_park = [&](auto S0, auto N) {
            constexpr int s0 = decltype(S0)::value, n = decltype(N)::value;
            if (c < NGU_CTA) {
                mbar_wait_n<n, 8>(bars + 8 * s0);
#pragma unroll
                for (int s = s0; s < s0 + n; s++) gu_load(wa[s], s);
#pragma unroll
                for (int s = s0; s < s0 + n; s++) gu_release(wa[s], s);
            }
        };
        gu_park(IC<0>(), IC<4>());
        asm volatile("barrier.cluster.wait.acquire.aligned;" ::: "memory");
        mbar_wait(bars + 8 * B_TS);
#pragma unroll 1
        for (int i = 0; i < 2; i++) {
            const int es = group_tables(sb + OFF_TAB + (v + 4 * i) * T_CH, lane) + (int)eu;
            if (lane < 2) { const uint32_t o = mapa(sb, lane); st_async4(o + M_SC + (8 * h + v + 4 * i) * 4, (uint32_t)min(max(es, 1), 254) * 0x800080u, o + M_BARS + 8 * B_SC); }
        }
        __syncwarp();
        if (lane == 0) mbar_arrive(bars + 8 * B_TD);
        gu_park(IC<4>(), IC<GU_PRE - 4>());
        if (c < NGU_CTA) {
            float dgt[4] = {0.f, 0.f, 0.f, 0.f}, dup[4] = {0.f, 0.f, 0.f, 0.f}, dg2[4] = {0.f, 0.f, 0.f, 0.f}, du2[4] = {0.f, 0.f, 0.f, 0.f};
            const uint32_t xo = sb + OFF_XSEL + r * XS_ROW + 64 * kh + 16 * mi;
            auto gu_mma = [&](const uint32_t (&a)[4][4], const uint32_t (&b)[4]) {
                mma_bf(dgt, a[0][0], a[0][1], a[0][2], a[0][3], b[0], b[1]);
                mma_bf(dup, a[1][0], a[1][1], a[1][2], a[1][3], b[0], b[1]);
                mma_bf(dg2, a[2][0], a[2][1], a[2][2], a[2][3], b[2], b[3]);
                mma_bf(du2, a[3][0], a[3][1], a[3][2], a[3][3], b[2], b[3]);
            };
            auto gu_batch = [&](auto S0, auto N) {
                constexpr int s0 = decltype(S0)::value, n = decltype(N)::value;
                uint32_t b[n][4];
                mbar_wait_n<n, 8>(bars + 8 * s0);
#pragma unroll
                for (int i = 0; i < n; i++) { ldsm4(xo + 128 * (s0 + i), b[i][0], b[i][1], b[i][2], b[i][3]); gu_load(wa[i], s0 + i); }
#pragma unroll
                for (int i = 0; i < n; i++) gu_mma(wa[i], b[i]);
#pragma unroll
                for (int i = 0; i < n; i++) gu_release(wa[n - 1], s0 + i);
            };
            mbar_spin(bars + 8 * B_XS);
            if (at == 0) TSTAMP(12);
#pragma unroll
            for (int s = 0; s < GU_PRE; s++) { uint32_t b[4]; ldsm4(xo + 128 * s, b[0], b[1], b[2], b[3]); gu_mma(wa[s], b); }
            gu_batch(IC<6>(), IC<2>());
            mbar_spin(bars + 8 * (B_XS + 1));
            gu_batch(IC<8>(), IC<4>()); gu_batch(IC<12>(), IC<3>()); gu_batch(IC<15>(), IC<1>());
#pragma unroll
            for (int i = 0; i < 4; i++) { dgt[i] += dg2[i]; dup[i] += du2[i]; }
            if (at == 0) TSTAMP(13);
            const uint32_t red = sb + M_RG, hs = sb + OFF_XSEL;
            sts128(red + ((v ^ 2) * 32 + lane) * 16, __float_as_uint(kh ? dgt[0] : dgt[2]), __float_as_uint(kh ? dgt[1] : dgt[3]),
                   __float_as_uint(kh ? dup[0] : dup[2]), __float_as_uint(kh ? dup[1] : dup[3]));
            bar_sync(1, 128);
            const uint4 oth = lds128(red + at * 16);
#pragma unroll
            for (int i = 0; i < 2; i++) {
                const float gv = bf_round((kh ? dgt[2 + i] : dgt[i]) + __uint_as_float(i ? oth.y : oth.x));
                const float uv = bf_round((kh ? dup[2 + i] : dup[i]) + __uint_as_float(i ? oth.w : oth.z));
                const float sl = bf_round(gv * sigmoid_f(gv));
                uint32_t hv = pack_bf(sl * uv, 0.f) & 0xffffu;
                hv = (hv == 0x8000u) ? 0x8000u : (hv ^ 0x8000u);
                sts16(hs + (2 * t + i) * 64 + (g >> 1) * 16 + (2 * ct + kh) * 4 + (g & 1) * 2, hv);
            }
            bar_sync(1, 128);
            if (v == 0) st_gpu128(&p.ex->h[32 * c + lane], lds128(hs + lane * 16));
        }
        else mbar_wait(bars + 8 * (B_XS + 1));
        if (at == 0) TSTAMP(14);
        {
            mbar_wait(bars + 8 * B_G);
            const int row = (int)lds32(sb + M_IDX + ftok * 4);
            const int w = row & 7, jj = (row >> 3) & 7;
            const uint32_t xa = sb + OFF_S + h * 32768 + (row >> 9) * 8192 + (w & 6) * 1024 + ((row >> 4) & 15) * 128 + (w & 1) * 64 + (jj & 1) * 32 + ((2 * fch) ^ (row & 16));
            const float xv = bf_lo(lds16(xa));
            const uint32_t gp = lds32(sb + OFF_GP + (8 * w + jj) * 64 + ((4 * (row >> 9) + ((row >> 6) & 3)) ^ ((jj & 6) + 8 * (w & 1))) * 4);
            const uint32_t ya = sb + (((fch >> 3) == h) ? OFF_TAB + (fch & 7) * T_CH : (h ? ALT1 : ALT0) + A_YIN + (fch & 7) * Y_CH) + (row >> 9) * 512 + (4 * w + ((row >> 6) & 3)) * 16 + jj * 2;
            const float rs = bf_round(sigmoid_f(ldsf(sb + M_RSEL + ftok * 4)));
            uint4 hq[14];
            {
                const uint4* hsrc = &p.ex->h[(56 * h + 2 * v) * 32 + lane];
                mbar_wait(bars + 8 * (B_FULL + NST_GU + H_WAIT));
                if (at == 0) TSTAMP(15);
#pragma unroll
                for (int i = 0; i < 14; i++) hq[i] = ld_gpu128(hsrc + (8 * (i >> 1) + (i & 1)) * 32);
                bool ok = false;
#pragma unroll 1
                for (int it = 0; it < (1 << 22); it++) {
                    uint32_t mn = 0xffffffffu;
#pragma unroll
                    for (int i = 0; i < 14; i++) mn = min(mn, hq[i].x);
                    ok = __all_sync(0xffffffffu, mn != 0);
                    if (ok) break;
                    if (PSLEEP > 0) __nanosleep(PSLEEP);
#pragma unroll
                    for (int i = 0; i < 14; i++) if (hq[i].x == 0) hq[i] = ld_gpu128(hsrc + (8 * (i >> 1) + (i & 1)) * 32);
                }
                if (!ok) __trap();
            }
            if (at == 0) TSTAMP(16);
            mbar_wait_n<DN_PRE, 8>(bars + 8 * (B_FULL + NST_GU));
            float dd[4][4];
#pragma unroll
            for (int j = 0; j < 4; j++) { dd[j][0] = dd[j][1] = dd[j][2] = dd[j][3] = 0.f; }
            const int krow0 = 64 * (v & 1) + 8 * (mi >> 1) + r;
            const uint32_t td = sb + OFF_RING + (v >> 1) * 4096 + krow0 * 32 + (((mi & 1) ^ ((krow0 >> 2) & 1)) << 4);
#pragma unroll
            for (int s = 0; s < 7; s++) {
                if (s >= DN_PRE) mbar_spin(bars + 8 * (B_FULL + NST_GU + s));
                const uint32_t tile = td + ((NST_GU + s) % NSLOT) * 8192 + ((NST_GU + s) % NSLOT >= ALT_SLOT ? dalt : 0);
                uint32_t a[4][4];
#pragma unroll
                for (int j = 0; j < 4; j++) ldsm4t(tile + j * 512, a[j][0], a[j][1], a[j][2], a[j][3]);
                mma_bf(dd[0], a[0][0], a[0][1], a[0][2], a[0][3], hq[2 * s].x, hq[2 * s].y);
                mma_bf(dd[1], a[1][0], a[1][1], a[1][2], a[1][3], hq[2 * s].z, hq[2 * s].w);
                mma_bf(dd[2], a[2][0], a[2][1], a[2][2], a[2][3], hq[2 * s + 1].x, hq[2 * s + 1].y);
                mma_bf(dd[3], a[3][0], a[3][1], a[3][2], a[3][3], hq[2 * s + 1].z, hq[2 * s + 1].w);
            }
            uint32_t ds[4];
#pragma unroll
            for (int j = 0; j < 4; j++) ds[j] = __float_as_uint((dd[0][j] + dd[1][j]) + (dd[2][j] + dd[3][j]));
            if (at == 0) TSTAMP(17);
            const uint32_t o = mapa(sb, h ^ 1);
            st_async16(o + OFF_DP + (128 * h + at) * 16, ds[0], ds[1], ds[2], ds[3], o + M_BARS + 8 * B_DP);
            sts128(sb + OFF_DP + (128 * h + at) * 16, ds[0], ds[1], ds[2], ds[3]);
            __syncwarp();
            if (lane == 0) mbar_arrive(bars + 8 * B_DP);
            mbar_spin(bars + 8 * B_DP);
            float pt[8];
#pragma unroll
            for (int k = 0; k < 8; k++) pt[k] = ldsf(sb + OFF_DP + k * 512 + at * 4);
            const float tot = -(((pt[0] + pt[1]) + (pt[2] + pt[3])) + ((pt[4] + pt[5]) + (pt[6] + pt[7])));
            const float eb = bf_round(bf_hi(gp) * bf_round(xv + bf_round(bf_round(tot) * rs)));
            mbar_wait_n<3, 8>(bars + 8 * (B_Y + 2));
            if (((row >> 8) & 1) == h) p.out[(size_t)row * D_ + 16 * pr + fch] = __float2bfloat16_rn(fmaf(bf_lo(gp), bf_lo(lds16(ya)), eb));
        }
        if (at == 0) { TSTAMP(18); TSDUMP(c < NGU_CTA ? 0x0087f300u : 0x0087c300u); if (c == 0) *(volatile unsigned*)&p.ex->epoch = epoch + 1; }
    } else {
        const uint32_t t_start = now_ns();
        asm volatile("setmaxnreg.dec.sync.aligned.u32 " HELP_REGS ";");
        if (pw != 12) {
            if (pw >= 14) {
#pragma unroll
                for (int k = 0; k < 5; k++) {
                    const int w = 1 + 2 * k, e = (tid & 63) - 32;
                    sts32(sb + OFF_BAND + k * 256 + (tid & 63) * 4, ((e >= 0 && e < w) ? 0x3C00u : 0u) | ((e + 1 >= 0 && e + 1 < w) ? 0x3C000000u : 0u));
                }
                cluster_next();
            } else {
                if (lane == 0) {
                    asm volatile("prefetch.tensormap [%0];" :: "l"(&tm_r) : "memory");
                    asm volatile("prefetch.tensormap [%0];" :: "l"(&tm_x) : "memory");
                }
                sts32(sb + M_BMAP + lane * 4, 0);
                __syncwarp();
                cluster_next();
                if (c < NGU_CTA) {
                    st_gpu128(&p.ex->h[32 * c + lane], make_uint4(0, 0, 0, 0));
                    if (ld_gpu128(&p.ex->h[32 * c + lane]).x != 0) __trap();
                }
            }
        } else {
            if (lane == 0) {
#pragma unroll
                for (int k = 0; k < 4; k++) { mbar_init(bars + 8 * (B_X + k), 1); mbar_init(bars + 8 * (B_S + k), 1); }
                asm volatile("fence.proxy.async.shared::cta;" ::: "memory");
                asm volatile("fence.mbarrier_init.release.cluster;" ::: "memory");
            }
            __syncwarp();
            asm volatile("barrier.cluster.arrive.relaxed.aligned;" ::: "memory");
            tma4d_warp(sb + OFF_XROW, &tm_r, 4 * h, pr, bars + 8 * B_X);
            asm volatile("barrier.cluster.wait.acquire.aligned;" ::: "memory");
            if (lane == 0) TSTAMP(20);
#pragma unroll
            for (int i = 0; i < 4; i++) {
                tma5d_both(sb + OFF_S + (4 * h + i) * 8192, &tm_x, 16 * pr, 32 * i + 16 * h, bars + 8 * (B_S + i));
                if (i < 3) tma4d_warp(sb + OFF_XROW + (i + 1) * 8192, &tm_r, 8 * (i + 1) + 4 * h, pr, bars + 8 * (B_X + i + 1));
            }
            if (lane == 0) {
                TSTAMP(24);
#pragma unroll
                for (int k = 0; k < 4; k++) { mbar_expect(bars + 8 * (B_X + k), 8192); mbar_expect(bars + 8 * (B_S + k), 16384); }
                asm volatile("prefetch.tensormap [%0];" :: "l"(&tm_gu) : "memory");
                asm volatile("prefetch.tensormap [%0];" :: "l"(&tm_down) : "memory");
                asm volatile("prefetch.tensormap [%0];" :: "l"(&tm_o) : "memory");
#pragma unroll
                for (int k = 0; k < B_S; k++) mbar_init(bars + 8 * k, k < B_EMPTY ? 1 : 4);
#pragma unroll
                for (int k = B_XS; k < B_X; k++) mbar_init(bars + 8 * k, (k >= B_Y && k < B_SD) ? 9 : (k == B_KD || k == B_TS || k == B_SD) ? 8 : k == B_TD ? 4 : k == B_XS + 1 ? 2 : k == B_DP ? 5 : 1);
#pragma unroll
                for (int k = 0; k < B_EMPTY; k++) mbar_expect(bars + 8 * k, 8192);
#pragma unroll
                for (int k = B_XS; k < B_SD; k++) if (k != B_TD && k != B_G) mbar_expect(bars + 8 * k, k < B_TD ? (c < NGU_CTA ? 8192 : 0) : k == B_SC ? 64 : k == B_DP ? 2048 : k == B_NONE ? 0 : 4096);
                asm volatile("fence.proxy.async.shared::cta;" ::: "memory");
                asm volatile("fence.mbarrier_init.release.cluster;" ::: "memory");
            }
            __syncwarp();
            asm volatile("barrier.cluster.arrive.relaxed.aligned;" ::: "memory");
        }
        bar_arrive(4, 256);
        bar_sync(6, 128);
        if (pw == 15) {
            const unsigned tag = (ld_epoch(p.ex) + 1) & 0xffffu;
            const int tok = lane & 7;
            uint32_t top = 0;
            bool ok = false;
            mbar_wait(bars + 8 * B_XF);
#pragma unroll 1
            for (int it = 0; it < (1 << 22); it++) {
                uint32_t tg;
                asm volatile("ld.relaxed.gpu.global.v2.u32 {%0,%1}, [%2];" : "=r"(top), "=r"(tg) : "l"(&p.ex->top[tok]) : "memory");
                ok = __all_sync(0xffffffffu, tg == tag);
                if (ok) break;
            }
            if (!ok) __trap();
            if (lane == 0) TSTAMP(25);
            const int row = 2047 - (int)(top & 0xffffu);
            if (c < NGU_CTA) {
#pragma unroll
                for (int k = 0; k < 8; k++) {
                    const int tk = 4 * h + ((k + pr) & 3), hf = k >> 2;
                    bulk_load_both(sb + OFF_XSEL + tk * XS_ROW + 1024 * hf, p.u + (size_t)__shfl_sync(0xffffffffu, row, tk) * D_ + 512 * hf, 1024, bars + 8 * (B_XS + hf));
                }
            }
            if (lane == 0) TSTAMP(21);
            if (lane < 8) {
                const uint32_t ord = top >> 16;
                sts32(sb + M_RSEL + tok * 4, ((ord & 0x8000u) ? (ord & 0x7fffu) : (~ord & 0xffffu)) << 16);
                sts32(sb + M_IDX + tok * 4, (uint32_t)row);
                if (((row >> 8) & 1) == h) asm volatile("red.shared.or.b32 [%0], %1;" :: "r"(sb + M_BMAP + ((row >> 7) & 1) * 64 + (row & 6) * 8 + ((row >> 4) & 3) * 4),
                                                   "r"(1u << (4 * (row >> 9) + ((row >> 5) & 2) + (row & 1) + 2 * (row & 8))) : "memory");
            }
            __syncwarp();
            if (lane == 0) { mbar_arrive(bars + 8 * (B_XS + 1)); TSDUMP(0x02200000u); }
            mbar_wait_n<2, 8>(bars + 8 * (B_XS + 1));
            if (lane == 0) bulk_load(sb + OFF_GP, &p.ex->g[256 * h], 4096, bars + 8 * B_GL);
            __syncwarp();
            mbar_wait(bars + 8 * B_GL);
#pragma unroll 2
            for (int i = lane; i < 256; i += 32) {
                uint4 a = lds128(sb + OFF_GP + i * 16);
#pragma unroll 1
                for (int it = 0; (((a.x ^ (tag << 16)) | (a.y ^ (tag << 16)) | (a.z ^ (tag << 16)) | (a.w ^ (tag << 16))) >> 16) != 0; it++) {
                    if (it > (1 << 22)) __trap();
                    a = ld_gpu128(&p.ex->g[256 * h + i]);
                }
                auto both = [](uint32_t w) { return (w & 0xffffu) | (pack_bf(1.f - bf_lo(w), 0.f) << 16); };
                sts128(sb + OFF_GP + i * 16, both(a.x), both(a.y), both(a.z), both(a.w));
            }
            __syncwarp();
            if (lane == 0) { TSTAMP(30); TSDUMP(1u << 30); }
            if (lane == 0) mbar_arrive(bars + 8 * B_G);
            return;
        }
        const int s0 = c < NGU_CTA ? 0 : NST_GU, s = lane, dn = s >= NST_GU;
        const int slot = s < NSLOT ? s : s < 2 * NSLOT ? s - NSLOT : s - 2 * NSLOT, depth = dn ? DEPTH_D : DEPTH_G;
        const uint32_t dst = sb + OFF_RING + slot * 8192 + (slot >= ALT_SLOT ? (h ? ALT1 : ALT0) + A_SLOT - ALT_SLOT * 8192 : 0);
        const uint32_t due = (t_start + T_W + h * (DT_G / 2) + DT_G * s + (dn ? (DT_D - DT_G) * (s - NST_GU) : 0)) & ~63u;
        const uint32_t w_slot = bars + 8 * (s >= s0 + NSLOT ? B_EMPTY + s - NSLOT : slot >= ALT_SLOT ? B_U : s >= X_SLOT ? B_XF : B_NONE);
        const uint32_t w_depth = bars + 8 * (s >= s0 + depth ? B_FULL + s - depth : B_NONE);
        const CUtensorMap* tm = dn ? &tm_down : &tm_gu;
        const int cx = dn ? 16 * pr : 32 * c, cy = dn ? 1792 * h + 256 * (s - NST_GU) : 64 * s;
#pragma unroll 1
        for (int k = s0 + pw - 12; k < NST; k += 3) {
            if (lane == k) {
#pragma unroll 1
                for (int n = 0; n < 1000; n++) {
                    const uint32_t now = now_ns();
                    if ((int)(due - now) <= 0) break;
                    __nanosleep(min((now ^ due) >> 1, 1023u));
                }
                mbar_wait2(w_slot, w_depth);
                tma3d(dst, tm, cx, cy, 0, bars + 8 * (B_FULL + s));
            }
            __syncwarp();
        }
    }
}

typedef CUresult (*EncodeFn)(CUtensorMap*, CUtensorMapDataType, cuuint32_t, void*, const cuuint64_t*, const cuuint64_t*,
                             const cuuint32_t*, const cuuint32_t*, CUtensorMapInterleave, CUtensorMapSwizzle,
                             CUtensorMapL2promotion, CUtensorMapFloatOOBfill);

void make_map(EncodeFn f, CUtensorMap* m, const void* ptr, int rank, const cuuint64_t* dims, const cuuint64_t* strides, const cuuint32_t* box, CUtensorMapSwizzle sw) {
    const cuuint32_t es[5] = {1, 1, 1, 1, 1};
    f(m, CU_TENSOR_MAP_DATA_TYPE_BFLOAT16, rank, (void*)ptr, dims, strides, box, es, CU_TENSOR_MAP_INTERLEAVE_NONE, sw,
      CU_TENSOR_MAP_L2_PROMOTION_L2_128B, CU_TENSOR_MAP_FLOAT_OOB_FILL_NONE);
}

}

extern "C" void kernel_launch(void* const* d_in, const int* in_sizes, int n_in, void* d_out, int out_size) {
    static EncodeFn enc = nullptr;
    static void* ex = nullptr;
    if (!enc) {
        void* fn = nullptr;
        cudaDriverEntryPointQueryResult qr;
        cudaGetDriverEntryPoint("cuTensorMapEncodeTiled", &fn, cudaEnableDefault, &qr);
        enc = (EncodeFn)fn;
        cudaFuncSetAttribute(fused_kernel, cudaFuncAttributeMaxDynamicSharedMemorySize, SMEM_BYTES);
        cudaGetSymbolAddress(&ex, g_ex);
    }
    CUtensorMap tgu, td, tx, tr, to;
    const char *wg = (const char*)d_in[9], *wu = (const char*)d_in[10];
    const bool swap = wu < wg;
    {
        const cuuint64_t dims[3] = {F_, D_, 2}, str[2] = {F_ * 2, (cuuint64_t)(swap ? wg - wu : wu - wg)};
        const cuuint32_t box[3] = {32, 64, 2};
        make_map(enc, &tgu, swap ? wu : wg, 3, dims, str, box, CU_TENSOR_MAP_SWIZZLE_64B);
    }
    {
        const cuuint64_t dims[3] = {D_, F_, 1}, str[2] = {D_ * 2, (cuuint64_t)D_ * 2 * F_};
        const cuuint32_t box[3] = {16, 256, 1};
        make_map(enc, &td, d_in[11], 3, dims, str, box, CU_TENSOR_MAP_SWIZZLE_32B);
    }
    {
        const cuuint64_t dims[5] = {D_, 2, 2, L_ / 16, 4}, str[4] = {D_ * 2 * 8, D_ * 2, D_ * 2 * 16, D_ * 2 * 2};
        const cuuint32_t box[5] = {16, 2, 2, 16, 4}, obox[5] = {16, 2, 2, 8, 1};
        make_map(enc, &tx, d_in[0], 5, dims, str, box, CU_TENSOR_MAP_SWIZZLE_32B);
        make_map(enc, &to, d_out, 5, dims, str, obox, CU_TENSOR_MAP_SWIZZLE_32B);
    }
    {
        const cuuint64_t dims[4] = {256, 4, L_ / 64, 64}, str[3] = {512, D_ * 2 * 64, D_ * 2};
        const cuuint32_t box[4] = {256, 4, 4, 1};
        make_map(enc, &tr, d_in[0], 4, dims, str, box, CU_TENSOR_MAP_SWIZZLE_NONE);
    }
    Params p;
    p.u = (const bf16*)d_in[0]; p.logA = (const bf16*)d_in[1]; p.Aim = (const bf16*)d_in[2];
    p.Cre = (const bf16*)d_in[3]; p.Cim = (const bf16*)d_in[4]; p.logdt = (const bf16*)d_in[5];
    p.Dskip = (const bf16*)d_in[6]; p.wr = (const bf16*)d_in[8]; p.gatew = (const bf16*)d_in[12];
    p.out = (bf16*)d_out;
    p.ex = (Exchange*)ex;
    p.zero = 0;
    p.swap_gu = swap ? 4096 : 0;
    fused_kernel<<<NCTA, NTHREADS, SMEM_BYTES>>>(p, tgu, td, tx, tr, to);
}
```

```cpp
#include <cuda_runtime.h>
#include <cuda_bf16.h>
#include <cuda_fp16.h>
#include <cuda.h>
#include <stdint.h>

typedef __nv_bfloat16 bf16;

namespace {

constexpr int L_ = 2048, D_ = 1024, F_ = 3584;
constexpr int NCTA = 130;
constexpr int NTHREADS = 512;
constexpr int MAIN_W0 = 4;
#define T_W 1600
#define DT_G 316
#define DT_D 344
#define DEPTH_G 5
#define DEPTH_D 3
#define H_WAIT 2
#define DN_PRE 5
#define PSLEEP 0
#define GU_BATCH 0
#define FENCES 16
#define MIX0_AT 2
#define MIX1_AT 4
#define SEND0_AT (MIX0_AT + 1)
#define SEND1_AT (MIX1_AT + 1)
#define DUP_MOV 2
#define KD_AT 7
#define KD_ORDER 0
#define STG_FROM 4
#define DV 0
#define SO 0
#define DU 1
#define FB_BLK 1
#define ZR p.zero
#define A_REUSE 0
#define MAIN_REGS "176"
#define HELP_REGS "32"
constexpr int kDenseUnroll = DU;
constexpr int GU_PRE = 6;
constexpr int NGU_CTA = 112;

constexpr int NSLOT    = 10;
constexpr int NST_GU   = 16, NST = 23;
constexpr int OFF_RING = 0;
constexpr int OFF_XROW = 53248, X_SLOT = 6;
constexpr int OFF_XSEL = 69632, XS_ROW = 2064;
constexpr int OFF_DP   = OFF_XSEL + 8192;
constexpr int OFF_S    = 87040;
constexpr int ALT0     = OFF_S + 32768, ALT1 = OFF_S - 512;
constexpr int A_YIN    = 32, Y_CH = 2064;
constexpr int A_SLOT   = 16896, ALT_SLOT = 8;
constexpr int U_PL     = 1184;
constexpr int U_CH     = 4752;
constexpr int OFF_U    = 153088;
constexpr int T_CH     = 4112;
constexpr int OFF_TAB  = 191104;
constexpr int T_R2     = 2176, T2_S = 208;
constexpr int T_R3     = 3040, T3_S = 336;
constexpr int OFF_GP   = 224000;
constexpr int OFF_BAND = 228096;
constexpr int OFF_MISC = 229376;
constexpr int M_BARS   = OFF_MISC;
constexpr int M_IDX    = OFF_MISC + 704;
constexpr int M_RSEL   = OFF_MISC + 736;
constexpr int M_BMAP   = OFF_MISC + 768;
constexpr int M_MX     = OFF_MISC + 896;
constexpr int M_SC     = OFF_MISC + 960;
constexpr int M_RG     = OFF_MISC + 1024;
constexpr int SMEM_BYTES = OFF_MISC + 3072;

constexpr int B_FULL = 0, B_EMPTY = NST, B_S = B_EMPTY + NST - NSLOT, B_XS = B_S + 4, B_TD = B_XS + 2, B_SC = B_TD + 1, B_G = B_SC + 1, B_GL = B_G + 1, B_NONE = B_GL + 1, B_DP = B_NONE + 1, B_Y = B_DP + 1,
              B_SD = B_Y + 4, B_KD = B_SD + 1, B_U = B_KD + 1, B_TS = B_U + 1, B_XF = B_TS + 1, B_X = B_XF + 1, NBAR = B_X + 4;
static_assert(NBAR <= 84, "barrier area");

struct Exchange {
    unsigned epoch, pad[31];
    uint4 h[8 * F_ / 8];
    uint4 r[L_ / 4];
    uint4 g[L_ / 4];
    uint2 top[16];
};
__device__ __align__(128) Exchange g_ex;

struct Params {
    const bf16 *logA, *Aim, *Cre, *Cim, *logdt, *Dskip, *u, *wr, *gatew;
    bf16* out;
    Exchange* ex;
    uint32_t zero;
    uint32_t swap_gu;
};

#define TSTAMP(i) do {} while (0)
#define CSTAMP(i) do {} while (0)
#define TSDUMP(mask) do {} while (0)
#define DBG_PARAMS
#define DBG_ARGS

__device__ __forceinline__ uint32_t smem_u32(const void* p) { return (uint32_t)__cvta_generic_to_shared(p); }
__device__ __forceinline__ void mbar_init(uint32_t b, uint32_t c) { asm volatile("mbarrier.init.shared::cta.b64 [%0], %1;" :: "r"(b), "r"(c) : "memory"); }
__device__ __forceinline__ void mbar_expect(uint32_t b, uint32_t tx) { asm volatile("mbarrier.arrive.expect_tx.shared::cta.b64 _, [%0], %1;" :: "r"(b), "r"(tx) : "memory"); }
__device__ __forceinline__ void mbar_arrive(uint32_t b) { asm volatile("mbarrier.arrive.shared::cta.b64 _, [%0];" :: "r"(b) : "memory"); }
#define WSLEEP "100"
#define W2SLEEP "40"
__device__ __forceinline__ void mbar_wait(uint32_t b) {
    asm volatile("{\n\t.reg .pred p, q;\n\t.reg .u32 n;\n\tmov.u32 n, 0;\n"
                 "W%=:\n\tmbarrier.try_wait.parity.shared::cta.b64 p, [%0], 0;\n\t"
                 "@p bra D%=;\n\tnanosleep.u32 " WSLEEP ";\n\tadd.u32 n, n, 1;\n\tsetp.lt.u32 q, n, 4194304;\n\t@q bra W%=;\n"
                 "D%=:\n\t}" :: "r"(b) : "memory");
}
__device__ __forceinline__ void mbar_spin(uint32_t b) {
    asm volatile("{\n\t.reg .pred p, q;\n\t.reg .u32 n;\n\tmov.u32 n, 0;\n"
                 "W%=:\n\tmbarrier.try_wait.parity.shared::cta.b64 p, [%0], 0;\n\t"
                 "@p bra D%=;\n\tadd.u32 n, n, 1;\n\tsetp.lt.u32 q, n, 4194304;\n\t@q bra W%=;\n"
                 "D%=:\n\t}" :: "r"(b) : "memory");
}
__device__ __forceinline__ void mbar_wait2(uint32_t a, uint32_t b) {
    asm volatile("{\n\t.reg .pred p, q;\n\t.reg .u32 n;\n\tmov.u32 n, 0;\n"
                 "W%=:\n\tmbarrier.try_wait.parity.shared::cta.b64 p, [%0], 0;\n\tmbarrier.try_wait.parity.shared::cta.b64 q, [%1], 0;\n\tand.pred p, p, q;\n\t"
                 "@p bra D%=;\n\tnanosleep.u32 " W2SLEEP ";\n\tadd.u32 n, n, 1;\n\tsetp.lt.u32 q, n, 4194304;\n\t@q bra W%=;\n"
                 "D%=:\n\t}" :: "r"(a), "r"(b) : "memory");
}
template <int N, int STEP>
__device__ __forceinline__ void mbar_wait_n(uint32_t b) {
#pragma unroll 1
    for (int n = 0; n < 4194304; n++) {
        uint32_t ok = 1;
#pragma unroll
        for (int i = 0; i < N; i++) {
            uint32_t d;
            asm volatile("{ .reg .pred p; mbarrier.try_wait.parity.shared::cta.b64 p, [%1], 0; selp.u32 %0, 1, 0, p; }" : "=r"(d) : "r"(b + STEP * i) : "memory");
            ok &= d;
        }
        if (ok) break;
    }
}
__device__ __forceinline__ unsigned ld_epoch(const Exchange* e) { unsigned v; asm volatile("ld.volatile.global.u32 %0, [%1];" : "=r"(v) : "l"(e) : "memory"); return v; }
__device__ __forceinline__ uint32_t now_ns() { uint32_t t; asm volatile("mov.u32 %0, %globaltimer_lo;" : "=r"(t)); return t; }
__device__ __forceinline__ uint32_t mapa(uint32_t addr, uint32_t rank) { uint32_t r; asm("mapa.shared::cluster.u32 %0, %1, %2;" : "=r"(r) : "r"(addr), "r"(rank)); return r; }
__device__ __forceinline__ void bulk_load(uint32_t dst, const void* src, uint32_t bytes, uint32_t bar) {
    asm volatile("cp.async.bulk.shared::cluster.global.mbarrier::complete_tx::bytes [%0], [%1], %2, [%3];" :: "r"(dst), "l"(src), "r"(bytes), "r"(bar) : "memory");
}
__device__ __forceinline__ void bulk_load_both(uint32_t dst, const void* src, uint32_t bytes, uint32_t bar) {
    asm volatile("{ .reg .pred p; elect.sync _|p, 0xffffffff;\n\t@p cp.async.bulk.shared::cluster.global.mbarrier::complete_tx::bytes.multicast::cluster [%0], [%1], %2, [%3], %4; }"
                 :: "r"(dst), "l"(src), "r"(bytes), "r"(bar), "h"((unsigned short)3) : "memory");
}
__device__ __forceinline__ void tma3d(uint32_t dst, const CUtensorMap* tm, int c0, int c1, int c2, uint32_t bar) {
    asm volatile("cp.async.bulk.tensor.3d.shared::cluster.global.mbarrier::complete_tx::bytes [%0], [%1, {%3, %4, %5}], [%2];"
        :: "r"(dst), "l"(tm), "r"(bar), "r"(c0), "r"(c1), "r"(c2) : "memory");
}
__device__ __forceinline__ void tma4d_warp(uint32_t dst, const CUtensorMap* tm, int c2, int c3, uint32_t bar) {
    asm volatile("{ .reg .pred p; elect.sync _|p, 0xffffffff;\n\t@p cp.async.bulk.tensor.4d.shared::cluster.global.mbarrier::complete_tx::bytes [%0], [%1, {%5, %5, %3, %4}], [%2]; }"
        :: "r"(dst), "l"(tm), "r"(bar), "r"(c2), "r"(c3), "r"(0) : "memory");
}
__device__ __forceinline__ void tma5d_both(uint32_t dst, const CUtensorMap* tm, int c0, int c3, uint32_t bar) {
    asm volatile("{ .reg .pred p; elect.sync _|p, 0xffffffff;\n\t@p cp.async.bulk.tensor.5d.shared::cluster.global.mbarrier::complete_tx::bytes.multicast::cluster [%0], [%1, {%3, %5, %5, %4, %5}], [%2], %6; }"
        :: "r"(dst), "l"(tm), "r"(bar), "r"(c0), "r"(c3), "r"(0), "h"((unsigned short)3) : "memory");
}
__device__ __forceinline__ void cluster_next() { asm volatile("barrier.cluster.wait.acquire.aligned;\n\tbarrier.cluster.arrive.relaxed.aligned;" ::: "memory"); }
__device__ __forceinline__ void st_async16(uint32_t dst, uint32_t x, uint32_t y, uint32_t z, uint32_t w, uint32_t bar) {
    asm volatile("st.async.weak.shared::cluster.mbarrier::complete_tx::bytes.v4.b32 [%0], {%1,%2,%3,%4}, [%5];"
                 :: "r"(dst), "r"(x), "r"(y), "r"(z), "r"(w), "r"(bar) : "memory");
}
__device__ __forceinline__ void st_async4(uint32_t dst, uint32_t v, uint32_t bar) {
    asm volatile("st.async.weak.shared::cluster.mbarrier::complete_tx::bytes.b32 [%0], %1, [%2];" :: "r"(dst), "r"(v), "r"(bar) : "memory");
}
__device__ __forceinline__ void bar_sync(int id, int n) { asm volatile("bar.sync %0, %1;" :: "r"(id), "r"(n) : "memory"); }
__device__ __forceinline__ void bar_arrive(int id, int n) { asm volatile("bar.arrive %0, %1;" :: "r"(id), "r"(n) : "memory"); }
__device__ __forceinline__ void cp16(uint32_t dst, const void* src) { asm volatile("cp.async.cg.shared.global [%0], [%1], 16;" :: "r"(dst), "l"(src) : "memory"); }
__device__ __forceinline__ void cp_wait_all() { asm volatile("cp.async.wait_all;" ::: "memory"); }
__device__ __forceinline__ uint32_t ldg16(const void* p) { uint32_t v; asm volatile("ld.global.nc.u16 %0, [%1];" : "=r"(v) : "l"(p)); return v; }
__device__ __forceinline__ uint2 ldg64(const void* p) { uint2 v; asm volatile("ld.global.nc.v2.u32 {%0,%1}, [%2];" : "=r"(v.x), "=r"(v.y) : "l"(p)); return v; }
__device__ __forceinline__ uint4 ldg128(const void* p) { uint4 v; asm volatile("ld.global.nc.v4.u32 {%0,%1,%2,%3}, [%4];" : "=r"(v.x), "=r"(v.y), "=r"(v.z), "=r"(v.w) : "l"(p)); return v; }
__device__ __forceinline__ uint4 ld_gpu128(const void* p) { uint4 v; asm volatile("ld.relaxed.gpu.global.v4.u32 {%0,%1,%2,%3}, [%4];" : "=r"(v.x), "=r"(v.y), "=r"(v.z), "=r"(v.w) : "l"(p) : "memory"); return v; }
__device__ __forceinline__ void st_gpu32(void* p, uint32_t v) { asm volatile("st.relaxed.gpu.global.u32 [%0], %1;" :: "l"(p), "r"(v) : "memory"); }
__device__ __forceinline__ void st_gpu128(void* p, const uint4& v) { asm volatile("st.relaxed.gpu.global.v4.u32 [%0], {%1,%2,%3,%4};" :: "l"(p), "r"(v.x), "r"(v.y), "r"(v.z), "r"(v.w) : "memory"); }

__device__ __forceinline__ void ldsm4(uint32_t a, uint32_t& r0, uint32_t& r1, uint32_t& r2, uint32_t& r3) {
    asm volatile("ldmatrix.sync.aligned.m8n8.x4.shared.b16 {%0,%1,%2,%3}, [%4];" : "=r"(r0), "=r"(r1), "=r"(r2), "=r"(r3) : "r"(a) : "memory");
}
__device__ __forceinline__ void ldsm2(uint32_t a, uint32_t& r0, uint32_t& r1) {
    asm volatile("ldmatrix.sync.aligned.m8n8.x2.shared.b16 {%0,%1}, [%2];" : "=r"(r0), "=r"(r1) : "r"(a) : "memory");
}
__device__ __forceinline__ void ldsm4t(uint32_t a, uint32_t& r0, uint32_t& r1, uint32_t& r2, uint32_t& r3) {
    asm volatile("ldmatrix.sync.aligned.m8n8.x4.trans.shared.b16 {%0,%1,%2,%3}, [%4];" : "=r"(r0), "=r"(r1), "=r"(r2), "=r"(r3) : "r"(a) : "memory");
}
__device__ __forceinline__ uint32_t lds16(uint32_t a) { uint32_t v; asm volatile("ld.shared.u16 %0, [%1];" : "=r"(v) : "r"(a) : "memory"); return v; }
__device__ __forceinline__ uint32_t lds32(uint32_t a) { uint32_t v; asm volatile("ld.shared.u32 %0, [%1];" : "=r"(v) : "r"(a) : "memory"); return v; }
__device__ __forceinline__ uint2 lds64(uint32_t a) { uint2 v; asm volatile("ld.shared.v2.u32 {%0,%1}, [%2];" : "=r"(v.x), "=r"(v.y) : "r"(a) : "memory"); return v; }
__device__ __forceinline__ uint4 lds128(uint32_t a) { uint4 v; asm volatile("ld.shared.v4.u32 {%0,%1,%2,%3}, [%4];" : "=r"(v.x), "=r"(v.y), "=r"(v.z), "=r"(v.w) : "r"(a) : "memory"); return v; }
__device__ __forceinline__ void sts16(uint32_t a, uint32_t v) { asm volatile("st.shared.u16 [%0], %1;" :: "r"(a), "r"(v) : "memory"); }
__device__ __forceinline__ void sts32(uint32_t a, uint32_t v) { asm volatile("st.shared.u32 [%0], %1;" :: "r"(a), "r"(v) : "memory"); }
__device__ __forceinline__ void sts64(uint32_t a, uint32_t x, uint32_t y) { asm volatile("st.shared.v2.u32 [%0], {%1,%2};" :: "r"(a), "r"(x), "r"(y) : "memory"); }
__device__ __forceinline__ void sts128(uint32_t a, uint32_t x, uint32_t y, uint32_t z, uint32_t w) { asm volatile("st.shared.v4.u32 [%0], {%1,%2,%3,%4};" :: "r"(a), "r"(x), "r"(y), "r"(z), "r"(w) : "memory"); }
__device__ __forceinline__ void sts16_if(bool p, uint32_t a, uint32_t v) { asm volatile("{ .reg .pred q; setp.ne.u32 q, %2, 0; @q st.shared.u16 [%0], %1; }" :: "r"(a), "h"((unsigned short)v), "r"((uint32_t)p) : "memory"); }
__device__ __forceinline__ void sts128_if(bool p, uint32_t a, uint32_t x, uint32_t y, uint32_t z, uint32_t w) {
    asm volatile("{ .reg .pred q; setp.ne.u32 q, %5, 0; @q st.shared.v4.u32 [%0], {%1,%2,%3,%4}; }" :: "r"(a), "r"(x), "r"(y), "r"(z), "r"(w), "r"((uint32_t)p) : "memory");
}
__device__ __forceinline__ void stsf(uint32_t a, float v) { asm volatile("st.shared.f32 [%0], %1;" :: "r"(a), "f"(v) : "memory"); }
__device__ __forceinline__ float ldsf(uint32_t a) { float v; asm volatile("ld.shared.f32 %0, [%1];" : "=f"(v) : "r"(a) : "memory"); return v; }

__device__ __forceinline__ void mma_bf(float (&d)[4], uint32_t a0, uint32_t a1, uint32_t a2, uint32_t a3, uint32_t b0, uint32_t b1) {
    asm volatile("mma.sync.aligned.m16n8k16.row.col.f32.bf16.bf16.f32 {%0,%1,%2,%3}, {%4,%5,%6,%7}, {%8,%9}, {%0,%1,%2,%3};"
        : "+f"(d[0]), "+f"(d[1]), "+f"(d[2]), "+f"(d[3]) : "r"(a0), "r"(a1), "r"(a2), "r"(a3), "r"(b0), "r"(b1));
}
__device__ __forceinline__ void widen_bf(float (&d)[4], uint32_t a0, uint32_t a1, uint32_t b) {
    asm volatile("mma.sync.aligned.m16n8k8.row.col.f32.bf16.bf16.f32 {%0,%1,%2,%3}, {%4,%5}, {%6}, {%7,%7,%7,%7};"
        : "=f"(d[0]), "=f"(d[1]), "=f"(d[2]), "=f"(d[3]) : "r"(a0), "r"(a1), "r"(b), "f"(0.f));
}
__device__ __forceinline__ void widen_h(float (&d)[4], const uint32_t (&a)[2], uint32_t b) {
    asm volatile("mma.sync.aligned.m16n8k8.row.col.f32.f16.f16.f32 {%0,%1,%2,%3}, {%4,%5}, {%6}, {%7,%7,%7,%7};"
        : "=f"(d[0]), "=f"(d[1]), "=f"(d[2]), "=f"(d[3]) : "r"(a[0]), "r"(a[1]), "r"(b), "f"(0.f));
}
__device__ __forceinline__ void widen_add_h(float (&d)[4], const uint32_t (&a)[2], uint32_t b, const float (&c)[4]) {
    asm volatile("mma.sync.aligned.m16n8k8.row.col.f32.f16.f16.f32 {%0,%1,%2,%3}, {%4,%5}, {%6}, {%7,%8,%9,%10};"
        : "=f"(d[0]), "=f"(d[1]), "=f"(d[2]), "=f"(d[3]) : "r"(a[0]), "r"(a[1]), "r"(b), "f"(c[0]), "f"(c[1]), "f"(c[2]), "f"(c[3]));
}
__device__ __forceinline__ void mma_h(uint32_t (&d)[2], const uint32_t (&a)[4], uint32_t b0, uint32_t b1) {
    asm volatile("mma.sync.aligned.m16n8k16.row.col.f16.f16.f16.f16 {%0,%1}, {%2,%3,%4,%5}, {%6,%7}, {%0,%1};"
        : "+r"(d[0]), "+r"(d[1]) : "r"(a[0]), "r"(a[1]), "r"(a[2]), "r"(a[3]), "r"(b0), "r"(b1));
}
__device__ __forceinline__ void mma_h_z(uint32_t& d0, uint32_t& d1, const uint32_t (&a)[4], uint32_t b0, uint32_t b1) {
    asm volatile("mma.sync.aligned.m16n8k16.row.col.f16.f16.f16.f16 {%0,%1}, {%2,%3,%4,%5}, {%6,%7}, {%8,%8};"
        : "=r"(d0), "=r"(d1) : "r"(a[0]), "r"(a[1]), "r"(a[2]), "r"(a[3]), "r"(b0), "r"(b1), "r"(0u));
}
__device__ __forceinline__ void mma_h2(uint32_t& d0, uint32_t& d1, const uint32_t (&a)[4], uint32_t b0, uint32_t b1) {
    asm volatile("mma.sync.aligned.m16n8k16.row.col.f16.f16.f16.f16 {%0,%1}, {%2,%3,%4,%5}, {%6,%7}, {%0,%1};"
        : "+r"(d0), "+r"(d1) : "r"(a[0]), "r"(a[1]), "r"(a[2]), "r"(a[3]), "r"(b0), "r"(b1));
}
__device__ __forceinline__ void mma_h_k8(uint32_t& d0, uint32_t& d1, uint32_t a0, uint32_t a1, uint32_t b) {
    asm volatile("mma.sync.aligned.m16n8k8.row.col.f16.f16.f16.f16 {%0,%1}, {%2,%3}, {%4}, {%0,%1};" : "+r"(d0), "+r"(d1) : "r"(a0), "r"(a1), "r"(b));
}
__device__ __forceinline__ void mma_h_k8_z(uint32_t (&d)[2], uint32_t a0, uint32_t a1, uint32_t b) {
    asm volatile("mma.sync.aligned.m16n8k8.row.col.f16.f16.f16.f16 {%0,%1}, {%2,%3}, {%4}, {%5,%5};" : "=r"(d[0]), "=r"(d[1]) : "r"(a0), "r"(a1), "r"(b), "r"(0u));
}
__device__ __forceinline__ uint32_t pack_bf(float lo, float hi) { uint32_t r; asm("cvt.rn.bf16x2.f32 %0, %1, %2;" : "=r"(r) : "f"(hi), "f"(lo)); return r; }
__device__ __forceinline__ uint32_t pack_h(float lo, float hi) { uint32_t r; asm("cvt.rn.f16x2.f32 %0, %1, %2;" : "=r"(r) : "f"(hi), "f"(lo)); return r; }
__device__ __forceinline__ float bf_lo(uint32_t v) { return __uint_as_float(v << 16); }
__device__ __forceinline__ float bf_hi(uint32_t v) { return __uint_as_float(v & 0xffff0000u); }
__device__ __forceinline__ float bf_round(float x) { return __uint_as_float(pack_bf(0.f, x) & 0xffff0000u); }
__device__ __forceinline__ uint32_t hmul2_bf(uint32_t a, uint32_t b) { uint32_t r; asm("mul.rn.bf16x2 %0, %1, %2;" : "=r"(r) : "r"(a), "r"(b)); return r; }
__device__ __forceinline__ uint32_t hadd2_bf(uint32_t a, uint32_t b) { uint32_t r; asm("add.rn.bf16x2 %0, %1, %2;" : "=r"(r) : "r"(a), "r"(b)); return r; }
__device__ __forceinline__ uint32_t hfma2_bf(uint32_t a, uint32_t b, uint32_t c) { uint32_t r; asm("fma.rn.bf16x2 %0, %1, %2, %3;" : "=r"(r) : "r"(a), "r"(b), "r"(c)); return r; }
__device__ __forceinline__ uint32_t hi_mul_bf(uint32_t a, uint32_t b) { uint32_t r; asm("{ .reg .b16 l, h; .reg .b32 t; mov.b32 {l, h}, %1; mov.b32 t, {h, h}; mul.rn.bf16x2 %0, t, %2; }" : "=r"(r) : "r"(a), "r"(b)); return r; }
__device__ __forceinline__ uint32_t lo_fma_bf(uint32_t a, uint32_t b, uint32_t c) { uint32_t r; asm("{ .reg .b16 l, h; .reg .b32 t; mov.b32 {l, h}, %1; mov.b32 t, {l, l}; fma.rn.bf16x2 %0, t, %2, %3; }" : "=r"(r) : "r"(a), "r"(b), "r"(c)); return r; }
__device__ __forceinline__ uint32_t amax2_bf(uint32_t m, uint32_t v) { uint32_t r; asm("max.xorsign.abs.bf16x2 %0, %1, %2;" : "=r"(r) : "r"(m), "r"(v)); return r; }
__device__ __forceinline__ uint32_t amax2_h(uint32_t m, uint32_t v) { uint32_t r; asm("max.xorsign.abs.f16x2 %0, %1, %2;" : "=r"(r) : "r"(m), "r"(v)); return r; }
__device__ __forceinline__ uint32_t hadd(uint32_t a, uint32_t b) { uint32_t r; asm("add.rn.f16x2 %0, %1, %2;" : "=r"(r) : "r"(a), "r"(b)); return r; }
__device__ __forceinline__ uint32_t hsub(uint32_t a, uint32_t b) { uint32_t r; asm("sub.rn.f16x2 %0, %1, %2;" : "=r"(r) : "r"(a), "r"(b)); return r; }
__device__ __forceinline__ uint32_t hsub2(uint32_t a, uint32_t b) { uint32_t r; asm("sub.rn.ftz.f16x2 %0, %1, %2;" : "=r"(r) : "r"(a), "r"(b)); return r; }
__device__ __forceinline__ uint32_t hmul(uint32_t a, uint32_t b) { uint32_t r; asm("mul.rn.f16x2 %0, %1, %2;" : "=r"(r) : "r"(a), "r"(b)); return r; }
__device__ __forceinline__ uint32_t hfma(uint32_t a, uint32_t b, uint32_t c) { uint32_t r; asm("fma.rn.f16x2 %0, %1, %2, %3;" : "=r"(r) : "r"(a), "r"(b), "r"(c)); return r; }
__device__ __forceinline__ uint32_t hfms(uint32_t a, uint32_t b, uint32_t c) { uint32_t r; asm("{ .reg .b32 t; neg.f16x2 t, %3; fma.rn.f16x2 %0, %1, %2, t; }" : "=r"(r) : "r"(a), "r"(b), "r"(c)); return r; }
__device__ __forceinline__ uint32_t warp_max16(uint32_t m) { return __reduce_max_sync(0xffffffffu, max(m & 0x7fffu, (m >> 16) & 0x7fffu)); }
__device__ __forceinline__ float ex2f(float x) { float r; asm("ex2.approx.ftz.f32 %0, %1;" : "=f"(r) : "f"(x)); return r; }

__device__ __forceinline__ float exp_acc(float x) {
    const float t = x * 1.4426950216293335f;
    const float r = fmaf(x, 1.4426950216293335f, -t) + x * 1.9259629911266175e-8f;
    return ex2f(t) * fmaf(r, 0.6931471805599453f, 1.f);
}
__device__ __forceinline__ float sigmoid_f(float x) { return __fdividef(1.f, 1.f + ex2f(-x * 1.4426950408889634f)); }
__device__ __forceinline__ void cexp(float l2, float th, float& zr, float& zi) {
    const float mag = ex2f(l2);
    const float k = (th * 0.15915494309189535f + 12582912.f) - 12582912.f;
    float r = fmaf(-k, 6.2831854820251465f, th);
    r = fmaf(-k, -1.7484555314695172e-7f, r);
    zr = mag * __cosf(r);
    zi = mag * __sinf(r);
}
struct hc { uint32_t re, im; };
__device__ __forceinline__ hc cmul(const hc& a, const hc& b) { return {hfms(a.re, b.re, hmul(a.im, b.im)), hfma(a.re, b.im, hmul(a.im, b.re))}; }
__device__ __forceinline__ hc cmulc(const hc& a, const hc& b) { return {hfma(a.re, b.re, hmul(a.im, b.im)), hfms(a.im, b.re, hmul(a.re, b.im))}; }
struct fc2 { float r[2], i[2]; };
__device__ __forceinline__ void csq(fc2& z) {
#pragma unroll
    for (int m = 0; m < 2; m++) {
        const float r = fmaf(z.r[m], z.r[m], -(z.i[m] * z.i[m]));
        asm("{ .reg .f32 t; mul.f32 t, %0, %1; mul.f32 %0, t, 0f40000000; }" : "+f"(z.i[m]) : "f"(z.r[m]));
        z.r[m] = r;
    }
}
__device__ __forceinline__ hc pk(const fc2& z) { return {pack_h(z.r[0], z.r[1]), pack_h(z.i[0], z.i[1])}; }
__device__ __forceinline__ void csq_conj(fc2& z) {
#pragma unroll
    for (int m = 0; m < 2; m++) {
        const float r = fmaf(z.r[m], z.r[m], -(z.i[m] * z.i[m]));
        asm("{ .reg .f32 t, n; neg.f32 n, %1; mul.f32 t, %0, n; mul.f32 %0, t, 0f40000000; }" : "+f"(z.i[m]) : "f"(z.r[m]));
        z.r[m] = r;
    }
}

struct Powers { hc C, z1, z2, z4, c8, c16, c32, c64, z128, z256, z512, z1024; };
__device__ __forceinline__ void kg_powers(Powers& q, uint32_t la, uint32_t ai, uint32_t cr, uint32_t ci, float dt, float cf) {
    fc2 z, y;
    const float dtl = -dt * 1.4426950408889634f;
    const uint32_t eb = pack_bf(ex2f(bf_lo(la) * 1.4426950408889634f), ex2f(bf_hi(la) * 1.4426950408889634f));
    const float l2[2] = {bf_lo(eb) * dtl, bf_hi(eb) * dtl}, th[2] = {bf_lo(ai) * dt, bf_hi(ai) * dt};
#pragma unroll
    for (int m = 0; m < 2; m++) { cexp(l2[m], th[m], z.r[m], z.i[m]); cexp(l2[m] * 128.f, th[m] * 128.f, y.r[m], y.i[m]); }
    q.C.re = pack_h(bf_lo(cr) * cf, bf_hi(cr) * cf);
    q.C.im = pack_h(bf_lo(ci) * cf, bf_hi(ci) * cf);
    q.z1 = pk(z); csq(z); q.z128 = pk(y); csq(y);
    q.z2 = pk(z); csq(z); q.z256 = pk(y); csq(y);
    q.z4 = pk(z); csq_conj(z); q.z512 = pk(y); csq(y);
    q.c8 = pk(z); csq(z); q.z1024 = pk(y);
    q.c16 = pk(z); csq(z);
    q.c32 = pk(z); csq(z);
    q.c64 = pk(z);
}
struct Rows { hc ta[8], tb[8], tc[8], pp[8]; };
#define PUT(a0, a1, row, a, b) sts128((((row) & 1) ? (a1) : (a0)) + (row) * 512, (a).re, (a).im, (b).re, (b).im)
template <bool FIRST>
__device__ __forceinline__ void kg_rows(Rows& w, const Powers& q, uint32_t t0, uint32_t t1, uint32_t u0, uint32_t u1, uint32_t uc, uint32_t zr, uint32_t (&Rl)[2]) {
    w.ta[0] = q.C; w.ta[1] = cmul(q.C, q.z1); w.ta[2] = cmul(q.C, q.z2); w.ta[4] = cmul(q.C, q.z4); w.tb[0] = cmul(q.C, q.z256); w.tb[4] = cmul(q.C, q.z512);
    PUT(t0, t1, 0, w.ta[0], w.tb[0]); PUT(t0, t1, 4, w.ta[4], w.tb[4]);
    w.tb[1] = cmul(w.ta[2], q.z256); w.tb[2] = cmul(w.ta[4], q.z256);
    PUT(t0, t1, 1, w.ta[1], w.tb[1]); PUT(t0, t1, 2, w.ta[2], w.tb[2]);
    w.ta[3] = cmul(w.ta[1], q.z2); w.ta[6] = cmul(w.ta[2], q.z4); w.ta[5] = cmul(w.ta[1], q.z4); w.tb[5] = cmul(w.ta[4], q.z512); w.tb[6] = cmul(w.tb[0], q.z512);
    PUT(t0, t1, 5, w.ta[5], w.tb[5]); PUT(t0, t1, 6, w.ta[6], w.tb[6]);
    w.tb[3] = cmul(w.ta[6], q.z256); w.ta[7] = cmul(w.ta[3], q.z4); w.tb[7] = cmul(w.tb[2], q.z512);
    PUT(t0, t1, 3, w.ta[3], w.tb[3]); PUT(t0, t1, 7, w.ta[7], w.tb[7]);
    sts64(uc, q.c64.re, q.c64.im);
    w.pp[0] = hc{0x3C003C00u ^ zr, zr}; w.pp[1] = q.c8; w.pp[2] = q.c16; w.pp[4] = q.c32;
    w.tc[0] = cmul(q.C, q.z1024); w.pp[3] = cmul(q.c8, q.c16); w.pp[5] = cmul(q.c8, q.c32); w.pp[6] = cmul(q.c16, q.c32);
    w.tc[2] = cmul(w.tc[0], q.z128); w.tc[4] = cmul(w.tc[0], q.z256); w.tc[1] = cmul(w.tc[0], q.z512); w.pp[7] = cmul(w.pp[3], q.c32);
    PUT(u0, u1, 0, w.tc[0], w.pp[0]); PUT(u0, u1, 1, w.tc[1], w.pp[1]); PUT(u0, u1, 2, w.tc[2], w.pp[2]); PUT(u0, u1, 4, w.tc[4], w.pp[4]);
    w.tc[6] = cmul(w.tc[2], q.z256); w.tc[3] = cmul(w.tc[2], q.z512); w.tc[5] = cmul(w.tc[4], q.z512);
    PUT(u0, u1, 3, w.tc[3], w.pp[3]); PUT(u0, u1, 5, w.tc[5], w.pp[5]); PUT(u0, u1, 6, w.tc[6], w.pp[6]);
    w.tc[7] = cmul(w.tc[6], q.z512);
    PUT(u0, u1, 7, w.tc[7], w.pp[7]);
    const uint32_t last = hfms(w.tc[0].re, q.z1024.re, hmul(w.tc[0].im, q.z1024.im));
    if (FIRST) mma_h_k8_z(Rl, 0x3C003C00u - zr, 0x3C003C00u + zr, last); else mma_h_k8(Rl[0], Rl[1], 0x3C003C00u - zr, 0x3C003C00u + zr, last);
}
#undef PUT
template <bool FIRST>
__device__ __forceinline__ void kg_products(uint32_t rt0, uint32_t rt1, uint32_t ru0, uint32_t ru1, uint32_t rc, uint32_t zr, uint32_t done, int lane,
                                            uint32_t (&Ra)[2][2], uint32_t (&Rb)[2][2], uint32_t (&Rc)[2]) {
    uint4 q1[8], q2[8], cw[8];
    if (!FIRST && KD_ORDER) {
#pragma unroll
        for (int ks = 0; ks < 8; ks++) { q2[ks] = lds128(((ks & 1) ? ru1 : ru0) + (ks >> 1) * 128); if (!(ks & 1)) cw[ks] = lds128(rc + ks * 32); if (ks < 2) q1[ks] = lds128(ks ? rt1 : rt0); }
#pragma unroll
        for (int ks = 2; ks < 8; ks++) q1[ks] = lds128(((ks & 1) ? rt1 : rt0) + (ks >> 1) * 128);
    } else
#pragma unroll
    for (int ks = 0; ks < 8; ks++) {
        q2[ks] = lds128(((ks & 1) ? ru1 : ru0) + (ks >> 1) * 128); if (!(ks & 1)) cw[ks] = lds128(rc + ks * 32); q1[ks] = lds128(((ks & 1) ? rt1 : rt0) + (ks >> 1) * 128);
    }
#pragma unroll
    for (int ks = 0; ks < 8; ks++) {
        const hc p0 = {q2[ks].z, q2[ks].w}, u = (ks & 1) ? hc{cw[ks & 6].z, cw[ks & 6].w} : hc{cw[ks].x, cw[ks].y};
        const hc p1 = cmul(p0, u), p2 = cmul(p1, u), p3 = cmul(p2, u);

        const uint32_t qa[4] = {p0.re ^ zr, p1.re, p0.im ^ zr, p1.im}, qb[4] = {p2.re, p3.re, p2.im, p3.im};
        if (!FIRST && ks == KD_AT) {
            uint32_t all = zr;
#pragma unroll
            for (int i = KD_AT; i < 8; i++) all &= q2[i].x & cw[i & 6].x;
            __syncwarp();
            if (lane == 0) mbar_arrive(done + all);
        }
        if (FIRST && ks == 0) {
            mma_h_z(Rc[0], Rc[1], qa, q2[ks].x, q2[ks].y); mma_h_z(Ra[0][0], Ra[0][1], qa, q1[ks].x, q1[ks].y); mma_h_z(Rb[0][0], Rb[0][1], qa, q1[ks].z, q1[ks].w);
            mma_h_z(Ra[1][0], Ra[1][1], qb, q1[ks].x, q1[ks].y); mma_h_z(Rb[1][0], Rb[1][1], qb, q1[ks].z, q1[ks].w);
        } else {
            mma_h(Rc, qa, q2[ks].x, q2[ks].y); mma_h(Ra[0], qa, q1[ks].x, q1[ks].y); mma_h(Rb[0], qa, q1[ks].z, q1[ks].w);
            mma_h(Ra[1], qb, q1[ks].x, q1[ks].y); mma_h(Rb[1], qb, q1[ks].z, q1[ks].w);
        }
    }
}
__device__ __forceinline__ void kernel_gen(const uint2& la, const uint2& ai, const uint2& cr, const uint2& ci, float dt, float cf, uint32_t TB, uint32_t UB, uint32_t done,
                                           int lane, uint32_t zr, uint32_t (&Ra)[2][2], uint32_t (&Rb)[2][2], uint32_t (&Rc)[2], uint32_t (&Rl)[2]) {
    const int g = lane >> 2, t = lane & 3;
    const uint32_t w0 = lane << 4, w1 = w0 ^ 64, r0 = g * 512 + (((g & 1) << 6) | (t << 4)), r1 = r0 ^ 64;
    const uint32_t t0 = TB + w0, t1 = TB + w1, u0 = UB + w0, u1 = UB + w1;
    const uint32_t uc = UB + 4096 + (lane >> 3) * 64 + t * 16 + (lane & 4) * 2;
    Powers p0, p1;
    Rows w;
    kg_powers(p0, la.x, ai.x, cr.x, ci.x, dt, cf);
    kg_rows<true>(w, p0, t0, t1, u0, u1, uc, zr, Rl);
    kg_powers(p1, la.y, ai.y, cr.y, ci.y, dt, cf);
    __syncwarp();
    kg_products<true>(TB + r0, TB + r1, UB + r0, UB + r1, UB + 4096 + t * 16, zr, done, lane, Ra, Rb, Rc);
    __syncwarp();
    asm volatile("barrier.cluster.wait.acquire.aligned;" ::: "memory");
    kg_rows<false>(w, p1, t0, t1, u0, u1, uc, zr, Rl);
    __syncwarp();
    kg_products<false>(TB + r0, TB + r1, UB + r0, UB + r1, UB + 4096 + t * 16, zr, done, lane, Ra, Rb, Rc);
    __syncwarp();
}

template <int V> struct IC { static constexpr int value = V; };

#define LANE_VARS \
    int tid_; asm volatile("mov.u32 %0, %%tid.x;" : "=r"(tid_)); \
    [[maybe_unused]] const int lane = tid_ & 31, warp = (tid_ >> 5) - MAIN_W0, g = lane >> 2, t = lane & 3, mi = lane >> 3, r = lane & 7; \
    [[maybe_unused]] const uint32_t TB = sb + OFF_TAB + warp * T_CH, UB = sb + OFF_U + warp * U_CH; \
    [[maybe_unused]] const bool lead = (tid_ == 32 * MAIN_W0)

#define FENCE() do { if (zr) asm volatile("exit;"); } while (0)
template <int ORD>
__device__ __forceinline__ void stream(uint32_t (&D)[8][2], const uint32_t (&Q)[2][4], const uint32_t (&V)[8][2]) {
    if (ORD == 0) {
#pragma unroll
        for (int J = 0; J < 8; J++) mma_h(D[J], Q[0], V[J][0], V[J][1]);
#pragma unroll
        for (int J = 1; J < 8; J++) mma_h(D[J], Q[1], V[J - 1][0], V[J - 1][1]);
    } else if (ORD == 1) {
#pragma unroll
        for (int J = 1; J < 8; J++) mma_h(D[J], Q[1], V[J - 1][0], V[J - 1][1]);
#pragma unroll
        for (int J = 0; J < 8; J++) mma_h(D[J], Q[0], V[J][0], V[J][1]);
    } else {
#pragma unroll
        for (int J = 7; J >= 0; J--) mma_h(D[J], Q[0], V[J][0], V[J][1]);
#pragma unroll
        for (int J = 7; J >= 1; J--) mma_h(D[J], Q[1], V[J - 1][0], V[J - 1][1]);
    }
}
__device__ __forceinline__ void dense_step(uint32_t (&M)[8][2], uint32_t (&Ye)[8][2], uint32_t (&Yo)[8][2], uint32_t (&X)[8][2],
                                           uint32_t (&F)[8][2], uint32_t (&Bq)[2][4], uint32_t ua, uint32_t ta, uint32_t zr) {
    uint32_t E[8][2], A[2][4], S[2][4], G[8][2], Bn[2][2];
    auto load_e = [&]() {
#pragma unroll
        for (int jp = 0; jp < 4; jp++) ldsm4(ua + jp * 256, E[2 * jp][0], E[2 * jp][1], E[2 * jp + 1][0], E[2 * jp + 1][1]);
    };
    auto load_a = [&]() {
#pragma unroll
        for (int h = 0; h < 2; h++) {
            A[h][0] = A_REUSE ? Bq[h][3] ^ zr : lds32(ta + 1024 * h); A[h][1] = lds32(ta + 1024 * h + 32); A[h][3] = lds32(ta + 1024 * h + 64);
            A[h][2] = (DV & 8) ? lds32(ta + 1024 * h + 32 + zr) : A[h][1] ^ zr;
        }
    };
    if (DV & 1) { load_a(); load_e(); } else { load_e(); load_a(); }
    if (DV & 2) {
#pragma unroll
        for (int h = 0; h < 2; h++) { Bn[h][0] = lds32(ta + 1024 * h + 96); Bn[h][1] = lds32(ta + 1024 * h + 128); }
        stream<SO % 3>(Ye, Bq, F);
#pragma unroll
        for (int h = 0; h < 2; h++) { S[h][0] = hadd(A[h][0], A[h][3]); S[h][1] = hadd(A[h][1], Bn[h][0]); S[h][2] = hadd(A[h][2], Bn[h][0]); S[h][3] = hadd(A[h][3], Bn[h][1]); }
#pragma unroll
        for (int J = 0; J < 8; J++) { G[J][0] = hsub(X[J][0], E[J][0]); G[J][1] = hsub(X[J][1], E[J][1]); }
#pragma unroll
        for (int jp = 0; jp < 4; jp++) ldsm4(ua + 2 * U_PL + jp * 256 - 16, X[2 * jp][0], X[2 * jp][1], X[2 * jp + 1][0], X[2 * jp + 1][1]);
        if (DV & 4) FENCE();
        stream<(SO / 9) % 3>(M, S, E);
#pragma unroll
        for (int h = 0; h < 2; h++) { Bq[h][0] = A[h][3] ^ zr; Bq[h][1] = Bn[h][0]; Bq[h][2] = Bn[h][0] ^ zr; Bq[h][3] = Bn[h][1]; }
#pragma unroll
        for (int J = 0; J < 8; J++) { F[J][0] = hsub(X[J][0], E[J][0]); F[J][1] = hsub(X[J][1], E[J][1]); }
        stream<(SO / 3) % 3>(Yo, A, G);
        return;
    }
    stream<SO % 3>(Ye, Bq, F);
#pragma unroll
    for (int J = 0; J < 8; J++) { G[J][0] = hsub(X[J][0], E[J][0]); G[J][1] = hsub(X[J][1], E[J][1]); }
    if (DV & 4) FENCE();
#pragma unroll
    for (int jp = 0; jp < 4; jp++) ldsm4(ua + 2 * U_PL + jp * 256 - 16, X[2 * jp][0], X[2 * jp][1], X[2 * jp + 1][0], X[2 * jp + 1][1]);
#pragma unroll
    for (int h = 0; h < 2; h++) { Bq[h][1] = lds32(ta + 1024 * h + 96); Bq[h][3] = lds32(ta + 1024 * h + 128); Bq[h][0] = A[h][3] ^ zr; Bq[h][2] = Bq[h][1] ^ zr; }
    stream<(SO / 3) % 3>(Yo, A, G);
#pragma unroll
    for (int h = 0; h < 2; h++)
#pragma unroll
        for (int i = 0; i < 4; i++) S[h][i] = hadd(A[h][i], Bq[h][i]);
    if (DV & 16) FENCE();
    stream<(SO / 9) % 3>(M, S, E);
#pragma unroll
    for (int J = 0; J < 8; J++) { F[J][0] = hsub(X[J][0], E[J][0]); F[J][1] = hsub(X[J][1], E[J][1]); }
}

__device__ __forceinline__ int group_tables(uint32_t TB, int lane) {
    const int g = lane >> 2, t = lane & 3;
    const uint4 b4 = lds128(TB + T_R2 + 16 * lane), c4 = lds128(TB + T_R2 + 512 + 16 * lane);
    uint32_t vb[4] = {b4.x, b4.y, b4.z, b4.w}, vc[2] = {c4.x, c4.y};
    const uint32_t k1024 = __shfl_sync(0xffffffffu, vc[0], 0) & 0xffffu;
    uint32_t kl = hadd(c4.z, __byte_perm(c4.z, 0, 0x1032));
    kl = hadd(kl, __shfl_xor_sync(0xffffffffu, kl, 1)); kl = hadd(kl, __shfl_xor_sync(0xffffffffu, kl, 2));
#pragma unroll
    for (int i = 0; i < 3; i++) sts128(TB + T_R2 + 16 * lane + 512 * i, 0, 0, 0, 0);
    if (lane == 2) vb[0] &= 0xffff0000u;
    if (lane == 0) vc[0] &= 0xffff0000u;
    if (lane == 4) vc[0] = hsub(vc[0], k1024);
    __syncwarp();
    if (t >= 2) {
        const uint32_t g1 = TB + T_R2 + T2_S * (g & 3) + 8 * (8 * t - 10 + (g >> 2));
        const uint32_t g0 = TB + T_R2 + T2_S * ((g - 1) & 3) + 8 * (8 * t - 10 + ((g - 1) >> 2)) + 4;
#pragma unroll
        for (int i = 0; i < 4; i++) {
            sts16(g0 + 16 * i, vb[i]); sts16(g0 + 16 * i + 10, vb[i]);
            sts16(g1 + 16 * i, vb[i] >> 16); sts16(g1 + 16 * i + 10, vb[i] >> 16);
        }
    }
    const uint32_t g3 = TB + T_R3 + T3_S * (((g - 1) >> 1) & 1) + 8 * (7 + 4 * t + ((g - 1) >> 2)) + 4 * ((g - 1) & 1);
#pragma unroll
    for (int i = 0; i < 2; i++) {
        sts16(g3 + 16 * i, vc[i]); sts16(g3 + 16 * i + 10, vc[i]);
        sts16(g3 + 16 * i + 128, vc[i] >> 16); sts16(g3 + 16 * i + 138, vc[i] >> 16);
    }
    const uint32_t g4 = (uint32_t)(((uint64_t)(T_R3 + T3_S + 308) << 48 | (uint64_t)(T_R2 + 180) << 32 | (T_R2 + 176) << 16 | (T_R2 + 3 * T2_S + 172)) >> (8 * (lane & 6))) & 0xffffu;
    sts16(TB + g4 + 10 * (lane & 1), (lane & 7) < 6 ? k1024 : kl);
    return (int)c4.w;
}

struct Chunks { uint32_t c3, c2, c1, c0, cm1, cm2, cm3, cm4, d2, d1, d0, dm1, em2, em3; };
__device__ __forceinline__ void convolve(uint32_t sb, int h, uint32_t zr, int pr, bf16* out, const CUtensorMap* tm_o DBG_PARAMS) {
    const uint32_t bars = sb + M_BARS;
    uint32_t M[8][2], Ye[8][2], Yo[8][2], F[8][2], Bq[2][4];
    {
        LANE_VARS;
        uint32_t X[8][2];
        uint32_t ua = UB + ((mi & 1) ? 0 : U_PL) + (8 + 8 * (mi >> 1) + r) * 16, ta = TB + 4 * (1 + g + 2 * t);
        uint32_t A[3][4], S[2][4];
        __syncwarp();
#pragma unroll
        for (int h2 = 0; h2 < 3; h2++) { A[h2][0] = lds32(ta + 1024 * h2); A[h2][1] = lds32(ta + 1024 * h2 + 32); A[h2][3] = lds32(ta + 1024 * h2 + 64); A[h2][2] = A[h2][1] ^ zr; }
#pragma unroll
        for (int h2 = 0; h2 < 2; h2++) {
            Bq[h2][1] = lds32(ta + 1024 * h2 + 96); Bq[h2][3] = lds32(ta + 1024 * h2 + 128); Bq[h2][0] = A[h2][3] ^ zr; Bq[h2][2] = Bq[h2][1] ^ zr;
#pragma unroll
            for (int i = 0; i < 4; i++) S[h2][i] = hadd(A[h2][i], Bq[h2][i]);
        }
        const uint32_t an = A[0][0] ^ zr, un = UB + (9 + lane) * 16;
        if (lead) TSTAMP(10);
        mbar_spin(bars + 8 * B_U);
        if (lead) { TSTAMP(3); CSTAMP(27); }
        uint32_t E[8][2], N[8], G[8][2];
#pragma unroll
        for (int jp = 0; jp < 4; jp++) ldsm4(ua + jp * 256, E[2 * jp][0], E[2 * jp][1], E[2 * jp + 1][0], E[2 * jp + 1][1]);
#pragma unroll
        for (int jp = 0; jp < 4; jp++) ldsm4(ua + 2 * U_PL + jp * 256, X[2 * jp][0], X[2 * jp][1], X[2 * jp + 1][0], X[2 * jp + 1][1]);
        ldsm4(un, N[0], N[1], N[2], N[3]); ldsm4(un + 512, N[4], N[5], N[6], N[7]);
#pragma unroll
        for (int J = 0; J < 8; J++) mma_h_z(M[J][0], M[J][1], S[0], E[J][0], E[J][1]);
#pragma unroll
        for (int J = 1; J < 8; J++) mma_h(M[J], S[1], E[J - 1][0], E[J - 1][1]);
#pragma unroll
        for (int J = 2; J < 8; J++) mma_h(M[J], A[2], E[J - 2][0], E[J - 2][1]);
        if (FENCES & 32) FENCE();
#pragma unroll
        for (int J = 0; J < 8; J++) mma_h_k8_z(Ye[J], zr, an, X[J][1]);
#pragma unroll
        for (int J = 0; J < 8; J++) mma_h_k8_z(Yo[J], zr, an, N[J]);
#pragma unroll
        for (int J = 0; J < 8; J++) { G[J][0] = hsub(X[J][0], E[J][0]); G[J][1] = hsub(X[J][1], E[J][1]); }
#pragma unroll
        for (int jp = 0; jp < 4; jp++) ldsm4(ua + 2 * U_PL + jp * 256 - 16, X[2 * jp][0], X[2 * jp][1], X[2 * jp + 1][0], X[2 * jp + 1][1]);
#pragma unroll
        for (int J = 0; J < 8; J++) mma_h(Yo[J], A[0], G[J][0], G[J][1]);
#pragma unroll
        for (int J = 1; J < 8; J++) mma_h(Yo[J], A[1], G[J - 1][0], G[J - 1][1]);
#pragma unroll
        for (int J = 2; J < 8; J++) mma_h(Yo[J], A[2], G[J - 2][0], G[J - 2][1]);
#pragma unroll
        for (int J = 0; J < 8; J++) { F[J][0] = hsub(X[J][0], E[J][0]); F[J][1] = hsub(X[J][1], E[J][1]); }
#pragma unroll kDenseUnroll
        for (int k = 1; k < 8; k++) {
            ua -= 16; ta += 128;
            dense_step(M, Ye, Yo, X, F, Bq, ua, ta, zr);
        }
    }
    mbar_wait_n<2, 8>(bars + 8 * B_TD);
    LANE_VARS;
    if (lead) { TSTAMP(4); CSTAMP(28); }
    __syncwarp();
    const uint32_t idh = (g == 2 * t) ? 0x3C00u : (g == 2 * t + 1) ? 0x3C000000u : 0u;
    const uint32_t sbr = mapa(sb, h ^ 1);
    const uint32_t yl = TB + lane * 16, yr = sbr + (h ? ALT0 : ALT1) + A_YIN + warp * Y_CH + lane * 16;
    const uint32_t ys = lds32(sb + M_SC + (8 * h + warp) * 4);
    uint32_t ea[4];
    auto finish = [&](int J) {
        float m[4], e[4], o[4];
        widen_h(m, M[J], idh); widen_add_h(e, Ye[J], idh, m); widen_add_h(o, Yo[J], idh, m);
        const uint32_t y[4] = {hmul2_bf(pack_bf(e[0], e[2]), ys), hmul2_bf(pack_bf(o[0], o[2]), ys), hmul2_bf(pack_bf(e[1], e[3]), ys), hmul2_bf(pack_bf(o[1], o[3]), ys)};
        if (!(J & 1)) {
#pragma unroll
            for (int i = 0; i < 4; i++) ea[i] = y[i];
        } else {
            st_async16(yr + (J >> 1) * 512, h ? ea[0] : y[0], h ? ea[1] : y[1], h ? ea[2] : y[2], h ? ea[3] : y[3], sbr + M_BARS + 8 * (B_Y + (J >> 1)));
            sts128(yl + (J >> 1) * 512, h ? y[0] : ea[0], h ? y[1] : ea[1], h ? y[2] : ea[2], h ? y[3] : ea[3]);
            __syncwarp();
            if (lane == 0) mbar_arrive(bars + 8 * (B_Y + (J >> 1)));
        }
    };
    const uint32_t a1 = UB + (3 - mi) * U_PL + (8 + r) * 16;
    const uint32_t a2 = UB + ((2 - mi) & 3) * U_PL + (8 + r - (mi == 3)) * 16;
    const uint32_t a3 = UB + (2 - (mi & 1)) * U_PL + (7 + r) * 16;
    const uint32_t bt = sb + OFF_BAND + 4 * (32 + g + 2 * t);
    auto load3 = [&](Chunks& u, int j) { ldsm4(a2 + j * 128, u.d2, u.d1, u.d0, u.dm1); ldsm4(a1 + j * 128, u.c3, u.c2, u.c1, u.c0); ldsm2(a3 + j * 128, u.em2, u.em3); };
    auto load2 = [&](Chunks& u, int j) {
        if (DUP_MOV == 0) load3(u, j);
        else { ldsm4(a1 + j * 128, u.c3, u.c2, u.c1, u.c0); if (DUP_MOV == 1) ldsm4(a2 + j * 128, u.d2, u.d1, u.d0, u.dm1); }
        ldsm4(a1 + j * 128 - 16, u.cm1, u.cm2, u.cm3, u.cm4);
        if (DUP_MOV >= 1) { u.em2 = u.cm2 ^ zr; u.em3 = u.cm3 ^ zr; }
        if (DUP_MOV >= 2) { u.d2 = u.c2 ^ zr; u.d1 = u.c1 ^ zr; u.d0 = u.c0 ^ zr; u.dm1 = u.cm1 ^ zr; }
    };
    Chunks u;
    uint32_t B35[4];
    uint2 Q[4][3], QS[2][3];
    {
        const uint32_t f7 = lds32(bt + 768 - 36), g7 = lds32(bt + 768 - 4), f9 = lds32(bt + 1024 - 32), g9 = lds32(bt + 1024), h9 = lds32(bt + 1024 + 32);
        const uint32_t f1 = hmul(lds32(bt - 28), lds16(TB + T_R2 + 176) * 0x10001u);
        load3(u, 0);
        const uint32_t tq = TB + T_R3 + 8 * (7 + g - 2 * t);
        uint2 Q0[4], Q1[4], Q2[4];
#pragma unroll
        for (int i = 0; i < 4; i++) { Q0[i] = lds64(tq + 64 * i); Q1[i] = lds64(tq + T3_S + 64 * i); Q2[i] = lds64(tq + T3_S - 8 + 64 * i); }
#pragma unroll
        for (int J = 0; J < 8; J++) mma_h(Ye[J], Bq[0], F[J][0], F[J][1]);
#pragma unroll
        for (int J = 1; J < 8; J++) mma_h(Ye[J], Bq[1], F[J - 1][0], F[J - 1][1]);
        const uint32_t B7[4] = {zr, f7, f7 ^ zr, g7}, B9a[4] = {zr + zr, f9, f9 ^ zr, g9}, B9b[4] = {g9 ^ zr, h9, h9 ^ zr, zr * 3}, B1[4] = {zr * 5, f1, f1 ^ zr, zr * 7};
        const uint32_t g7b = g7 ^ zr, z7 = zr * 9;
        if (FENCES & 1) FENCE();
        uint32_t WE[2][4], WO[2][4];
#pragma unroll
        for (int j = 0; j < 5; j++) {
            uint32_t (&we)[4] = WE[j & 1], (&wo)[4] = WO[j & 1], (&pe)[4] = WE[~j & 1], (&po)[4] = WO[~j & 1];
            if (j == 3) {
                const uint32_t t2 = TB + T_R2 + 8 * (6 + g - 2 * t);
                B35[0] = lds32(bt + 256 - 28); B35[1] = lds32(bt + 512 - 40); B35[2] = lds32(bt + 256 + 4); B35[3] = lds32(bt + 512 - 8);
#pragma unroll
                for (int i = 0; i < 3; i++)
#pragma unroll
                    for (int s = 0; s < 4; s++) Q[s][i] = lds64(t2 + T2_S * s + 64 * i);
            }
            if (j < 4) {
                mma_h_z(we[2], we[3], B9a, u.d0, u.dm1); mma_h_z(wo[2], wo[3], B9a, u.d2, u.d1);
                mma_h_z(we[0], we[1], B7, u.c1, u.c0); mma_h_z(wo[0], wo[1], B7, u.c3, u.c2);
            }
            if (j == 0) { finish(0); finish(1); }
#pragma unroll
            for (int i = 0; i < 5 - j && j > 0; i++) { mma_h(Ye[j + 3 + i], pe, Q0[i].x, Q0[i].y); mma_h(Yo[j + 3 + i], pe, Q1[i].x, Q1[i].y); }
            if (j < 4) {
                mma_h2(we[2], we[3], B9b, u.em2, u.em3); mma_h2(wo[2], wo[3], B9b, u.d0, u.dm1);
                mma_h_k8(we[0], we[1], g7b, z7, u.dm1); mma_h_k8(wo[0], wo[1], g7b, z7, u.c1);
                mma_h(Ye[j + 4], B1, u.d0, u.dm1); mma_h(Yo[j + 4], B1, u.d2, u.d1);
                if (j < 3) load3(u, j + 1); else load2(u, 0);
            }
#pragma unroll
            for (int i = 0; i < 5 - j && j > 0; i++) { mma_h(Ye[j + 3 + i], po, Q2[i].x, Q2[i].y); mma_h(Yo[j + 3 + i], po, Q0[i].x, Q0[i].y); }
            if (j == 3) {
#pragma unroll
                for (int i = 0; i < 3; i++)
#pragma unroll
                    for (int s = 0; s < 2; s++) { QS[s][i].x = hadd(Q[s][i].x, Q[s + 2][i].x); QS[s][i].y = hadd(Q[s][i].y, Q[s + 2][i].y); }
            }
            if (j < 3 ? ((FENCES & 2) || (j == 2 && (FENCES & 4))) : (j == 4 && (FENCES & 8))) FENCE();
        }
    }
    uint32_t xo, go, ya, sel, any, wu, oo;
    auto mix_setup = [&]() {
        LANE_VARS;
        const int pos = 2 * (warp & 3) + (t >> 1);
        xo = sb + OFF_S + h * 32768 + (warp & 3) * 2048 + (warp >> 2) * 1024 + (g >> 1) * 128 + (t >> 1) * 64 + (g & 1) * 32 + (((t ^ (g >> 1)) & 1) << 4);
        go = sb + OFF_GP + (8 * pos + g) * 64 + ((warp >> 2) ^ (g >> 1) ^ (2 * (t & 2))) * 8;
        const int ch = 2 * mi + (r & 1);
        ya = sb + ((((r >> 1) & 1) == h) ? OFF_TAB + ch * T_CH : (h ? ALT1 : ALT0) + A_YIN + ch * Y_CH) + (8 * (warp & 3) + (r & 4) + 2 * (warp >> 2)) * 16;
        sel = lds16(sb + M_BMAP + (8 * warp + g) * 2);
        any = __reduce_or_sync(0xffffffffu, sel);
        sel >>= t >> 1;
        oo = (128 * (warp >> 2) + 8 * g + pos) * D_ + 8 * (t & 1);
        wu = __shfl_sync(0xffffffffu, warp, 0);
    };
    struct MixIn { uint32_t gp[2]; uint4 e[2]; };
    auto mix_load = [&](MixIn& q, int J) {
        const uint2 g2 = lds64(go ^ (16 * J));
        q.gp[0] = g2.x; q.gp[1] = g2.y;
#pragma unroll
        for (int k = 0; k < 2; k++) {
            const uint4 x = lds128(xo + J * 8192 + k * 512);
            q.e[k] = make_uint4(hi_mul_bf(q.gp[k], x.x), hi_mul_bf(q.gp[k], x.y), hi_mul_bf(q.gp[k], x.z), hi_mul_bf(q.gp[k], x.w));
        }
    };
    auto mix_calc = [&](MixIn& q, int J) {
#pragma unroll
        for (int k = 0; k < 2; k++) {
            uint32_t y[4];
            ldsm4t(ya + J * 512 + k * 16, y[0], y[1], y[2], y[3]);
            q.e[k] = make_uint4(lo_fma_bf(q.gp[k], y[0], q.e[k].x), lo_fma_bf(q.gp[k], y[1], q.e[k].y), lo_fma_bf(q.gp[k], y[2], q.e[k].z), lo_fma_bf(q.gp[k], y[3], q.e[k].w));
            if (J < 2) sts128_if(!((sel >> (4 * J + 2 * k)) & 1u), xo + J * 8192 + k * 512, q.e[k].x, q.e[k].y, q.e[k].z, q.e[k].w);
        }
    };
    auto mix_send = [&](const MixIn& q, int J) {
        if (J >= STG_FROM || (J >= 2 && ((any >> (4 * J)) & 15u))) {
#pragma unroll
            for (int k = 0; k < 2; k++) if (!((sel >> (4 * J + 2 * k)) & 1u)) *(uint4*)(out + (size_t)(512 * J + 256 * h + 64 * k) * D_ + 16 * pr + oo) = q.e[k];
        } else {
#pragma unroll
            for (int k = 0; k < 2 && J >= 2; k++) sts128(xo + J * 8192 + k * 512, q.e[k].x, q.e[k].y, q.e[k].z, q.e[k].w);
            asm volatile("fence.proxy.async.shared::cta;" ::: "memory");
            __syncwarp();
            asm volatile("{ .reg .pred p; elect.sync _|p, 0xffffffff;\n\t@p cp.async.bulk.tensor.5d.global.shared::cta.bulk_group [%0, {%2, %3, %3, %4, %5}], [%1]; }"
                         :: "l"(tm_o), "r"(sb + OFF_S + h * 32768 + J * 8192 + (wu & 3) * 2048 + (wu >> 2) * 1024),
                            "r"(16 * pr), "r"(0), "r"(32 * J + 16 * h + 8 * (wu >> 2)), "r"(wu & 3) : "memory");
        }
    };
    MixIn q, q2, q3;
    const uint32_t zq = zr + zr;
#pragma unroll
    for (int j = 0; j < 6; j++) {
        if (j == SEND0_AT) mix_send(q, 0);
        if (j == SEND1_AT) mix_send(q, 1);
        if (j == MIX0_AT) mbar_wait_n<2, 8 * (B_Y - B_G)>(bars + 8 * B_G);
        else if (j == MIX1_AT) mbar_spin(bars + 8 * (B_Y + 1));
        else if (j > 0 && (FENCES & 16)) FENCE();
        uint32_t H[7][2];
        mma_h_z(H[3][0], H[3][1], B35, u.d0, u.dm1); mma_h_z(H[4][0], H[4][1], B35, u.c1, u.c0);
        mma_h_z(H[5][0], H[5][1], B35, u.d2, u.d1); mma_h_z(H[6][0], H[6][1], B35, u.c3, u.c2);
        mma_h_z(H[2][0], H[2][1], B35, u.cm1, u.cm2); mma_h_z(H[1][0], H[1][1], B35, u.em2, u.em3); mma_h_z(H[0][0], H[0][1], B35, u.cm3, u.cm4);
        if (j < 5) load2(u, j + 1);
        if (j > 0) finish(j + 1);
        if (j == MIX0_AT) { mix_setup(); mix_load(q, 0); mix_calc(q, 0); }
        if (j == MIX1_AT) { mix_load(q, 1); mix_calc(q, 1); }
        if (j == 5) { mix_load(q2, 2); mix_load(q3, 3); }
        const int n = j < 4 ? 3 : 6 - j;
#pragma unroll
        for (int s = 0; s < 2; s++) {
            const int o = 3 - s;
            const uint32_t qe[4] = {H[o][0] ^ zr, H[o + 1][0] ^ zq, H[o][1] ^ zr, H[o + 1][1] ^ zq};
            const uint32_t qg[4] = {hsub(H[o + 2][0], H[o][0]), hsub2(H[o + 3][0], H[o + 1][0]), hsub(H[o + 2][1], H[o][1]), hsub2(H[o + 3][1], H[o + 1][1])};
            const uint32_t qf[4] = {hsub(H[o - 2][0], H[o][0]), hsub2(H[o - 1][0], H[o + 1][0]), hsub(H[o - 2][1], H[o][1]), hsub2(H[o - 1][1], H[o + 1][1])};
#pragma unroll
            for (int i = 0; i < n; i++) mma_h(M[j + 2 + i], qe, QS[s][i].x, QS[s][i].y);
#pragma unroll
            for (int i = 0; i < n; i++) mma_h(Yo[j + 2 + i], qg, Q[s][i].x, Q[s][i].y);
#pragma unroll
            for (int i = 0; i < n; i++) mma_h(Ye[j + 2 + i], qf, Q[s + 2][i].x, Q[s + 2][i].y);
        }
    }
    finish(7);
    if (lead) { TSTAMP(5); CSTAMP(29); }
    if (SEND0_AT == 6) mix_send(q, 0);
    if (SEND1_AT == 6) mix_send(q, 1);
    mbar_spin(bars + 8 * (B_Y + 2));
    asm volatile("cp.async.bulk.commit_group;" ::: "memory");
    mix_calc(q2, 2);
    mix_send(q2, 2);
    asm volatile("cp.async.bulk.wait_group 0;" ::: "memory");
    __syncwarp();
    if (lane == 0) mbar_arrive(bars + 8 * B_SD);
    mbar_spin(bars + 8 * (B_Y + 3));
    if (lead) TSTAMP(6);
    mix_calc(q3, 3);
    mix_send(q3, 3);
    asm volatile("cp.async.bulk.commit_group;" ::: "memory");
    asm volatile("cp.async.bulk.wait_group.read 0;" ::: "memory");
}

__global__ void __cluster_dims__(2, 1, 1) __launch_bounds__(NTHREADS, 1)
fused_kernel(const Params p, const __grid_constant__ CUtensorMap tm_gu, const __grid_constant__ CUtensorMap tm_down, const __grid_constant__ CUtensorMap tm_x,
             const __grid_constant__ CUtensorMap tm_r, const __grid_constant__ CUtensorMap tm_o) {
    extern __shared__ __align__(1024) unsigned char smem[];
    const uint32_t sb = __shfl_sync(0xffffffffu, smem_u32(smem), 0);
    int tid;
    asm volatile("mov.u32 %0, %%tid.x;" : "=r"(tid));
    const int pw = tid >> 5, lane = tid & 31;
    const int kc = ((blockIdx.x >> 1) + 60) & 63, lo = kc < 32, hi = kc >= 60, kq = lo ? kc >> 3 : ((kc - 32) * 37) >> 8;
    const int h = blockIdx.x & 1;
    const int pr = (hi ? 1 : 4) * kc - (lo ? 31 : hi ? 0 : 27) * kq - ((lo | hi) ? 0 : 96);
    const int c = 2 * pr + h;
    const int fb = FB_BLK ? (int)blockIdx.x : c;
    const uint32_t bars = sb + M_BARS;

    uint2 v_la, v_ai, v_cr, v_ci;
    uint32_t ldt16, dsk16;
    {
        const uint32_t ch = 8 * c + pw - MAIN_W0, po = ch * 128 + 4 * lane;
        asm volatile("{ .reg .pred q; setp.ge.u32 q, %16, 8; @q bra.uni L%=;\n\t"
                     "ld.global.nc.v2.u32 {%0,%1}, [%10];\n\tld.global.nc.v2.u32 {%2,%3}, [%11];\n\tld.global.nc.u16 %8, [%14];\n\t"
                     "ld.global.nc.v2.u32 {%4,%5}, [%12];\n\tld.global.nc.v2.u32 {%6,%7}, [%13];\n\tld.global.nc.u16 %9, [%15];\nL%=:\n\t}"
                     : "=r"(v_la.x), "=r"(v_la.y), "=r"(v_ai.x), "=r"(v_ai.y), "=r"(v_cr.x), "=r"(v_cr.y), "=r"(v_ci.x), "=r"(v_ci.y), "=r"(ldt16), "=r"(dsk16)
                     : "l"(p.logA + po), "l"(p.Aim + po), "l"(p.Cre + po), "l"(p.Cim + po), "l"(p.logdt + ch), "l"(p.Dskip + ch), "r"(pw - MAIN_W0));
    }

    if (blockIdx.x >= 128) {
        if (blockIdx.x != 128) return;
        const unsigned tag = (ld_epoch(p.ex) + 1) & 0xffffu;
        const uint32_t idx0 = 2047 - (512 * (tid & 3) + (tid >> 3) + 256 * ((tid >> 2) & 1));
        const uint32_t list = sb + 128;
#pragma unroll 1
        for (int pass = 0; pass < 2; pass++) {
            if (tid == 0) sts32(sb + 64, 0);
            sts128(list + 16 * tid, 0, 0, 0, 0);
            uint4 a = make_uint4(lane == 0 ? 0x10000u : 0u, 0, 0, 0);
            bool ok = pass == 0;
#pragma unroll 1
            for (int it = 0; it < (1 << 22) && !ok; it++) {
                a = ld_gpu128(&p.ex->r[tid]);
                ok = (((a.x ^ tag) | (a.y ^ tag) | (a.z ^ tag) | (a.w ^ tag)) & 0xffffu) == 0;
            }
            if (!ok) __trap();
            const uint32_t key[4] = {(a.x & 0xffff0000u) | idx0, (a.y & 0xffff0000u) | (idx0 - 64), (a.z & 0xffff0000u) | (idx0 - 128), (a.w & 0xffff0000u) | (idx0 - 192)};
            const uint32_t wm = __reduce_max_sync(0xffffffffu, max(max(key[0], key[1]), max(key[2], key[3])));
            if (lane == 0) sts32(sb + pw * 4, wm);
            __syncthreads();
            const uint2 q = lds64(sb + 8 * (lane & 7));
            const uint32_t thr = __reduce_min_sync(0xffffffffu, max(q.x, q.y));
            if (tid == 0) TSTAMP(0);
            const uint32_t n = (key[0] >= thr) + (key[1] >= thr) + (key[2] >= thr) + (key[3] >= thr);
            if (n) {
                uint32_t pos;
                asm volatile("atom.shared.add.u32 %0, [%1], %2;" : "=r"(pos) : "r"(sb + 64), "r"(n) : "memory");
#pragma unroll
                for (int i = 0; i < 4; i++) if (key[i] >= thr) { sts32(list + 4 * pos, key[i]); pos++; }
            }
            __syncthreads();
            const int ncand = (int)lds32(sb + 64);
            const uint2 l0 = lds64(list + 8 * lane);
#pragma unroll 1
            for (int j = pw; j < ncand; j += 16) {
                const uint32_t mine = lds32(list + 4 * j);
                int rank = __popc(__ballot_sync(0xffffffffu, l0.x > mine)) + __popc(__ballot_sync(0xffffffffu, l0.y > mine));
#pragma unroll 1
                for (int i = 64; i < ncand; i += 32) rank += __popc(__ballot_sync(0xffffffffu, lds32(list + 4 * (i + lane)) > mine));
                if (rank < 8 && lane == 0) asm volatile("st.relaxed.gpu.global.v2.u32 [%0], {%1, %2};" :: "l"(&p.ex->top[rank]), "r"(mine), "r"(pass ? tag : tag ^ 0x8000u) : "memory");
            }
            if (tid == 0) TSTAMP(1);
            __syncthreads();
        }
        if (tid == 0) TSDUMP(3u);
        return;
    }

    if (pw != 12) asm volatile("barrier.cluster.arrive.relaxed.aligned;" ::: "memory");

    if (pw >= MAIN_W0 && pw < MAIN_W0 + 8) {
        const int warp = pw - MAIN_W0;
        [[maybe_unused]] const bool lead = (tid == 32 * MAIN_W0);
        asm volatile("setmaxnreg.inc.sync.aligned.u32 " MAIN_REGS ";");
        cluster_next();
        [[maybe_unused]] const int d = 8 * c + warp;
        const int g = lane >> 2, t = lane & 3, mi = lane >> 3, r = lane & 7;
        const uint32_t TB = sb + OFF_TAB + warp * T_CH;
        const uint32_t UB = sb + OFF_U + warp * U_CH;
        const uint32_t zr = ZR;

        uint32_t Ra[2][2], Rb[2][2], Rc[2], Rl[2];
        int esum;
        {
            const float dt = bf_round(exp_acc(__uint_as_float(ldt16 << 16)));
            const uint32_t ec = max(warp_max16(amax2_bf(amax2_bf(v_cr.x, v_cr.y), amax2_bf(v_ci.x, v_ci.y))) >> 7, 6u);
            const float cf = __uint_as_float((__float_as_uint(dt) & 0x7fffffu) | ((260u - ec) << 23));
            esum = (int)ec + (int)(__float_as_uint(dt) >> 23) - 274;
            kernel_gen(v_la, v_ai, v_cr, v_ci, dt, cf, TB, UB, bars + 8 * B_KD, lane, zr, Ra, Rb, Rc, Rl);
        }
        if (lead) TSTAMP(2);

        {
            uint32_t mk = amax2_h(amax2_h(amax2_h(Ra[0][0], Ra[0][1]), amax2_h(Ra[1][0], Ra[1][1])), amax2_h(amax2_h(Rb[0][0], Rb[0][1]), amax2_h(Rb[1][0], Rb[1][1])));
            mk = amax2_h(amax2_h(mk, hmul(Rl[0], 0x34003400u)), amax2_h(Rc[0], Rc[1]));
            const int eb = (dsk16 >> 7) & 0xff, ek = max((int)(warp_max16(mk) >> 10), eb ? eb - 127 - esum : 0), en = eb - esum - 3 - ek;
            const float ds = (lane == 0 && eb && en > 0) ? __uint_as_float(((dsk16 & 0x807fu) << 16) | (en << 23)) : 0.f;
            const float fs = __uint_as_float(max(139 - ek, 1) << 23);
            const uint32_t ks = pack_h(fs, fs);
            uint32_t va[4], vb[4];
#pragma unroll
            for (int i = 0; i < 4; i++) { va[i] = hmul(Ra[i >> 1][i & 1], ks); vb[i] = hmul(Rb[i >> 1][i & 1], ks); }
            va[0] = hadd(va[0], pack_h(ds, 0.f));
            const uint32_t k512 = __shfl_sync(0xffffffffu, vb[0], 2) & 0xffffu, k255 = __shfl_sync(0xffffffffu, va[3], 31);
#pragma unroll
            for (int i = 0; i < 4; i++) {
                const uint32_t pv = __shfl_sync(0xffffffffu, lane == 31 ? (i ? va[i - 1] : 0u) : va[i], lane - 1);
                sts64(TB + 48 + 256 * i + 8 * lane, __byte_perm(pv, va[i], 0x5432), va[i]);
            }
#pragma unroll
            for (int i = 0; i < 4; i++) {
                const uint32_t nx = __shfl_sync(0xffffffffu, lane == 0 ? (i < 3 ? vb[i + (i < 3)] : k512) : vb[i], lane + 1 + 2 * (lane & 1));
                const uint32_t aa = __byte_perm(vb[i], 0, 0x1010);
                sts128_if(t < 2, TB + 1072 + 256 * i + 32 * g + 16 * t, (i == 0 && lane == 0) ? __byte_perm(k255, aa, 0x5432) : aa ^ zr, aa, vb[i] ^ zr, __byte_perm(vb[i], nx, 0x5432));
            }
            const uint32_t k0 = lane == 3 ? k512 : 0u, kk = k0 * 0x10001u;
            sts128_if(lane < 8, TB + 16 * lane + (lane < 3 ? 0 : 2048), kk, kk ^ zr, kk + zr, k0);
            sts128(TB + T_R2 + 16 * lane, vb[0], vb[1], vb[2], vb[3]);
            esum += (int)ek;
            sts128(TB + T_R2 + 512 + 16 * lane, hmul(Rc[0], ks), hmul(Rc[1], ks), hmul(Rl[0], ks), (uint32_t)esum);
            __syncwarp();
            if (lane == 0) mbar_arrive(bars + 8 * B_TS);
        }
        if (lead) TSTAMP(11);

        convolve(sb, h, zr, pr, p.out, &tm_o DBG_ARGS);
        { LANE_VARS; if (lead) { TSTAMP(7); TSDUMP(0x3c000cffu); } }
    } else if (pw < 4) {
        const int v = pw, at = tid;
        const int g = lane >> 2, t = lane & 3, mi = lane >> 3, r = lane & 7;
        const uint32_t dalt = (h ? ALT1 : ALT0) + A_SLOT - ALT_SLOT * 8192;
        cp16(sb + OFF_GP + tid * 16, p.wr + tid * 8);
        cp16(sb + OFF_GP + 2048 + tid * 16, p.gatew + tid * 8);
        const unsigned epoch = ld_epoch(p.ex);
        if (tid == 0) sts128(sb + OFF_S - 16, 0, 0, 0, 0);
        const unsigned tag = (epoch + 1) & 0xffffu;
        const int ftok = 2 * ((at >> 2) & 3) + (at & 1), fch = (at >> 4) + 8 * ((at >> 1) & 1);
        uint32_t eu;
        {
            cluster_next();
            cp_wait_all();
            bar_sync(1, 128);
            const uint32_t wo = sb + OFF_GP + 512 * v + 64 * ((g >> 1) & 1) + 16 * t + 4 * (g & 1);
            uint32_t w0[4], w1[4];
#pragma unroll
            for (int cb = 0; cb < 4; cb++) { w0[cb] = lds32(wo + 128 * cb); w1[cb] = lds32(wo + 128 * cb + 8); }
            const uint32_t go = sb + OFF_GP + 2048 + 512 * v + 64 * (g & 1) + 16 * t;
            const uint32_t ro = sb + M_RG + (g >> 1) * 32 + (2 * v + (g & 1)) * 4;
            const uint32_t xo = sb + OFF_XROW + (g >> 1) * 2048 + 512 * v + 64 * (g & 1) + 16 * t;
            const uint32_t one0 = 0x3F803F80u ^ p.zero, one1 = 0x3F803F80u + p.zero;
            auto row_sum = [&](uint32_t a) {
                const uint4 x = lds128(a), y = lds128(a + 16);
                return ((__uint_as_float(x.x) + __uint_as_float(x.y)) + (__uint_as_float(x.z) + __uint_as_float(x.w)))
                     + ((__uint_as_float(y.x) + __uint_as_float(y.y)) + (__uint_as_float(y.z) + __uint_as_float(y.w)));
            };
            const int dl = 8 * (r >> 1) + 4 - 2 * mi - (r & 1);
            const uint32_t so = sb + OFF_S + (v >> 1) * 32768 + (dl & 6) * 1024 + (8 * (v & 1) + (dl >> 4)) * 128 + (dl & 1) * 64 + (dl & 8) * 4 + ((dl & 16) ^ (h << 4));
            const uint32_t so2 = so + (dl >= 0 ? 0 : v == 2 ? -30720 : v == 0 ? 26624 : 0), so1 = (dl < 0 && v == 0) ? sb + OFF_S - 16 : so2;
            auto src = [&](int k) { return (k == 0 ? so1 : (k & 3) == 0 ? so2 : so) + (k >> 2) * 8192 + (k & 3) * 256; };
            uint32_t xr[16][4], mx = 0, idb = 0;
            auto slice = [&](int k) { ldsm4t(src(k), xr[k][0], xr[k][1], xr[k][2], xr[k][3]); };
            auto to_half = [&](uint32_t (&q)[4]) {
                float f0[4], f1[4];
                widen_bf(f0, q[0], q[1], idb); widen_bf(f1, q[2], q[3], idb);
                q[0] = pack_h(f0[0], f0[1]); q[1] = pack_h(f0[2], f0[3]); q[2] = pack_h(f1[0], f1[1]); q[3] = pack_h(f1[2], f1[3]);
            };
            auto track = [&](int k) { mx = amax2_bf(amax2_bf(mx, amax2_bf(xr[k][0], xr[k][1])), amax2_bf(xr[k][2], xr[k][3])); };
            auto cta_exp = [&]() {
                const uint32_t wm = warp_max16(mx);
                if (lane == 0) sts32(sb + M_MX + v * 4, wm);
                bar_sync(1, 128);
                const uint4 m4 = lds128(sb + M_MX);
                return max(max(m4.x, m4.y), max(m4.z, m4.w)) >> 7;
            };
            auto set_scale = [&]() { const uint32_t sc = (257u - eu) << 7; idb = (g == 2 * t) ? sc : (g == 2 * t + 1) ? sc << 16 : 0u; };
            uint4 x[4], gw[4];
#pragma unroll
            for (int cb = 0; cb < 4; cb++) gw[cb] = lds128(go + 128 * cb);
            auto gate = [&](int i) {
                float e0[4] = {0.f, 0.f, 0.f, 0.f}, e1[4] = {0.f, 0.f, 0.f, 0.f};
#pragma unroll
                for (int cb = 0; cb < 4; cb++)
                    mma_bf((cb & 1) ? e1 : e0, hmul2_bf(x[cb].x, gw[cb].x), hmul2_bf(x[cb].y, gw[cb].y), hmul2_bf(x[cb].z, gw[cb].z), hmul2_bf(x[cb].w, gw[cb].w), one0, one1);
                if (t == 0) stsf(ro + 512 + 128 * i, (e0[0] + e0[3]) + (e1[0] + e1[3]));
            };
#pragma unroll
            for (int i = 0; i < 4; i++) {
                if (i == 0) mbar_spin(bars + 8 * B_X); else mbar_wait_n<2, 8 * (B_X - B_S + 1)>(bars + 8 * (B_S + i - 1));
#pragma unroll
                for (int cb = 0; cb < 4; cb++) x[cb] = lds128(xo + 8192 * i + 128 * cb);
#pragma unroll
                for (int k = max(4 * i - 4, 0); k < 4 * i; k++) slice(k);
                float d0[4] = {0.f, 0.f, 0.f, 0.f}, d1[4] = {0.f, 0.f, 0.f, 0.f};
#pragma unroll
                for (int cb = 0; cb < 4; cb++) mma_bf((cb & 1) ? d1 : d0, x[cb].x, x[cb].y, x[cb].z, x[cb].w, w0[cb], w1[cb]);
                if (t == (g & 1)) stsf(ro + 128 * i, (d0[0] + d0[3]) + (d1[0] + d1[3]));
                if (i == 3) break;
                gate(i);
#pragma unroll
                for (int k = max(4 * i - 4, 0); k < 4 * i; k++) track(k);
                if (i == 1) {
                    eu = min(cta_exp() + 3u, 255u);
                    set_scale();
                }
#pragma unroll
                for (int k = max(4 * i - 4, 0); k < 4 * i; k++) to_half(xr[k]);
            }
            bar_sync(4, 256);
            if (at < 16) {
                const uint32_t rb = pack_bf(0.f, row_sum(sb + M_RG + at * 32));
                st_gpu32((uint32_t*)p.ex->r + 16 * c + at, ((rb ^ (((int)rb >> 31) | 0x80000000u)) & 0xffff0000u) | tag);
            }
            if (at == 32) mbar_arrive(bars + 8 * B_XF);
            if (at == 0) TSTAMP(8);
#pragma unroll
            for (int k = 8; k < 12; k++) { track(k); to_half(xr[k]); }
            mbar_spin(bars + 8 * (B_S + 3));
            if (at == 0) TSTAMP(9);
#pragma unroll
            for (int k = 12; k < 16; k++) slice(k);
            uint32_t utail = 0;
            if (at < 64 && r >= 5) utail = lds16(sb + OFF_S + 57344 + 1952 + ((12 - r) & 6) * 1024 + (r & 1) * 64 + ((h ^ 1) << 4) + 2 * (at >> 3));
#pragma unroll
            for (int k = 12; k < 16; k++) { track(k); to_half(xr[k]); }
            mx = amax2_bf(mx, utail);
            uint32_t over;
            asm volatile("{ .reg .pred p, q; setp.ne.u32 p, %1, 0; bar.red.or.pred q, 1, 128, p; selp.u32 %0, 1, 0, q; }"
                         : "=r"(over) : "r"((uint32_t)(max(mx & 0x7f80u, (mx >> 16) & 0x7f80u) > (eu << 7))) : "memory");
            mbar_spin(bars + 8 * B_KD);
            const uint32_t uo = sb + OFF_U + g * U_CH + t * U_PL;
            auto put = [&](int k, const uint32_t (&q)[4]) { sts128(uo + (8 + 4 * v + 16 * (k >> 2) + (k & 3)) * 16, q[0], q[1], q[2], q[3]); };
            if (!over) {
#pragma unroll
                for (int k = 0; k < 16; k++) put(k, xr[k]);
            } else {
                eu = cta_exp();
                set_scale();
#pragma unroll 1
                for (int k = 0; k < 16; k++) {
                    uint32_t q[4];
                    ldsm4t(src(k), q[0], q[1], q[2], q[3]);
                    to_half(q);
                    put(k, q);
                }
            }
            sts128(uo + v * 32, 0, 0, 0, 0); sts128(uo + v * 32 + 16, 0, 0, 0, 0);
            if (at < 64) sts16(sb + OFF_U + (at >> 3) * U_CH + 72 * 16 + r * 2, pack_h(bf_lo(utail) * bf_lo((257u - eu) << 7), 0.f));
            __syncwarp();
            if (lane == 0) mbar_arrive(bars + 8 * B_U);
#pragma unroll
            for (int cb = 0; cb < 4; cb++) gw[cb] = lds128(go + 128 * cb);
            gate(3);
            bar_sync(1, 128);
            if (at < 16) {
                const float gv = bf_round(sigmoid_f(bf_round(row_sum(sb + M_RG + 512 + at * 32))));
                st_gpu32((uint32_t*)p.ex->g + 1024 * h + 16 * (8 * (pr & 7) + (pr >> 3)) + (at ^ (2 * (pr >> 4) + 8 * (pr & 1))), pack_bf(gv, 1.f - gv));
            }
            if (at == 0) TSTAMP(23);
        }
        const int ct = v & 1, kh = v >> 1;
        uint32_t wa[GU_PRE][4][4];
        uint32_t ta, tb;
        {
            const int krow0 = 8 * (mi >> 1) + r;
            const uint32_t off0 = krow0 * 64 + (((2 * ct + (mi & 1)) ^ ((krow0 >> 1) & 3)) << 4);
            ta = sb + OFF_RING + kh * 2048 + off0 + p.swap_gu; tb = ta + 4096 - 2 * p.swap_gu;
        }
        auto gu_load = [&](uint32_t (&a)[4][4], int s) {
            const uint32_t o = (s % NSLOT) * 8192 + (s % NSLOT >= ALT_SLOT ? dalt : 0);
            ldsm4t(ta + o, a[0][0], a[0][1], a[0][2], a[0][3]);
            ldsm4t(tb + o, a[1][0], a[1][1], a[1][2], a[1][3]);
            ldsm4t(ta + o + 1024, a[2][0], a[2][1], a[2][2], a[2][3]);
            ldsm4t(tb + o + 1024, a[3][0], a[3][1], a[3][2], a[3][3]);
        };
        auto gu_release = [&](const uint32_t (&a)[4][4], int s) {
            if (s < B_S - B_EMPTY && lane == 0) mbar_arrive(bars + 8 * (B_EMPTY + s) + (a[0][0] & a[1][0] & a[2][0] & a[3][0] & p.zero));
        };
        auto gu_park = [&](auto S0, auto N) {
            constexpr int s0 = decltype(S0)::value, n = decltype(N)::value;
            if (fb < NGU_CTA) {
                mbar_wait_n<n, 8>(bars + 8 * s0);
#pragma unroll
                for (int s = s0; s < s0 + n; s++) gu_load(wa[s], s);
#pragma unroll
                for (int s = s0; s < s0 + n; s++) gu_release(wa[s], s);
            }
        };
        gu_park(IC<0>(), IC<4>());
        asm volatile("barrier.cluster.wait.acquire.aligned;" ::: "memory");
        mbar_wait(bars + 8 * B_TS);
#pragma unroll 1
        for (int i = 0; i < 2; i++) {
            const int es = group_tables(sb + OFF_TAB + (v + 4 * i) * T_CH, lane) + (int)eu;
            if (lane < 2) { const uint32_t o = mapa(sb, lane); st_async4(o + M_SC + (8 * h + v + 4 * i) * 4, (uint32_t)min(max(es, 1), 254) * 0x800080u, o + M_BARS + 8 * B_SC); }
        }
        __syncwarp();
        if (lane == 0) mbar_arrive(bars + 8 * B_TD);
        gu_park(IC<4>(), IC<GU_PRE - 4>());
        if (fb < NGU_CTA) {
            float dgt[4] = {0.f, 0.f, 0.f, 0.f}, dup[4] = {0.f, 0.f, 0.f, 0.f}, dg2[4] = {0.f, 0.f, 0.f, 0.f}, du2[4] = {0.f, 0.f, 0.f, 0.f};
            const uint32_t xo = sb + OFF_XSEL + r * XS_ROW + 64 * kh + 16 * mi;
            auto gu_mma = [&](const uint32_t (&a)[4][4], const uint32_t (&b)[4]) {
                mma_bf(dgt, a[0][0], a[0][1], a[0][2], a[0][3], b[0], b[1]);
                mma_bf(dup, a[1][0], a[1][1], a[1][2], a[1][3], b[0], b[1]);
                mma_bf(dg2, a[2][0], a[2][1], a[2][2], a[2][3], b[2], b[3]);
                mma_bf(du2, a[3][0], a[3][1], a[3][2], a[3][3], b[2], b[3]);
            };
            auto gu_batch = [&](auto S0, auto N) {
                constexpr int s0 = decltype(S0)::value, n = decltype(N)::value;
                uint32_t b[n][4];
                mbar_wait_n<n, 8>(bars + 8 * s0);
#pragma unroll
                for (int i = 0; i < n; i++) { ldsm4(xo + 128 * (s0 + i), b[i][0], b[i][1], b[i][2], b[i][3]); gu_load(wa[i], s0 + i); }
#pragma unroll
                for (int i = 0; i < n; i++) gu_mma(wa[i], b[i]);
#pragma unroll
                for (int i = 0; i < n; i++) gu_release(wa[n - 1], s0 + i);
            };
            mbar_spin(bars + 8 * B_XS);
            if (at == 0) TSTAMP(12);
#pragma unroll
            for (int s = 0; s < GU_PRE; s++) { uint32_t b[4]; ldsm4(xo + 128 * s, b[0], b[1], b[2], b[3]); gu_mma(wa[s], b); }
            gu_batch(IC<6>(), IC<2>());
            mbar_spin(bars + 8 * (B_XS + 1));
            gu_batch(IC<8>(), IC<4>()); gu_batch(IC<12>(), IC<3>()); gu_batch(IC<15>(), IC<1>());
#pragma unroll
            for (int i = 0; i < 4; i++) { dgt[i] += dg2[i]; dup[i] += du2[i]; }
            if (at == 0) TSTAMP(13);
            const uint32_t red = sb + M_RG, hs = sb + OFF_XSEL;
            sts128(red + ((v ^ 2) * 32 + lane) * 16, __float_as_uint(kh ? dgt[0] : dgt[2]), __float_as_uint(kh ? dgt[1] : dgt[3]),
                   __float_as_uint(kh ? dup[0] : dup[2]), __float_as_uint(kh ? dup[1] : dup[3]));
            bar_sync(1, 128);
            const uint4 oth = lds128(red + at * 16);
#pragma unroll
            for (int i = 0; i < 2; i++) {
                const float gv = bf_round((kh ? dgt[2 + i] : dgt[i]) + __uint_as_float(i ? oth.y : oth.x));
                const float uv = bf_round((kh ? dup[2 + i] : dup[i]) + __uint_as_float(i ? oth.w : oth.z));
                const float sl = bf_round(gv * sigmoid_f(gv));
                uint32_t hv = pack_bf(sl * uv, 0.f) & 0xffffu;
                hv = (hv == 0x8000u) ? 0x8000u : (hv ^ 0x8000u);
                sts16(hs + (2 * t + i) * 64 + (g >> 1) * 16 + (2 * ct + kh) * 4 + (g & 1) * 2, hv);
            }
            bar_sync(1, 128);
            if (v == 0) st_gpu128(&p.ex->h[32 * fb + lane], lds128(hs + lane * 16));
        }
        else mbar_wait(bars + 8 * (B_XS + 1));
        if (at == 0) TSTAMP(14);
        {
            mbar_wait(bars + 8 * B_G);
            const int row = (int)lds32(sb + M_IDX + ftok * 4);
            const int w = row & 7, jj = (row >> 3) & 7;
            const uint32_t xa = sb + OFF_S + h * 32768 + (row >> 9) * 8192 + (w & 6) * 1024 + ((row >> 4) & 15) * 128 + (w & 1) * 64 + (jj & 1) * 32 + ((2 * fch) ^ (row & 16));
            const float xv = bf_lo(lds16(xa));
            const uint32_t gp = lds32(sb + OFF_GP + (8 * w + jj) * 64 + ((4 * (row >> 9) + ((row >> 6) & 3)) ^ ((jj & 6) + 8 * (w & 1))) * 4);
            const uint32_t ya = sb + (((fch >> 3) == h) ? OFF_TAB + (fch & 7) * T_CH : (h ? ALT1 : ALT0) + A_YIN + (fch & 7) * Y_CH) + (row >> 9) * 512 + (4 * w + ((row >> 6) & 3)) * 16 + jj * 2;
            const float rs = bf_round(sigmoid_f(ldsf(sb + M_RSEL + ftok * 4)));
            uint4 hq[14];
            {
                const uint4* hsrc = &p.ex->h[(56 * h + 2 * v) * 32 + lane];
                mbar_wait(bars + 8 * (B_FULL + NST_GU + H_WAIT));
                if (at == 0) TSTAMP(15);
#pragma unroll
                for (int i = 0; i < 14; i++) hq[i] = ld_gpu128(hsrc + (8 * (i >> 1) + (i & 1)) * 32);
                bool ok = false;
#pragma unroll 1
                for (int it = 0; it < (1 << 22); it++) {
                    uint32_t mn = 0xffffffffu;
#pragma unroll
                    for (int i = 0; i < 14; i++) mn = min(mn, hq[i].x);
                    ok = __all_sync(0xffffffffu, mn != 0);
                    if (ok) break;
                    if (PSLEEP > 0) __nanosleep(PSLEEP);
#pragma unroll
                    for (int i = 0; i < 14; i++) if (hq[i].x == 0) hq[i] = ld_gpu128(hsrc + (8 * (i >> 1) + (i & 1)) * 32);
                }
                if (!ok) __trap();
            }
            if (at == 0) TSTAMP(16);
            mbar_wait_n<DN_PRE, 8>(bars + 8 * (B_FULL + NST_GU));
            float dd[4][4];
#pragma unroll
            for (int j = 0; j < 4; j++) { dd[j][0] = dd[j][1] = dd[j][2] = dd[j][3] = 0.f; }
            const int krow0 = 64 * (v & 1) + 8 * (mi >> 1) + r;
            const uint32_t td = sb + OFF_RING + (v >> 1) * 4096 + krow0 * 32 + (((mi & 1) ^ ((krow0 >> 2) & 1)) << 4);
#pragma unroll
            for (int s = 0; s < 7; s++) {
                if (s >= DN_PRE) mbar_spin(bars + 8 * (B_FULL + NST_GU + s));
                const uint32_t tile = td + ((NST_GU + s) % NSLOT) * 8192 + ((NST_GU + s) % NSLOT >= ALT_SLOT ? dalt : 0);
                uint32_t a[4][4];
#pragma unroll
                for (int j = 0; j < 4; j++) ldsm4t(tile + j * 512, a[j][0], a[j][1], a[j][2], a[j][3]);
                mma_bf(dd[0], a[0][0], a[0][1], a[0][2], a[0][3], hq[2 * s].x, hq[2 * s].y);
                mma_bf(dd[1], a[1][0], a[1][1], a[1][2], a[1][3], hq[2 * s].z, hq[2 * s].w);
                mma_bf(dd[2], a[2][0], a[2][1], a[2][2], a[2][3], hq[2 * s + 1].x, hq[2 * s + 1].y);
                mma_bf(dd[3], a[3][0], a[3][1], a[3][2], a[3][3], hq[2 * s + 1].z, hq[2 * s + 1].w);
            }
            uint32_t ds[4];
#pragma unroll
            for (int j = 0; j < 4; j++) ds[j] = __float_as_uint((dd[0][j] + dd[1][j]) + (dd[2][j] + dd[3][j]));
            if (at == 0) TSTAMP(17);
            const uint32_t o = mapa(sb, h ^ 1);
            st_async16(o + OFF_DP + (128 * h + at) * 16, ds[0], ds[1], ds[2], ds[3], o + M_BARS + 8 * B_DP);
            sts128(sb + OFF_DP + (128 * h + at) * 16, ds[0], ds[1], ds[2], ds[3]);
            __syncwarp();
            if (lane == 0) mbar_arrive(bars + 8 * B_DP);
            mbar_spin(bars + 8 * B_DP);
            float pt[8];
#pragma unroll
            for (int k = 0; k < 8; k++) pt[k] = ldsf(sb + OFF_DP + k * 512 + at * 4);
            const float tot = -(((pt[0] + pt[1]) + (pt[2] + pt[3])) + ((pt[4] + pt[5]) + (pt[6] + pt[7])));
            const float eb = bf_round(bf_hi(gp) * bf_round(xv + bf_round(bf_round(tot) * rs)));
            mbar_wait_n<3, 8>(bars + 8 * (B_Y + 2));
            if (((row >> 8) & 1) == h) p.out[(size_t)row * D_ + 16 * pr + fch] = __float2bfloat16_rn(fmaf(bf_lo(gp), bf_lo(lds16(ya)), eb));
        }
        if (at == 0) { TSTAMP(18); TSDUMP(fb < NGU_CTA ? 0x0087f300u : 0x0087c300u); if (c == 0) *(volatile unsigned*)&p.ex->epoch = epoch + 1; }
    } else {
        const uint32_t t_start = now_ns();
        asm volatile("setmaxnreg.dec.sync.aligned.u32 " HELP_REGS ";");
        if (pw != 12) {
            if (pw >= 14) {
#pragma unroll
                for (int k = 0; k < 5; k++) {
                    const int w = 1 + 2 * k, e = (tid & 63) - 32;
                    sts32(sb + OFF_BAND + k * 256 + (tid & 63) * 4, ((e >= 0 && e < w) ? 0x3C00u : 0u) | ((e + 1 >= 0 && e + 1 < w) ? 0x3C000000u : 0u));
                }
                cluster_next();
            } else {
                if (lane == 0) {
                    asm volatile("prefetch.tensormap [%0];" :: "l"(&tm_r) : "memory");
                    asm volatile("prefetch.tensormap [%0];" :: "l"(&tm_x) : "memory");
                }
                sts32(sb + M_BMAP + lane * 4, 0);
                __syncwarp();
                cluster_next();
                uint4* gz = &p.ex->g[256 * h + 4 * (8 * (pr & 7) + (pr >> 3)) + (lane & 3)];
                uint4* hz = fb < NGU_CTA ? &p.ex->h[32 * fb + lane] : gz;
                st_gpu128(gz, make_uint4(0, 0, 0, 0)); st_gpu128(hz, make_uint4(0, 0, 0, 0));
                if ((ld_gpu128(gz).x | ld_gpu128(hz).x) != 0) __trap();
            }
        } else {
            if (lane == 0) {
#pragma unroll
                for (int k = 0; k < 4; k++) { mbar_init(bars + 8 * (B_X + k), 1); mbar_init(bars + 8 * (B_S + k), 1); }
                asm volatile("fence.proxy.async.shared::cta;" ::: "memory");
                asm volatile("fence.mbarrier_init.release.cluster;" ::: "memory");
            }
            __syncwarp();
            asm volatile("barrier.cluster.arrive.relaxed.aligned;" ::: "memory");
            tma4d_warp(sb + OFF_XROW, &tm_r, 4 * h, pr, bars + 8 * B_X);
            asm volatile("barrier.cluster.wait.acquire.aligned;" ::: "memory");
            if (lane == 0) TSTAMP(20);
#pragma unroll
            for (int i = 0; i < 4; i++) {
                tma5d_both(sb + OFF_S + (4 * h + i) * 8192, &tm_x, 16 * pr, 32 * i + 16 * h, bars + 8 * (B_S + i));
                if (i < 3) tma4d_warp(sb + OFF_XROW + (i + 1) * 8192, &tm_r, 8 * (i + 1) + 4 * h, pr, bars + 8 * (B_X + i + 1));
            }
            if (lane == 0) {
                TSTAMP(24);
#pragma unroll
                for (int k = 0; k < 4; k++) { mbar_expect(bars + 8 * (B_X + k), 8192); mbar_expect(bars + 8 * (B_S + k), 16384); }
                asm volatile("prefetch.tensormap [%0];" :: "l"(&tm_gu) : "memory");
                asm volatile("prefetch.tensormap [%0];" :: "l"(&tm_down) : "memory");
                asm volatile("prefetch.tensormap [%0];" :: "l"(&tm_o) : "memory");
#pragma unroll
                for (int k = 0; k < B_S; k++) mbar_init(bars + 8 * k, k < B_EMPTY ? 1 : 4);
#pragma unroll
                for (int k = B_XS; k < B_X; k++) mbar_init(bars + 8 * k, (k >= B_Y && k < B_SD) ? 9 : (k == B_KD || k == B_TS || k == B_SD) ? 8 : (k == B_TD || k == B_U) ? 4 : k == B_XS + 1 ? 2 : k == B_DP ? 5 : 1);
#pragma unroll
                for (int k = 0; k < B_EMPTY; k++) mbar_expect(bars + 8 * k, 8192);
#pragma unroll
                for (int k = B_XS; k < B_SD; k++) if (k != B_TD && k != B_G) mbar_expect(bars + 8 * k, k < B_TD ? (fb < NGU_CTA ? 8192 : 0) : k == B_SC ? 64 : k == B_DP ? 2048 : k == B_NONE ? 0 : 4096);
                asm volatile("fence.proxy.async.shared::cta;" ::: "memory");
                asm volatile("fence.mbarrier_init.release.cluster;" ::: "memory");
            }
            __syncwarp();
            asm volatile("barrier.cluster.arrive.relaxed.aligned;" ::: "memory");
        }
        bar_arrive(4, 256);
        bar_sync(6, 128);
        if (pw == 15) {
            const unsigned tag = (ld_epoch(p.ex) + 1) & 0xffffu;
            const int tok = lane & 7;
            uint32_t top = 0;
            bool ok = false;
            mbar_wait(bars + 8 * B_XF);
#pragma unroll 1
            for (int it = 0; it < (1 << 22); it++) {
                uint32_t tg;
                asm volatile("ld.relaxed.gpu.global.v2.u32 {%0,%1}, [%2];" : "=r"(top), "=r"(tg) : "l"(&p.ex->top[tok]) : "memory");
                ok = __all_sync(0xffffffffu, tg == tag);
                if (ok) break;
            }
            if (!ok) __trap();
            if (lane == 0) TSTAMP(25);
            const int row = 2047 - (int)(top & 0xffffu);
            if (fb < NGU_CTA) {
#pragma unroll
                for (int k = 0; k < 8; k++) {
                    const int tk = 4 * h + ((k + pr) & 3), hf = k >> 2;
                    bulk_load_both(sb + OFF_XSEL + tk * XS_ROW + 1024 * hf, p.u + (size_t)__shfl_sync(0xffffffffu, row, tk) * D_ + 512 * hf, 1024, bars + 8 * (B_XS + hf));
                }
            }
            if (lane == 0) TSTAMP(21);
            if (lane < 8) {
                const uint32_t ord = top >> 16;
                sts32(sb + M_RSEL + tok * 4, ((ord & 0x8000u) ? (ord & 0x7fffu) : (~ord & 0xffffu)) << 16);
                sts32(sb + M_IDX + tok * 4, (uint32_t)row);
                if (((row >> 8) & 1) == h) asm volatile("red.shared.or.b32 [%0], %1;" :: "r"(sb + M_BMAP + ((row >> 7) & 1) * 64 + (row & 6) * 8 + ((row >> 4) & 3) * 4),
                                                   "r"(1u << (4 * (row >> 9) + ((row >> 5) & 2) + (row & 1) + 2 * (row & 8))) : "memory");
            }
            __syncwarp();
            if (lane == 0) { mbar_arrive(bars + 8 * (B_XS + 1)); TSDUMP(0x02200000u); }
            mbar_wait_n<2, 8>(bars + 8 * (B_XS + 1));
            if (lane == 0) bulk_load(sb + OFF_GP, &p.ex->g[256 * h], 4096, bars + 8 * B_GL);
            __syncwarp();
            mbar_wait(bars + 8 * B_GL);
            uint32_t mn = 0xffffffffu;
#pragma unroll
            for (int i = 0; i < 8; i++) { const uint4 a = lds128(sb + OFF_GP + (32 * i + lane) * 16); mn = min(min(mn, min(a.x, a.y)), min(a.z, a.w)); }
            if (mn == 0) {
#pragma unroll 1
                for (int i = lane, it = 0; i < 256; ) {
                    const uint4 a = ld_gpu128(&p.ex->g[256 * h + i]);
                    if (min(min(a.x, a.y), min(a.z, a.w)) != 0) { sts128(sb + OFF_GP + i * 16, a.x, a.y, a.z, a.w); i += 32; }
                    else if (++it > (1 << 22)) __trap();
                }
            }
            __syncwarp();
            if (lane == 0) { TSTAMP(30); TSDUMP(1u << 30); }
            if (lane == 0) mbar_arrive(bars + 8 * B_G);
            return;
        }
        const int s0 = fb < NGU_CTA ? 0 : NST_GU, s = lane, dn = s >= NST_GU;
        const int slot = s < NSLOT ? s : s < 2 * NSLOT ? s - NSLOT : s - 2 * NSLOT, depth = dn ? DEPTH_D : DEPTH_G;
        const uint32_t dst = sb + OFF_RING + slot * 8192 + (slot >= ALT_SLOT ? (h ? ALT1 : ALT0) + A_SLOT - ALT_SLOT * 8192 : 0);
        const uint32_t due = (t_start + T_W + h * (DT_G / 2) + DT_G * s + (dn ? (DT_D - DT_G) * (s - NST_GU) : 0)) & ~63u;
        const uint32_t w_slot = bars + 8 * (s >= s0 + NSLOT ? B_EMPTY + s - NSLOT : slot >= ALT_SLOT ? B_U : s >= X_SLOT ? B_XF : B_NONE);
        const uint32_t w_depth = bars + 8 * (s >= s0 + depth ? B_FULL + s - depth : B_NONE);
        const CUtensorMap* tm = dn ? &tm_down : &tm_gu;
        const int cx = dn ? 16 * pr : 32 * fb, cy = dn ? 1792 * h + 256 * (s - NST_GU) : 64 * s;
#pragma unroll 1
        for (int k = s0 + pw - 12; k < NST; k += 3) {
            if (lane == k) {
#pragma unroll 1
                for (int n = 0; n < 1000; n++) {
                    const uint32_t now = now_ns();
                    if ((int)(due - now) <= 0) break;
                    __nanosleep(min((now ^ due) >> 1, 1023u));
                }
                mbar_wait2(w_slot, w_depth);
                tma3d(dst, tm, cx, cy, 0, bars + 8 * (B_FULL + s));
            }
            __syncwarp();
        }
    }
}

typedef CUresult (*EncodeFn)(CUtensorMap*, CUtensorMapDataType, cuuint32_t, void*, const cuuint64_t*, const cuuint64_t*,
                             const cuuint32_t*, const cuuint32_t*, CUtensorMapInterleave, CUtensorMapSwizzle,
                             CUtensorMapL2promotion, CUtensorMapFloatOOBfill);

void make_map(EncodeFn f, CUtensorMap* m, const void* ptr, int rank, const cuuint64_t* dims, const cuuint64_t* strides, const cuuint32_t* box, CUtensorMapSwizzle sw) {
    const cuuint32_t es[5] = {1, 1, 1, 1, 1};
    f(m, CU_TENSOR_MAP_DATA_TYPE_BFLOAT16, rank, (void*)ptr, dims, strides, box, es, CU_TENSOR_MAP_INTERLEAVE_NONE, sw,
      CU_TENSOR_MAP_L2_PROMOTION_L2_128B, CU_TENSOR_MAP_FLOAT_OOB_FILL_NONE);
}

}

extern "C" void kernel_launch(void* const* d_in, const int* in_sizes, int n_in, void* d_out, int out_size) {
    static EncodeFn enc = nullptr;
    static void* ex = nullptr;
    if (!enc) {
        void* fn = nullptr;
        cudaDriverEntryPointQueryResult qr;
        cudaGetDriverEntryPoint("cuTensorMapEncodeTiled", &fn, cudaEnableDefault, &qr);
        enc = (EncodeFn)fn;
        cudaFuncSetAttribute(fused_kernel, cudaFuncAttributeMaxDynamicSharedMemorySize, SMEM_BYTES);
        cudaGetSymbolAddress(&ex, g_ex);
    }
    CUtensorMap tgu, td, tx, tr, to;
    const char *wg = (const char*)d_in[9], *wu = (const char*)d_in[10];
    const bool swap = wu < wg;
    {
        const cuuint64_t dims[3] = {F_, D_, 2}, str[2] = {F_ * 2, (cuuint64_t)(swap ? wg - wu : wu - wg)};
        const cuuint32_t box[3] = {32, 64, 2};
        make_map(enc, &tgu, swap ? wu : wg, 3, dims, str, box, CU_TENSOR_MAP_SWIZZLE_64B);
    }
    {
        const cuuint64_t dims[3] = {D_, F_, 1}, str[2] = {D_ * 2, (cuuint64_t)D_ * 2 * F_};
        const cuuint32_t box[3] = {16, 256, 1};
        make_map(enc, &td, d_in[11], 3, dims, str, box, CU_TENSOR_MAP_SWIZZLE_32B);
    }
    {
        const cuuint64_t dims[5] = {D_, 2, 2, L_ / 16, 4}, str[4] = {D_ * 2 * 8, D_ * 2, D_ * 2 * 16, D_ * 2 * 2};
        const cuuint32_t box[5] = {16, 2, 2, 16, 4}, obox[5] = {16, 2, 2, 8, 1};
        make_map(enc, &tx, d_in[0], 5, dims, str, box, CU_TENSOR_MAP_SWIZZLE_32B);
        make_map(enc, &to, d_out, 5, dims, str, obox, CU_TENSOR_MAP_SWIZZLE_32B);
    }
    {
        const cuuint64_t dims[4] = {256, 4, L_ / 64, 64}, str[3] = {512, D_ * 2 * 64, D_ * 2};
        const cuuint32_t box[4] = {256, 4, 4, 1};
        make_map(enc, &tr, d_in[0], 4, dims, str, box, CU_TENSOR_MAP_SWIZZLE_NONE);
    }
    Params p;
    p.u = (const bf16*)d_in[0]; p.logA = (const bf16*)d_in[1]; p.Aim = (const bf16*)d_in[2];
    p.Cre = (const bf16*)d_in[3]; p.Cim = (const bf16*)d_in[4]; p.logdt = (const bf16*)d_in[5];
    p.Dskip = (const bf16*)d_in[6]; p.wr = (const bf16*)d_in[8]; p.gatew = (const bf16*)d_in[12];
    p.out = (bf16*)d_out;
    p.ex = (Exchange*)ex;
    p.zero = 0;
    p.swap_gu = swap ? 4096 : 0;
    fused_kernel<<<NCTA, NTHREADS, SMEM_BYTES>>>(p, tgu, td, tx, tr, to);
}
```

```cpp
#include <cuda_runtime.h>
#include <cuda_bf16.h>
#include <cuda_fp16.h>
#include <cuda.h>
#include <stdint.h>

typedef __nv_bfloat16 bf16;

namespace {

constexpr int L_ = 2048, D_ = 1024, F_ = 3584;
constexpr int NCTA = 130;
constexpr int NTHREADS = 512;
constexpr int MAIN_W0 = 4;
#define T_W 1600
#define DT_G 316
#define DT_D 344
#define DEPTH_G 5
#define DEPTH_D 3
#define H_WAIT 2
#define DN_PRE 5
#define PSLEEP 0
#define GU_BATCH 0
#define FENCES 16
#define MIX0_AT 2
#define MIX1_AT 4
#define SEND0_AT (MIX0_AT + 1)
#define SEND1_AT (MIX1_AT + 1)
#define DUP_MOV 2
#define KD_AT 7
#define KD_ORDER 0
#define STG_FROM 4
#define DV 0
#define SO 0
#define DU 1
#define FB_BLK 1
#define ZR p.zero
#define UNI_WARP 1
#define UNI_V 1
#define A_REUSE 0
#define MAIN_REGS "176"
#define HELP_REGS "32"
constexpr int kDenseUnroll = DU;
constexpr int GU_PRE = 6;
constexpr int NGU_CTA = 112;

constexpr int NSLOT    = 10;
constexpr int NST_GU   = 16, NST = 23;
constexpr int OFF_RING = 0;
constexpr int OFF_XROW = 53248, X_SLOT = 6;
constexpr int OFF_XSEL = 69632, XS_ROW = 2064;
constexpr int OFF_DP   = OFF_XSEL + 8192;
constexpr int OFF_S    = 87040;
constexpr int ALT0     = OFF_S + 32768, ALT1 = OFF_S - 512;
constexpr int A_YIN    = 32, Y_CH = 2064;
constexpr int A_SLOT   = 16896, ALT_SLOT = 8;
constexpr int U_PL     = 1184;
constexpr int U_CH     = 4752;
constexpr int OFF_U    = 153088;
constexpr int T_CH     = 4112;
constexpr int OFF_TAB  = 191104;
constexpr int T_R2     = 2176, T2_S = 208;
constexpr int T_R3     = 3040, T3_S = 336;
constexpr int OFF_GP   = 224000;
constexpr int OFF_BAND = 228096;
constexpr int OFF_MISC = 229376;
constexpr int M_BARS   = OFF_MISC;
constexpr int M_IDX    = OFF_MISC + 704;
constexpr int M_RSEL   = OFF_MISC + 736;
constexpr int M_BMAP   = OFF_MISC + 768;
constexpr int M_MX     = OFF_MISC + 896;
constexpr int M_SC     = OFF_MISC + 960;
constexpr int M_RG     = OFF_MISC + 1024;
constexpr int SMEM_BYTES = OFF_MISC + 3072;

constexpr int B_FULL = 0, B_EMPTY = NST, B_S = B_EMPTY + NST - NSLOT, B_XS = B_S + 4, B_TD = B_XS + 2, B_SC = B_TD + 1, B_G = B_SC + 1, B_GL = B_G + 1, B_NONE = B_GL + 1, B_DP = B_NONE + 1, B_Y = B_DP + 1,
              B_SD = B_Y + 4, B_KD = B_SD + 1, B_U = B_KD + 1, B_TS = B_U + 1, B_XF = B_TS + 1, B_X = B_XF + 1, NBAR = B_X + 4;
static_assert(NBAR <= 84, "barrier area");

struct Exchange {
    unsigned epoch, pad[31];
    uint4 h[8 * F_ / 8];
    uint4 r[L_ / 4];
    uint4 g[L_ / 4];
    uint2 top[16];
};
__device__ __align__(128) Exchange g_ex;

struct Params {
    const bf16 *logA, *Aim, *Cre, *Cim, *logdt, *Dskip, *u, *wr, *gatew;
    bf16* out;
    Exchange* ex;
    uint32_t zero;
    uint32_t swap_gu;
};

#define TSTAMP(i) do {} while (0)
#define CSTAMP(i) do {} while (0)
#define TSDUMP(mask) do {} while (0)
#define DBG_PARAMS
#define DBG_ARGS

__device__ __forceinline__ uint32_t smem_u32(const void* p) { return (uint32_t)__cvta_generic_to_shared(p); }
__device__ __forceinline__ void mbar_init(uint32_t b, uint32_t c) { asm volatile("mbarrier.init.shared::cta.b64 [%0], %1;" :: "r"(b), "r"(c) : "memory"); }
__device__ __forceinline__ void mbar_expect(uint32_t b, uint32_t tx) { asm volatile("mbarrier.arrive.expect_tx.shared::cta.b64 _, [%0], %1;" :: "r"(b), "r"(tx) : "memory"); }
__device__ __forceinline__ void mbar_arrive(uint32_t b) { asm volatile("mbarrier.arrive.shared::cta.b64 _, [%0];" :: "r"(b) : "memory"); }
#define WSLEEP "100"
#define W2SLEEP "40"
__device__ __forceinline__ void mbar_wait(uint32_t b) {
    asm volatile("{\n\t.reg .pred p, q;\n\t.reg .u32 n;\n\tmov.u32 n, 0;\n"
                 "W%=:\n\tmbarrier.try_wait.parity.shared::cta.b64 p, [%0], 0;\n\t"
                 "@p bra D%=;\n\tnanosleep.u32 " WSLEEP ";\n\tadd.u32 n, n, 1;\n\tsetp.lt.u32 q, n, 4194304;\n\t@q bra W%=;\n"
                 "D%=:\n\t}" :: "r"(b) : "memory");
}
__device__ __forceinline__ void mbar_spin(uint32_t b) {
    asm volatile("{\n\t.reg .pred p, q;\n\t.reg .u32 n;\n\tmov.u32 n, 0;\n"
                 "W%=:\n\tmbarrier.try_wait.parity.shared::cta.b64 p, [%0], 0;\n\t"
                 "@p bra D%=;\n\tadd.u32 n, n, 1;\n\tsetp.lt.u32 q, n, 4194304;\n\t@q bra W%=;\n"
                 "D%=:\n\t}" :: "r"(b) : "memory");
}
__device__ __forceinline__ void mbar_wait2(uint32_t a, uint32_t b) {
    asm volatile("{\n\t.reg .pred p, q;\n\t.reg .u32 n;\n\tmov.u32 n, 0;\n"
                 "W%=:\n\tmbarrier.try_wait.parity.shared::cta.b64 p, [%0], 0;\n\tmbarrier.try_wait.parity.shared::cta.b64 q, [%1], 0;\n\tand.pred p, p, q;\n\t"
                 "@p bra D%=;\n\tnanosleep.u32 " W2SLEEP ";\n\tadd.u32 n, n, 1;\n\tsetp.lt.u32 q, n, 4194304;\n\t@q bra W%=;\n"
                 "D%=:\n\t}" :: "r"(a), "r"(b) : "memory");
}
template <int N, int STEP>
__device__ __forceinline__ void mbar_wait_n(uint32_t b) {
#pragma unroll 1
    for (int n = 0; n < 4194304; n++) {
        uint32_t ok = 1;
#pragma unroll
        for (int i = 0; i < N; i++) {
            uint32_t d;
            asm volatile("{ .reg .pred p; mbarrier.try_wait.parity.shared::cta.b64 p, [%1], 0; selp.u32 %0, 1, 0, p; }" : "=r"(d) : "r"(b + STEP * i) : "memory");
            ok &= d;
        }
        if (ok) break;
    }
}
__device__ __forceinline__ unsigned ld_epoch(const Exchange* e) { unsigned v; asm volatile("ld.volatile.global.u32 %0, [%1];" : "=r"(v) : "l"(e) : "memory"); return v; }
__device__ __forceinline__ uint32_t now_ns() { uint32_t t; asm volatile("mov.u32 %0, %globaltimer_lo;" : "=r"(t)); return t; }
__device__ __forceinline__ uint32_t mapa(uint32_t addr, uint32_t rank) { uint32_t r; asm("mapa.shared::cluster.u32 %0, %1, %2;" : "=r"(r) : "r"(addr), "r"(rank)); return r; }
__device__ __forceinline__ void bulk_load(uint32_t dst, const void* src, uint32_t bytes, uint32_t bar) {
    asm volatile("cp.async.bulk.shared::cluster.global.mbarrier::complete_tx::bytes [%0], [%1], %2, [%3];" :: "r"(dst), "l"(src), "r"(bytes), "r"(bar) : "memory");
}
__device__ __forceinline__ void bulk_load_both(uint32_t dst, const void* src, uint32_t bytes, uint32_t bar) {
    asm volatile("{ .reg .pred p; elect.sync _|p, 0xffffffff;\n\t@p cp.async.bulk.shared::cluster.global.mbarrier::complete_tx::bytes.multicast::cluster [%0], [%1], %2, [%3], %4; }"
                 :: "r"(dst), "l"(src), "r"(bytes), "r"(bar), "h"((unsigned short)3) : "memory");
}
__device__ __forceinline__ void tma3d(uint32_t dst, const CUtensorMap* tm, int c0, int c1, int c2, uint32_t bar) {
    asm volatile("cp.async.bulk.tensor.3d.shared::cluster.global.mbarrier::complete_tx::bytes [%0], [%1, {%3, %4, %5}], [%2];"
        :: "r"(dst), "l"(tm), "r"(bar), "r"(c0), "r"(c1), "r"(c2) : "memory");
}
__device__ __forceinline__ void tma4d_warp(uint32_t dst, const CUtensorMap* tm, int c2, int c3, uint32_t bar) {
    asm volatile("{ .reg .pred p; elect.sync _|p, 0xffffffff;\n\t@p cp.async.bulk.tensor.4d.shared::cluster.global.mbarrier::complete_tx::bytes [%0], [%1, {%5, %5, %3, %4}], [%2]; }"
        :: "r"(dst), "l"(tm), "r"(bar), "r"(c2), "r"(c3), "r"(0) : "memory");
}
__device__ __forceinline__ void tma5d_both(uint32_t dst, const CUtensorMap* tm, int c0, int c3, uint32_t bar) {
    asm volatile("{ .reg .pred p; elect.sync _|p, 0xffffffff;\n\t@p cp.async.bulk.tensor.5d.shared::cluster.global.mbarrier::complete_tx::bytes.multicast::cluster [%0], [%1, {%3, %5, %5, %4, %5}], [%2], %6; }"
        :: "r"(dst), "l"(tm), "r"(bar), "r"(c0), "r"(c3), "r"(0), "h"((unsigned short)3) : "memory");
}
__device__ __forceinline__ void cluster_next() { asm volatile("barrier.cluster.wait.acquire.aligned;\n\tbarrier.cluster.arrive.relaxed.aligned;" ::: "memory"); }
__device__ __forceinline__ void st_async16(uint32_t dst, uint32_t x, uint32_t y, uint32_t z, uint32_t w, uint32_t bar) {
    asm volatile("st.async.weak.shared::cluster.mbarrier::complete_tx::bytes.v4.b32 [%0], {%1,%2,%3,%4}, [%5];"
                 :: "r"(dst), "r"(x), "r"(y), "r"(z), "r"(w), "r"(bar) : "memory");
}
__device__ __forceinline__ void st_async4(uint32_t dst, uint32_t v, uint32_t bar) {
    asm volatile("st.async.weak.shared::cluster.mbarrier::complete_tx::bytes.b32 [%0], %1, [%2];" :: "r"(dst), "r"(v), "r"(bar) : "memory");
}
__device__ __forceinline__ void bar_sync(int id, int n) { asm volatile("bar.sync %0, %1;" :: "r"(id), "r"(n) : "memory"); }
__device__ __forceinline__ void bar_arrive(int id, int n) { asm volatile("bar.arrive %0, %1;" :: "r"(id), "r"(n) : "memory"); }
__device__ __forceinline__ void cp16(uint32_t dst, const void* src) { asm volatile("cp.async.cg.shared.global [%0], [%1], 16;" :: "r"(dst), "l"(src) : "memory"); }
__device__ __forceinline__ void cp_wait_all() { asm volatile("cp.async.wait_all;" ::: "memory"); }
__device__ __forceinline__ uint32_t ldg16(const void* p) { uint32_t v; asm volatile("ld.global.nc.u16 %0, [%1];" : "=r"(v) : "l"(p)); return v; }
__device__ __forceinline__ uint2 ldg64(const void* p) { uint2 v; asm volatile("ld.global.nc.v2.u32 {%0,%1}, [%2];" : "=r"(v.x), "=r"(v.y) : "l"(p)); return v; }
__device__ __forceinline__ uint4 ldg128(const void* p) { uint4 v; asm volatile("ld.global.nc.v4.u32 {%0,%1,%2,%3}, [%4];" : "=r"(v.x), "=r"(v.y), "=r"(v.z), "=r"(v.w) : "l"(p)); return v; }
__device__ __forceinline__ uint4 ld_gpu128(const void* p) { uint4 v; asm volatile("ld.relaxed.gpu.global.v4.u32 {%0,%1,%2,%3}, [%4];" : "=r"(v.x), "=r"(v.y), "=r"(v.z), "=r"(v.w) : "l"(p) : "memory"); return v; }
__device__ __forceinline__ void st_gpu32(void* p, uint32_t v) { asm volatile("st.relaxed.gpu.global.u32 [%0], %1;" :: "l"(p), "r"(v) : "memory"); }
__device__ __forceinline__ void st_gpu128(void* p, const uint4& v) { asm volatile("st.relaxed.gpu.global.v4.u32 [%0], {%1,%2,%3,%4};" :: "l"(p), "r"(v.x), "r"(v.y), "r"(v.z), "r"(v.w) : "memory"); }

__device__ __forceinline__ void ldsm4(uint32_t a, uint32_t& r0, uint32_t& r1, uint32_t& r2, uint32_t& r3) {
    asm volatile("ldmatrix.sync.aligned.m8n8.x4.shared.b16 {%0,%1,%2,%3}, [%4];" : "=r"(r0), "=r"(r1), "=r"(r2), "=r"(r3) : "r"(a) : "memory");
}
__device__ __forceinline__ void ldsm2(uint32_t a, uint32_t& r0, uint32_t& r1) {
    asm volatile("ldmatrix.sync.aligned.m8n8.x2.shared.b16 {%0,%1}, [%2];" : "=r"(r0), "=r"(r1) : "r"(a) : "memory");
}
__device__ __forceinline__ void ldsm4t(uint32_t a, uint32_t& r0, uint32_t& r1, uint32_t& r2, uint32_t& r3) {
    asm volatile("ldmatrix.sync.aligned.m8n8.x4.trans.shared.b16 {%0,%1,%2,%3}, [%4];" : "=r"(r0), "=r"(r1), "=r"(r2), "=r"(r3) : "r"(a) : "memory");
}
__device__ __forceinline__ uint32_t lds16(uint32_t a) { uint32_t v; asm volatile("ld.shared.u16 %0, [%1];" : "=r"(v) : "r"(a) : "memory"); return v; }
__device__ __forceinline__ uint32_t lds32(uint32_t a) { uint32_t v; asm volatile("ld.shared.u32 %0, [%1];" : "=r"(v) : "r"(a) : "memory"); return v; }
__device__ __forceinline__ uint2 lds64(uint32_t a) { uint2 v; asm volatile("ld.shared.v2.u32 {%0,%1}, [%2];" : "=r"(v.x), "=r"(v.y) : "r"(a) : "memory"); return v; }
__device__ __forceinline__ uint4 lds128(uint32_t a) { uint4 v; asm volatile("ld.shared.v4.u32 {%0,%1,%2,%3}, [%4];" : "=r"(v.x), "=r"(v.y), "=r"(v.z), "=r"(v.w) : "r"(a) : "memory"); return v; }
__device__ __forceinline__ void sts16(uint32_t a, uint32_t v) { asm volatile("st.shared.u16 [%0], %1;" :: "r"(a), "r"(v) : "memory"); }
__device__ __forceinline__ void sts32(uint32_t a, uint32_t v) { asm volatile("st.shared.u32 [%0], %1;" :: "r"(a), "r"(v) : "memory"); }
__device__ __forceinline__ void sts64(uint32_t a, uint32_t x, uint32_t y) { asm volatile("st.shared.v2.u32 [%0], {%1,%2};" :: "r"(a), "r"(x), "r"(y) : "memory"); }
__device__ __forceinline__ void sts128(uint32_t a, uint32_t x, uint32_t y, uint32_t z, uint32_t w) { asm volatile("st.shared.v4.u32 [%0], {%1,%2,%3,%4};" :: "r"(a), "r"(x), "r"(y), "r"(z), "r"(w) : "memory"); }
__device__ __forceinline__ void sts16_if(bool p, uint32_t a, uint32_t v) { asm volatile("{ .reg .pred q; setp.ne.u32 q, %2, 0; @q st.shared.u16 [%0], %1; }" :: "r"(a), "h"((unsigned short)v), "r"((uint32_t)p) : "memory"); }
__device__ __forceinline__ void sts128_if(bool p, uint32_t a, uint32_t x, uint32_t y, uint32_t z, uint32_t w) {
    asm volatile("{ .reg .pred q; setp.ne.u32 q, %5, 0; @q st.shared.v4.u32 [%0], {%1,%2,%3,%4}; }" :: "r"(a), "r"(x), "r"(y), "r"(z), "r"(w), "r"((uint32_t)p) : "memory");
}
__device__ __forceinline__ void stsf(uint32_t a, float v) { asm volatile("st.shared.f32 [%0], %1;" :: "r"(a), "f"(v) : "memory"); }
__device__ __forceinline__ float ldsf(uint32_t a) { float v; asm volatile("ld.shared.f32 %0, [%1];" : "=f"(v) : "r"(a) : "memory"); return v; }

__device__ __forceinline__ void mma_bf(float (&d)[4], uint32_t a0, uint32_t a1, uint32_t a2, uint32_t a3, uint32_t b0, uint32_t b1) {
    asm volatile("mma.sync.aligned.m16n8k16.row.col.f32.bf16.bf16.f32 {%0,%1,%2,%3}, {%4,%5,%6,%7}, {%8,%9}, {%0,%1,%2,%3};"
        : "+f"(d[0]), "+f"(d[1]), "+f"(d[2]), "+f"(d[3]) : "r"(a0), "r"(a1), "r"(a2), "r"(a3), "r"(b0), "r"(b1));
}
__device__ __forceinline__ void widen_bf(float (&d)[4], uint32_t a0, uint32_t a1, uint32_t b) {
    asm volatile("mma.sync.aligned.m16n8k8.row.col.f32.bf16.bf16.f32 {%0,%1,%2,%3}, {%4,%5}, {%6}, {%7,%7,%7,%7};"
        : "=f"(d[0]), "=f"(d[1]), "=f"(d[2]), "=f"(d[3]) : "r"(a0), "r"(a1), "r"(b), "f"(0.f));
}
__device__ __forceinline__ void widen_h(float (&d)[4], const uint32_t (&a)[2], uint32_t b) {
    asm volatile("mma.sync.aligned.m16n8k8.row.col.f32.f16.f16.f32 {%0,%1,%2,%3}, {%4,%5}, {%6}, {%7,%7,%7,%7};"
        : "=f"(d[0]), "=f"(d[1]), "=f"(d[2]), "=f"(d[3]) : "r"(a[0]), "r"(a[1]), "r"(b), "f"(0.f));
}
__device__ __forceinline__ void widen_add_h(float (&d)[4], const uint32_t (&a)[2], uint32_t b, const float (&c)[4]) {
    asm volatile("mma.sync.aligned.m16n8k8.row.col.f32.f16.f16.f32 {%0,%1,%2,%3}, {%4,%5}, {%6}, {%7,%8,%9,%10};"
        : "=f"(d[0]), "=f"(d[1]), "=f"(d[2]), "=f"(d[3]) : "r"(a[0]), "r"(a[1]), "r"(b), "f"(c[0]), "f"(c[1]), "f"(c[2]), "f"(c[3]));
}
__device__ __forceinline__ void mma_h(uint32_t (&d)[2], const uint32_t (&a)[4], uint32_t b0, uint32_t b1) {
    asm volatile("mma.sync.aligned.m16n8k16.row.col.f16.f16.f16.f16 {%0,%1}, {%2,%3,%4,%5}, {%6,%7}, {%0,%1};"
        : "+r"(d[0]), "+r"(d[1]) : "r"(a[0]), "r"(a[1]), "r"(a[2]), "r"(a[3]), "r"(b0), "r"(b1));
}
__device__ __forceinline__ void mma_h_z(uint32_t& d0, uint32_t& d1, const uint32_t (&a)[4], uint32_t b0, uint32_t b1) {
    asm volatile("mma.sync.aligned.m16n8k16.row.col.f16.f16.f16.f16 {%0,%1}, {%2,%3,%4,%5}, {%6,%7}, {%8,%8};"
        : "=r"(d0), "=r"(d1) : "r"(a[0]), "r"(a[1]), "r"(a[2]), "r"(a[3]), "r"(b0), "r"(b1), "r"(0u));
}
__device__ __forceinline__ void mma_h2(uint32_t& d0, uint32_t& d1, const uint32_t (&a)[4], uint32_t b0, uint32_t b1) {
    asm volatile("mma.sync.aligned.m16n8k16.row.col.f16.f16.f16.f16 {%0,%1}, {%2,%3,%4,%5}, {%6,%7}, {%0,%1};"
        : "+r"(d0), "+r"(d1) : "r"(a[0]), "r"(a[1]), "r"(a[2]), "r"(a[3]), "r"(b0), "r"(b1));
}
__device__ __forceinline__ void mma_h_k8(uint32_t& d0, uint32_t& d1, uint32_t a0, uint32_t a1, uint32_t b) {
    asm volatile("mma.sync.aligned.m16n8k8.row.col.f16.f16.f16.f16 {%0,%1}, {%2,%3}, {%4}, {%0,%1};" : "+r"(d0), "+r"(d1) : "r"(a0), "r"(a1), "r"(b));
}
__device__ __forceinline__ void mma_h_k8_z(uint32_t (&d)[2], uint32_t a0, uint32_t a1, uint32_t b) {
    asm volatile("mma.sync.aligned.m16n8k8.row.col.f16.f16.f16.f16 {%0,%1}, {%2,%3}, {%4}, {%5,%5};" : "=r"(d[0]), "=r"(d[1]) : "r"(a0), "r"(a1), "r"(b), "r"(0u));
}
__device__ __forceinline__ uint32_t pack_bf(float lo, float hi) { uint32_t r; asm("cvt.rn.bf16x2.f32 %0, %1, %2;" : "=r"(r) : "f"(hi), "f"(lo)); return r; }
__device__ __forceinline__ uint32_t pack_h(float lo, float hi) { uint32_t r; asm("cvt.rn.f16x2.f32 %0, %1, %2;" : "=r"(r) : "f"(hi), "f"(lo)); return r; }
__device__ __forceinline__ float bf_lo(uint32_t v) { return __uint_as_float(v << 16); }
__device__ __forceinline__ float bf_hi(uint32_t v) { return __uint_as_float(v & 0xffff0000u); }
__device__ __forceinline__ float bf_round(float x) { return __uint_as_float(pack_bf(0.f, x) & 0xffff0000u); }
__device__ __forceinline__ uint32_t hmul2_bf(uint32_t a, uint32_t b) { uint32_t r; asm("mul.rn.bf16x2 %0, %1, %2;" : "=r"(r) : "r"(a), "r"(b)); return r; }
__device__ __forceinline__ uint32_t hadd2_bf(uint32_t a, uint32_t b) { uint32_t r; asm("add.rn.bf16x2 %0, %1, %2;" : "=r"(r) : "r"(a), "r"(b)); return r; }
__device__ __forceinline__ uint32_t hfma2_bf(uint32_t a, uint32_t b, uint32_t c) { uint32_t r; asm("fma.rn.bf16x2 %0, %1, %2, %3;" : "=r"(r) : "r"(a), "r"(b), "r"(c)); return r; }
__device__ __forceinline__ uint32_t hi_mul_bf(uint32_t a, uint32_t b) { uint32_t r; asm("{ .reg .b16 l, h; .reg .b32 t; mov.b32 {l, h}, %1; mov.b32 t, {h, h}; mul.rn.bf16x2 %0, t, %2; }" : "=r"(r) : "r"(a), "r"(b)); return r; }
__device__ __forceinline__ uint32_t lo_fma_bf(uint32_t a, uint32_t b, uint32_t c) { uint32_t r; asm("{ .reg .b16 l, h; .reg .b32 t; mov.b32 {l, h}, %1; mov.b32 t, {l, l}; fma.rn.bf16x2 %0, t, %2, %3; }" : "=r"(r) : "r"(a), "r"(b), "r"(c)); return r; }
__device__ __forceinline__ uint32_t amax2_bf(uint32_t m, uint32_t v) { uint32_t r; asm("max.xorsign.abs.bf16x2 %0, %1, %2;" : "=r"(r) : "r"(m), "r"(v)); return r; }
__device__ __forceinline__ uint32_t amax2_h(uint32_t m, uint32_t v) { uint32_t r; asm("max.xorsign.abs.f16x2 %0, %1, %2;" : "=r"(r) : "r"(m), "r"(v)); return r; }
__device__ __forceinline__ uint32_t hadd(uint32_t a, uint32_t b) { uint32_t r; asm("add.rn.f16x2 %0, %1, %2;" : "=r"(r) : "r"(a), "r"(b)); return r; }
__device__ __forceinline__ uint32_t hsub(uint32_t a, uint32_t b) { uint32_t r; asm("sub.rn.f16x2 %0, %1, %2;" : "=r"(r) : "r"(a), "r"(b)); return r; }
__device__ __forceinline__ uint32_t hsub2(uint32_t a, uint32_t b) { uint32_t r; asm("sub.rn.ftz.f16x2 %0, %1, %2;" : "=r"(r) : "r"(a), "r"(b)); return r; }
__device__ __forceinline__ uint32_t hmul(uint32_t a, uint32_t b) { uint32_t r; asm("mul.rn.f16x2 %0, %1, %2;" : "=r"(r) : "r"(a), "r"(b)); return r; }
__device__ __forceinline__ uint32_t hfma(uint32_t a, uint32_t b, uint32_t c) { uint32_t r; asm("fma.rn.f16x2 %0, %1, %2, %3;" : "=r"(r) : "r"(a), "r"(b), "r"(c)); return r; }
__device__ __forceinline__ uint32_t hfms(uint32_t a, uint32_t b, uint32_t c) { uint32_t r; asm("{ .reg .b32 t; neg.f16x2 t, %3; fma.rn.f16x2 %0, %1, %2, t; }" : "=r"(r) : "r"(a), "r"(b), "r"(c)); return r; }
__device__ __forceinline__ uint32_t warp_max16(uint32_t m) { return __reduce_max_sync(0xffffffffu, max(m & 0x7fffu, (m >> 16) & 0x7fffu)); }
__device__ __forceinline__ float ex2f(float x) { float r; asm("ex2.approx.ftz.f32 %0, %1;" : "=f"(r) : "f"(x)); return r; }

__device__ __forceinline__ float exp_acc(float x) {
    const float t = x * 1.4426950216293335f;
    const float r = fmaf(x, 1.4426950216293335f, -t) + x * 1.9259629911266175e-8f;
    return ex2f(t) * fmaf(r, 0.6931471805599453f, 1.f);
}
__device__ __forceinline__ float sigmoid_f(float x) { return __fdividef(1.f, 1.f + ex2f(-x * 1.4426950408889634f)); }
__device__ __forceinline__ void cexp(float l2, float th, float& zr, float& zi) {
    const float mag = ex2f(l2);
    const float k = (th * 0.15915494309189535f + 12582912.f) - 12582912.f;
    float r = fmaf(-k, 6.2831854820251465f, th);
    r = fmaf(-k, -1.7484555314695172e-7f, r);
    zr = mag * __cosf(r);
    zi = mag * __sinf(r);
}
struct hc { uint32_t re, im; };
__device__ __forceinline__ hc cmul(const hc& a, const hc& b) { return {hfms(a.re, b.re, hmul(a.im, b.im)), hfma(a.re, b.im, hmul(a.im, b.re))}; }
__device__ __forceinline__ hc cmulc(const hc& a, const hc& b) { return {hfma(a.re, b.re, hmul(a.im, b.im)), hfms(a.im, b.re, hmul(a.re, b.im))}; }
struct fc2 { float r[2], i[2]; };
__device__ __forceinline__ void csq(fc2& z) {
#pragma unroll
    for (int m = 0; m < 2; m++) {
        const float r = fmaf(z.r[m], z.r[m], -(z.i[m] * z.i[m]));
        asm("{ .reg .f32 t; mul.f32 t, %0, %1; mul.f32 %0, t, 0f40000000; }" : "+f"(z.i[m]) : "f"(z.r[m]));
        z.r[m] = r;
    }
}
__device__ __forceinline__ hc pk(const fc2& z) { return {pack_h(z.r[0], z.r[1]), pack_h(z.i[0], z.i[1])}; }
__device__ __forceinline__ void csq_conj(fc2& z) {
#pragma unroll
    for (int m = 0; m < 2; m++) {
        const float r = fmaf(z.r[m], z.r[m], -(z.i[m] * z.i[m]));
        asm("{ .reg .f32 t, n; neg.f32 n, %1; mul.f32 t, %0, n; mul.f32 %0, t, 0f40000000; }" : "+f"(z.i[m]) : "f"(z.r[m]));
        z.r[m] = r;
    }
}

struct Powers { hc C, z1, z2, z4, c8, c16, c32, c64, z128, z256, z512, z1024; };
__device__ __forceinline__ void kg_powers(Powers& q, uint32_t la, uint32_t ai, uint32_t cr, uint32_t ci, float dt, float cf) {
    fc2 z, y;
    const float dtl = -dt * 1.4426950408889634f;
    const uint32_t eb = pack_bf(ex2f(bf_lo(la) * 1.4426950408889634f), ex2f(bf_hi(la) * 1.4426950408889634f));
    const float l2[2] = {bf_lo(eb) * dtl, bf_hi(eb) * dtl}, th[2] = {bf_lo(ai) * dt, bf_hi(ai) * dt};
#pragma unroll
    for (int m = 0; m < 2; m++) { cexp(l2[m], th[m], z.r[m], z.i[m]); cexp(l2[m] * 128.f, th[m] * 128.f, y.r[m], y.i[m]); }
    q.C.re = pack_h(bf_lo(cr) * cf, bf_hi(cr) * cf);
    q.C.im = pack_h(bf_lo(ci) * cf, bf_hi(ci) * cf);
    q.z1 = pk(z); csq(z); q.z128 = pk(y); csq(y);
    q.z2 = pk(z); csq(z); q.z256 = pk(y); csq(y);
    q.z4 = pk(z); csq_conj(z); q.z512 = pk(y); csq(y);
    q.c8 = pk(z); csq(z); q.z1024 = pk(y);
    q.c16 = pk(z); csq(z);
    q.c32 = pk(z); csq(z);
    q.c64 = pk(z);
}
struct Rows { hc ta[8], tb[8], tc[8], pp[8]; };
#define PUT(a0, a1, row, a, b) sts128((((row) & 1) ? (a1) : (a0)) + (row) * 512, (a).re, (a).im, (b).re, (b).im)
template <bool FIRST>
__device__ __forceinline__ void kg_rows(Rows& w, const Powers& q, uint32_t t0, uint32_t t1, uint32_t u0, uint32_t u1, uint32_t uc, uint32_t zr, uint32_t (&Rl)[2]) {
    w.ta[0] = q.C; w.ta[1] = cmul(q.C, q.z1); w.ta[2] = cmul(q.C, q.z2); w.ta[4] = cmul(q.C, q.z4); w.tb[0] = cmul(q.C, q.z256); w.tb[4] = cmul(q.C, q.z512);
    PUT(t0, t1, 0, w.ta[0], w.tb[0]); PUT(t0, t1, 4, w.ta[4], w.tb[4]);
    w.tb[1] = cmul(w.ta[2], q.z256); w.tb[2] = cmul(w.ta[4], q.z256);
    PUT(t0, t1, 1, w.ta[1], w.tb[1]); PUT(t0, t1, 2, w.ta[2], w.tb[2]);
    w.ta[3] = cmul(w.ta[1], q.z2); w.ta[6] = cmul(w.ta[2], q.z4); w.ta[5] = cmul(w.ta[1], q.z4); w.tb[5] = cmul(w.ta[4], q.z512); w.tb[6] = cmul(w.tb[0], q.z512);
    PUT(t0, t1, 5, w.ta[5], w.tb[5]); PUT(t0, t1, 6, w.ta[6], w.tb[6]);
    w.tb[3] = cmul(w.ta[6], q.z256); w.ta[7] = cmul(w.ta[3], q.z4); w.tb[7] = cmul(w.tb[2], q.z512);
    PUT(t0, t1, 3, w.ta[3], w.tb[3]); PUT(t0, t1, 7, w.ta[7], w.tb[7]);
    sts64(uc, q.c64.re, q.c64.im);
    w.pp[0] = hc{0x3C003C00u ^ zr, zr}; w.pp[1] = q.c8; w.pp[2] = q.c16; w.pp[4] = q.c32;
    w.tc[0] = cmul(q.C, q.z1024); w.pp[3] = cmul(q.c8, q.c16); w.pp[5] = cmul(q.c8, q.c32); w.pp[6] = cmul(q.c16, q.c32);
    w.tc[2] = cmul(w.tc[0], q.z128); w.tc[4] = cmul(w.tc[0], q.z256); w.tc[1] = cmul(w.tc[0], q.z512); w.pp[7] = cmul(w.pp[3], q.c32);
    PUT(u0, u1, 0, w.tc[0], w.pp[0]); PUT(u0, u1, 1, w.tc[1], w.pp[1]); PUT(u0, u1, 2, w.tc[2], w.pp[2]); PUT(u0, u1, 4, w.tc[4], w.pp[4]);
    w.tc[6] = cmul(w.tc[2], q.z256); w.tc[3] = cmul(w.tc[2], q.z512); w.tc[5] = cmul(w.tc[4], q.z512);
    PUT(u0, u1, 3, w.tc[3], w.pp[3]); PUT(u0, u1, 5, w.tc[5], w.pp[5]); PUT(u0, u1, 6, w.tc[6], w.pp[6]);
    w.tc[7] = cmul(w.tc[6], q.z512);
    PUT(u0, u1, 7, w.tc[7], w.pp[7]);
    const uint32_t last = hfms(w.tc[0].re, q.z1024.re, hmul(w.tc[0].im, q.z1024.im));
    if (FIRST) mma_h_k8_z(Rl, 0x3C003C00u - zr, 0x3C003C00u + zr, last); else mma_h_k8(Rl[0], Rl[1], 0x3C003C00u - zr, 0x3C003C00u + zr, last);
}
#undef PUT
template <bool FIRST>
__device__ __forceinline__ void kg_products(uint32_t rt0, uint32_t rt1, uint32_t ru0, uint32_t ru1, uint32_t rc, uint32_t zr, uint32_t done, int lane,
                                            uint32_t (&Ra)[2][2], uint32_t (&Rb)[2][2], uint32_t (&Rc)[2]) {
    uint4 q1[8], q2[8], cw[8];
    if (!FIRST && KD_ORDER) {
#pragma unroll
        for (int ks = 0; ks < 8; ks++) { q2[ks] = lds128(((ks & 1) ? ru1 : ru0) + (ks >> 1) * 128); if (!(ks & 1)) cw[ks] = lds128(rc + ks * 32); if (ks < 2) q1[ks] = lds128(ks ? rt1 : rt0); }
#pragma unroll
        for (int ks = 2; ks < 8; ks++) q1[ks] = lds128(((ks & 1) ? rt1 : rt0) + (ks >> 1) * 128);
    } else
#pragma unroll
    for (int ks = 0; ks < 8; ks++) {
        q2[ks] = lds128(((ks & 1) ? ru1 : ru0) + (ks >> 1) * 128); if (!(ks & 1)) cw[ks] = lds128(rc + ks * 32); q1[ks] = lds128(((ks & 1) ? rt1 : rt0) + (ks >> 1) * 128);
    }
#pragma unroll
    for (int ks = 0; ks < 8; ks++) {
        const hc p0 = {q2[ks].z, q2[ks].w}, u = (ks & 1) ? hc{cw[ks & 6].z, cw[ks & 6].w} : hc{cw[ks].x, cw[ks].y};
        const hc p1 = cmul(p0, u), p2 = cmul(p1, u), p3 = cmul(p2, u);

        const uint32_t qa[4] = {p0.re ^ zr, p1.re, p0.im ^ zr, p1.im}, qb[4] = {p2.re, p3.re, p2.im, p3.im};
        if (!FIRST && ks == KD_AT) {
            uint32_t all = zr;
#pragma unroll
            for (int i = KD_AT; i < 8; i++) all &= q2[i].x & cw[i & 6].x;
            __syncwarp();
            if (lane == 0) mbar_arrive(done + all);
        }
        if (FIRST && ks == 0) {
            mma_h_z(Rc[0], Rc[1], qa, q2[ks].x, q2[ks].y); mma_h_z(Ra[0][0], Ra[0][1], qa, q1[ks].x, q1[ks].y); mma_h_z(Rb[0][0], Rb[0][1], qa, q1[ks].z, q1[ks].w);
            mma_h_z(Ra[1][0], Ra[1][1], qb, q1[ks].x, q1[ks].y); mma_h_z(Rb[1][0], Rb[1][1], qb, q1[ks].z, q1[ks].w);
        } else {
            mma_h(Rc, qa, q2[ks].x, q2[ks].y); mma_h(Ra[0], qa, q1[ks].x, q1[ks].y); mma_h(Rb[0], qa, q1[ks].z, q1[ks].w);
            mma_h(Ra[1], qb, q1[ks].x, q1[ks].y); mma_h(Rb[1], qb, q1[ks].z, q1[ks].w);
        }
    }
}
__device__ __forceinline__ void kernel_gen(const uint2& la, const uint2& ai, const uint2& cr, const uint2& ci, float dt, float cf, uint32_t TB, uint32_t UB, uint32_t done,
                                           int lane, uint32_t zr, uint32_t (&Ra)[2][2], uint32_t (&Rb)[2][2], uint32_t (&Rc)[2], uint32_t (&Rl)[2]) {
    const int g = lane >> 2, t = lane & 3;
    const uint32_t w0 = lane << 4, w1 = w0 ^ 64, r0 = g * 512 + (((g & 1) << 6) | (t << 4)), r1 = r0 ^ 64;
    const uint32_t t0 = TB + w0, t1 = TB + w1, u0 = UB + w0, u1 = UB + w1;
    const uint32_t uc = UB + 4096 + (lane >> 3) * 64 + t * 16 + (lane & 4) * 2;
    Powers p0, p1;
    Rows w;
    kg_powers(p0, la.x, ai.x, cr.x, ci.x, dt, cf);
    kg_rows<true>(w, p0, t0, t1, u0, u1, uc, zr, Rl);
    kg_powers(p1, la.y, ai.y, cr.y, ci.y, dt, cf);
    __syncwarp();
    kg_products<true>(TB + r0, TB + r1, UB + r0, UB + r1, UB + 4096 + t * 16, zr, done, lane, Ra, Rb, Rc);
    __syncwarp();
    asm volatile("barrier.cluster.wait.acquire.aligned;" ::: "memory");
    kg_rows<false>(w, p1, t0, t1, u0, u1, uc, zr, Rl);
    __syncwarp();
    kg_products<false>(TB + r0, TB + r1, UB + r0, UB + r1, UB + 4096 + t * 16, zr, done, lane, Ra, Rb, Rc);
    __syncwarp();
}

template <int V> struct IC { static constexpr int value = V; };

#define LANE_VARS \
    int tid_; asm volatile("mov.u32 %0, %%tid.x;" : "=r"(tid_)); \
    [[maybe_unused]] const int lane = tid_ & 31, warp = UNI_WARP ? wuni : (tid_ >> 5) - MAIN_W0, g = lane >> 2, t = lane & 3, mi = lane >> 3, r = lane & 7; \
    [[maybe_unused]] const uint32_t TB = sb + OFF_TAB + warp * T_CH, UB = sb + OFF_U + warp * U_CH; \
    [[maybe_unused]] const bool lead = (tid_ == 32 * MAIN_W0)

#define FENCE() do { if (zr) asm volatile("exit;"); } while (0)
template <int ORD>
__device__ __forceinline__ void stream(uint32_t (&D)[8][2], const uint32_t (&Q)[2][4], const uint32_t (&V)[8][2]) {
    if (ORD == 0) {
#pragma unroll
        for (int J = 0; J < 8; J++) mma_h(D[J], Q[0], V[J][0], V[J][1]);
#pragma unroll
        for (int J = 1; J < 8; J++) mma_h(D[J], Q[1], V[J - 1][0], V[J - 1][1]);
    } else if (ORD == 1) {
#pragma unroll
        for (int J = 1; J < 8; J++) mma_h(D[J], Q[1], V[J - 1][0], V[J - 1][1]);
#pragma unroll
        for (int J = 0; J < 8; J++) mma_h(D[J], Q[0], V[J][0], V[J][1]);
    } else {
#pragma unroll
        for (int J = 7; J >= 0; J--) mma_h(D[J], Q[0], V[J][0], V[J][1]);
#pragma unroll
        for (int J = 7; J >= 1; J--) mma_h(D[J], Q[1], V[J - 1][0], V[J - 1][1]);
    }
}
__device__ __forceinline__ void dense_step(uint32_t (&M)[8][2], uint32_t (&Ye)[8][2], uint32_t (&Yo)[8][2], uint32_t (&X)[8][2],
                                           uint32_t (&F)[8][2], uint32_t (&Bq)[2][4], uint32_t ua, uint32_t ta, uint32_t zr) {
    uint32_t E[8][2], A[2][4], S[2][4], G[8][2], Bn[2][2];
    auto load_e = [&]() {
#pragma unroll
        for (int jp = 0; jp < 4; jp++) ldsm4(ua + jp * 256, E[2 * jp][0], E[2 * jp][1], E[2 * jp + 1][0], E[2 * jp + 1][1]);
    };
    auto load_a = [&]() {
#pragma unroll
        for (int h = 0; h < 2; h++) {
            A[h][0] = A_REUSE ? Bq[h][3] ^ zr : lds32(ta + 1024 * h); A[h][1] = lds32(ta + 1024 * h + 32); A[h][3] = lds32(ta + 1024 * h + 64);
            A[h][2] = (DV & 8) ? lds32(ta + 1024 * h + 32 + zr) : A[h][1] ^ zr;
        }
    };
    if (DV & 1) { load_a(); load_e(); } else { load_e(); load_a(); }
    if (DV & 2) {
#pragma unroll
        for (int h = 0; h < 2; h++) { Bn[h][0] = lds32(ta + 1024 * h + 96); Bn[h][1] = lds32(ta + 1024 * h + 128); }
        stream<SO % 3>(Ye, Bq, F);
#pragma unroll
        for (int h = 0; h < 2; h++) { S[h][0] = hadd(A[h][0], A[h][3]); S[h][1] = hadd(A[h][1], Bn[h][0]); S[h][2] = hadd(A[h][2], Bn[h][0]); S[h][3] = hadd(A[h][3], Bn[h][1]); }
#pragma unroll
        for (int J = 0; J < 8; J++) { G[J][0] = hsub(X[J][0], E[J][0]); G[J][1] = hsub(X[J][1], E[J][1]); }
#pragma unroll
        for (int jp = 0; jp < 4; jp++) ldsm4(ua + 2 * U_PL + jp * 256 - 16, X[2 * jp][0], X[2 * jp][1], X[2 * jp + 1][0], X[2 * jp + 1][1]);
        if (DV & 4) FENCE();
        stream<(SO / 9) % 3>(M, S, E);
#pragma unroll
        for (int h = 0; h < 2; h++) { Bq[h][0] = A[h][3] ^ zr; Bq[h][1] = Bn[h][0]; Bq[h][2] = Bn[h][0] ^ zr; Bq[h][3] = Bn[h][1]; }
#pragma unroll
        for (int J = 0; J < 8; J++) { F[J][0] = hsub(X[J][0], E[J][0]); F[J][1] = hsub(X[J][1], E[J][1]); }
        stream<(SO / 3) % 3>(Yo, A, G);
        return;
    }
    stream<SO % 3>(Ye, Bq, F);
#pragma unroll
    for (int J = 0; J < 8; J++) { G[J][0] = hsub(X[J][0], E[J][0]); G[J][1] = hsub(X[J][1], E[J][1]); }
    if (DV & 4) FENCE();
#pragma unroll
    for (int jp = 0; jp < 4; jp++) ldsm4(ua + 2 * U_PL + jp * 256 - 16, X[2 * jp][0], X[2 * jp][1], X[2 * jp + 1][0], X[2 * jp + 1][1]);
#pragma unroll
    for (int h = 0; h < 2; h++) { Bq[h][1] = lds32(ta + 1024 * h + 96); Bq[h][3] = lds32(ta + 1024 * h + 128); Bq[h][0] = A[h][3] ^ zr; Bq[h][2] = Bq[h][1] ^ zr; }
    stream<(SO / 3) % 3>(Yo, A, G);
#pragma unroll
    for (int h = 0; h < 2; h++)
#pragma unroll
        for (int i = 0; i < 4; i++) S[h][i] = hadd(A[h][i], Bq[h][i]);
    if (DV & 16) FENCE();
    stream<(SO / 9) % 3>(M, S, E);
#pragma unroll
    for (int J = 0; J < 8; J++) { F[J][0] = hsub(X[J][0], E[J][0]); F[J][1] = hsub(X[J][1], E[J][1]); }
}

__device__ __forceinline__ int group_tables(uint32_t TB, int lane) {
    const int g = lane >> 2, t = lane & 3;
    const uint4 b4 = lds128(TB + T_R2 + 16 * lane), c4 = lds128(TB + T_R2 + 512 + 16 * lane);
    uint32_t vb[4] = {b4.x, b4.y, b4.z, b4.w}, vc[2] = {c4.x, c4.y};
    const uint32_t k1024 = __shfl_sync(0xffffffffu, vc[0], 0) & 0xffffu;
    uint32_t kl = hadd(c4.z, __byte_perm(c4.z, 0, 0x1032));
    kl = hadd(kl, __shfl_xor_sync(0xffffffffu, kl, 1)); kl = hadd(kl, __shfl_xor_sync(0xffffffffu, kl, 2));
#pragma unroll
    for (int i = 0; i < 3; i++) sts128(TB + T_R2 + 16 * lane + 512 * i, 0, 0, 0, 0);
    if (lane == 2) vb[0] &= 0xffff0000u;
    if (lane == 0) vc[0] &= 0xffff0000u;
    if (lane == 4) vc[0] = hsub(vc[0], k1024);
    __syncwarp();
    if (t >= 2) {
        const uint32_t g1 = TB + T_R2 + T2_S * (g & 3) + 8 * (8 * t - 10 + (g >> 2));
        const uint32_t g0 = TB + T_R2 + T2_S * ((g - 1) & 3) + 8 * (8 * t - 10 + ((g - 1) >> 2)) + 4;
#pragma unroll
        for (int i = 0; i < 4; i++) {
            sts16(g0 + 16 * i, vb[i]); sts16(g0 + 16 * i + 10, vb[i]);
            sts16(g1 + 16 * i, vb[i] >> 16); sts16(g1 + 16 * i + 10, vb[i] >> 16);
        }
    }
    const uint32_t g3 = TB + T_R3 + T3_S * (((g - 1) >> 1) & 1) + 8 * (7 + 4 * t + ((g - 1) >> 2)) + 4 * ((g - 1) & 1);
#pragma unroll
    for (int i = 0; i < 2; i++) {
        sts16(g3 + 16 * i, vc[i]); sts16(g3 + 16 * i + 10, vc[i]);
        sts16(g3 + 16 * i + 128, vc[i] >> 16); sts16(g3 + 16 * i + 138, vc[i] >> 16);
    }
    const uint32_t g4 = (uint32_t)(((uint64_t)(T_R3 + T3_S + 308) << 48 | (uint64_t)(T_R2 + 180) << 32 | (T_R2 + 176) << 16 | (T_R2 + 3 * T2_S + 172)) >> (8 * (lane & 6))) & 0xffffu;
    sts16(TB + g4 + 10 * (lane & 1), (lane & 7) < 6 ? k1024 : kl);
    return (int)c4.w;
}

struct Chunks { uint32_t c3, c2, c1, c0, cm1, cm2, cm3, cm4, d2, d1, d0, dm1, em2, em3; };
__device__ __forceinline__ void convolve(uint32_t sb, int h, uint32_t zr, int pr, int wuni, bf16* out, const CUtensorMap* tm_o DBG_PARAMS) {
    const uint32_t bars = sb + M_BARS;
    uint32_t M[8][2], Ye[8][2], Yo[8][2], F[8][2], Bq[2][4];
    {
        LANE_VARS;
        uint32_t X[8][2];
        uint32_t ua = UB + ((mi & 1) ? 0 : U_PL) + (8 + 8 * (mi >> 1) + r) * 16, ta = TB + 4 * (1 + g + 2 * t);
        uint32_t A[3][4], S[2][4];
        __syncwarp();
#pragma unroll
        for (int h2 = 0; h2 < 3; h2++) { A[h2][0] = lds32(ta + 1024 * h2); A[h2][1] = lds32(ta + 1024 * h2 + 32); A[h2][3] = lds32(ta + 1024 * h2 + 64); A[h2][2] = A[h2][1] ^ zr; }
#pragma unroll
        for (int h2 = 0; h2 < 2; h2++) {
            Bq[h2][1] = lds32(ta + 1024 * h2 + 96); Bq[h2][3] = lds32(ta + 1024 * h2 + 128); Bq[h2][0] = A[h2][3] ^ zr; Bq[h2][2] = Bq[h2][1] ^ zr;
#pragma unroll
            for (int i = 0; i < 4; i++) S[h2][i] = hadd(A[h2][i], Bq[h2][i]);
        }
        const uint32_t an = A[0][0] ^ zr, un = UB + (9 + lane) * 16;
        if (lead) TSTAMP(10);
        mbar_spin(bars + 8 * B_U);
        if (lead) { TSTAMP(3); CSTAMP(27); }
        uint32_t E[8][2], N[8], G[8][2];
#pragma unroll
        for (int jp = 0; jp < 4; jp++) ldsm4(ua + jp * 256, E[2 * jp][0], E[2 * jp][1], E[2 * jp + 1][0], E[2 * jp + 1][1]);
#pragma unroll
        for (int jp = 0; jp < 4; jp++) ldsm4(ua + 2 * U_PL + jp * 256, X[2 * jp][0], X[2 * jp][1], X[2 * jp + 1][0], X[2 * jp + 1][1]);
        ldsm4(un, N[0], N[1], N[2], N[3]); ldsm4(un + 512, N[4], N[5], N[6], N[7]);
#pragma unroll
        for (int J = 0; J < 8; J++) mma_h_z(M[J][0], M[J][1], S[0], E[J][0], E[J][1]);
#pragma unroll
        for (int J = 1; J < 8; J++) mma_h(M[J], S[1], E[J - 1][0], E[J - 1][1]);
#pragma unroll
        for (int J = 2; J < 8; J++) mma_h(M[J], A[2], E[J - 2][0], E[J - 2][1]);
        if (FENCES & 32) FENCE();
#pragma unroll
        for (int J = 0; J < 8; J++) mma_h_k8_z(Ye[J], zr, an, X[J][1]);
#pragma unroll
        for (int J = 0; J < 8; J++) mma_h_k8_z(Yo[J], zr, an, N[J]);
#pragma unroll
        for (int J = 0; J < 8; J++) { G[J][0] = hsub(X[J][0], E[J][0]); G[J][1] = hsub(X[J][1], E[J][1]); }
#pragma unroll
        for (int jp = 0; jp < 4; jp++) ldsm4(ua + 2 * U_PL + jp * 256 - 16, X[2 * jp][0], X[2 * jp][1], X[2 * jp + 1][0], X[2 * jp + 1][1]);
#pragma unroll
        for (int J = 0; J < 8; J++) mma_h(Yo[J], A[0], G[J][0], G[J][1]);
#pragma unroll
        for (int J = 1; J < 8; J++) mma_h(Yo[J], A[1], G[J - 1][0], G[J - 1][1]);
#pragma unroll
        for (int J = 2; J < 8; J++) mma_h(Yo[J], A[2], G[J - 2][0], G[J - 2][1]);
#pragma unroll
        for (int J = 0; J < 8; J++) { F[J][0] = hsub(X[J][0], E[J][0]); F[J][1] = hsub(X[J][1], E[J][1]); }
#pragma unroll kDenseUnroll
        for (int k = 1; k < 8; k++) {
            ua -= 16; ta += 128;
            dense_step(M, Ye, Yo, X, F, Bq, ua, ta, zr);
        }
    }
    mbar_wait_n<2, 8>(bars + 8 * B_TD);
    LANE_VARS;
    if (lead) { TSTAMP(4); CSTAMP(28); }
    __syncwarp();
    const uint32_t idh = (g == 2 * t) ? 0x3C00u : (g == 2 * t + 1) ? 0x3C000000u : 0u;
    const uint32_t sbr = mapa(sb, h ^ 1);
    const uint32_t yl = TB + lane * 16, yr = sbr + (h ? ALT0 : ALT1) + A_YIN + warp * Y_CH + lane * 16;
    const uint32_t ys = lds32(sb + M_SC + (8 * h + warp) * 4);
    uint32_t ea[4];
    auto finish = [&](int J) {
        float m[4], e[4], o[4];
        widen_h(m, M[J], idh); widen_add_h(e, Ye[J], idh, m); widen_add_h(o, Yo[J], idh, m);
        const uint32_t y[4] = {hmul2_bf(pack_bf(e[0], e[2]), ys), hmul2_bf(pack_bf(o[0], o[2]), ys), hmul2_bf(pack_bf(e[1], e[3]), ys), hmul2_bf(pack_bf(o[1], o[3]), ys)};
        if (!(J & 1)) {
#pragma unroll
            for (int i = 0; i < 4; i++) ea[i] = y[i];
        } else {
            st_async16(yr + (J >> 1) * 512, h ? ea[0] : y[0], h ? ea[1] : y[1], h ? ea[2] : y[2], h ? ea[3] : y[3], sbr + M_BARS + 8 * (B_Y + (J >> 1)));
            sts128(yl + (J >> 1) * 512, h ? y[0] : ea[0], h ? y[1] : ea[1], h ? y[2] : ea[2], h ? y[3] : ea[3]);
            __syncwarp();
            if (lane == 0) mbar_arrive(bars + 8 * (B_Y + (J >> 1)));
        }
    };
    const uint32_t a1 = UB + (3 - mi) * U_PL + (8 + r) * 16;
    const uint32_t a2 = UB + ((2 - mi) & 3) * U_PL + (8 + r - (mi == 3)) * 16;
    const uint32_t a3 = UB + (2 - (mi & 1)) * U_PL + (7 + r) * 16;
    const uint32_t bt = sb + OFF_BAND + 4 * (32 + g + 2 * t);
    auto load3 = [&](Chunks& u, int j) { ldsm4(a2 + j * 128, u.d2, u.d1, u.d0, u.dm1); ldsm4(a1 + j * 128, u.c3, u.c2, u.c1, u.c0); ldsm2(a3 + j * 128, u.em2, u.em3); };
    auto load2 = [&](Chunks& u, int j) {
        if (DUP_MOV == 0) load3(u, j);
        else { ldsm4(a1 + j * 128, u.c3, u.c2, u.c1, u.c0); if (DUP_MOV == 1) ldsm4(a2 + j * 128, u.d2, u.d1, u.d0, u.dm1); }
        ldsm4(a1 + j * 128 - 16, u.cm1, u.cm2, u.cm3, u.cm4);
        if (DUP_MOV >= 1) { u.em2 = u.cm2 ^ zr; u.em3 = u.cm3 ^ zr; }
        if (DUP_MOV >= 2) { u.d2 = u.c2 ^ zr; u.d1 = u.c1 ^ zr; u.d0 = u.c0 ^ zr; u.dm1 = u.cm1 ^ zr; }
    };
    Chunks u;
    uint32_t B35[4];
    uint2 Q[4][3], QS[2][3];
    {
        const uint32_t f7 = lds32(bt + 768 - 36), g7 = lds32(bt + 768 - 4), f9 = lds32(bt + 1024 - 32), g9 = lds32(bt + 1024), h9 = lds32(bt + 1024 + 32);
        const uint32_t f1 = hmul(lds32(bt - 28), lds16(TB + T_R2 + 176) * 0x10001u);
        load3(u, 0);
        const uint32_t tq = TB + T_R3 + 8 * (7 + g - 2 * t);
        uint2 Q0[4], Q1[4], Q2[4];
#pragma unroll
        for (int i = 0; i < 4; i++) { Q0[i] = lds64(tq + 64 * i); Q1[i] = lds64(tq + T3_S + 64 * i); Q2[i] = lds64(tq + T3_S - 8 + 64 * i); }
#pragma unroll
        for (int J = 0; J < 8; J++) mma_h(Ye[J], Bq[0], F[J][0], F[J][1]);
#pragma unroll
        for (int J = 1; J < 8; J++) mma_h(Ye[J], Bq[1], F[J - 1][0], F[J - 1][1]);
        const uint32_t B7[4] = {zr, f7, f7 ^ zr, g7}, B9a[4] = {zr + zr, f9, f9 ^ zr, g9}, B9b[4] = {g9 ^ zr, h9, h9 ^ zr, zr * 3}, B1[4] = {zr * 5, f1, f1 ^ zr, zr * 7};
        const uint32_t g7b = g7 ^ zr, z7 = zr * 9;
        if (FENCES & 1) FENCE();
        uint32_t WE[2][4], WO[2][4];
#pragma unroll
        for (int j = 0; j < 5; j++) {
            uint32_t (&we)[4] = WE[j & 1], (&wo)[4] = WO[j & 1], (&pe)[4] = WE[~j & 1], (&po)[4] = WO[~j & 1];
            if (j == 3) {
                const uint32_t t2 = TB + T_R2 + 8 * (6 + g - 2 * t);
                B35[0] = lds32(bt + 256 - 28); B35[1] = lds32(bt + 512 - 40); B35[2] = lds32(bt + 256 + 4); B35[3] = lds32(bt + 512 - 8);
#pragma unroll
                for (int i = 0; i < 3; i++)
#pragma unroll
                    for (int s = 0; s < 4; s++) Q[s][i] = lds64(t2 + T2_S * s + 64 * i);
            }
            if (j < 4) {
                mma_h_z(we[2], we[3], B9a, u.d0, u.dm1); mma_h_z(wo[2], wo[3], B9a, u.d2, u.d1);
                mma_h_z(we[0], we[1], B7, u.c1, u.c0); mma_h_z(wo[0], wo[1], B7, u.c3, u.c2);
            }
            if (j == 0) { finish(0); finish(1); }
#pragma unroll
            for (int i = 0; i < 5 - j && j > 0; i++) { mma_h(Ye[j + 3 + i], pe, Q0[i].x, Q0[i].y); mma_h(Yo[j + 3 + i], pe, Q1[i].x, Q1[i].y); }
            if (j < 4) {
                mma_h2(we[2], we[3], B9b, u.em2, u.em3); mma_h2(wo[2], wo[3], B9b, u.d0, u.dm1);
                mma_h_k8(we[0], we[1], g7b, z7, u.dm1); mma_h_k8(wo[0], wo[1], g7b, z7, u.c1);
                mma_h(Ye[j + 4], B1, u.d0, u.dm1); mma_h(Yo[j + 4], B1, u.d2, u.d1);
                if (j < 3) load3(u, j + 1); else load2(u, 0);
            }
#pragma unroll
            for (int i = 0; i < 5 - j && j > 0; i++) { mma_h(Ye[j + 3 + i], po, Q2[i].x, Q2[i].y); mma_h(Yo[j + 3 + i], po, Q0[i].x, Q0[i].y); }
            if (j == 3) {
#pragma unroll
                for (int i = 0; i < 3; i++)
#pragma unroll
                    for (int s = 0; s < 2; s++) { QS[s][i].x = hadd(Q[s][i].x, Q[s + 2][i].x); QS[s][i].y = hadd(Q[s][i].y, Q[s + 2][i].y); }
            }
            if (j < 3 ? ((FENCES & 2) || (j == 2 && (FENCES & 4))) : (j == 4 && (FENCES & 8))) FENCE();
        }
    }
    uint32_t xo, go, ya, sel, any, wu, oo;
    auto mix_setup = [&]() {
        LANE_VARS;
        const int pos = 2 * (warp & 3) + (t >> 1);
        xo = sb + OFF_S + h * 32768 + (warp & 3) * 2048 + (warp >> 2) * 1024 + (g >> 1) * 128 + (t >> 1) * 64 + (g & 1) * 32 + (((t ^ (g >> 1)) & 1) << 4);
        go = sb + OFF_GP + (8 * pos + g) * 64 + ((warp >> 2) ^ (g >> 1) ^ (2 * (t & 2))) * 8;
        const int ch = 2 * mi + (r & 1);
        ya = sb + ((((r >> 1) & 1) == h) ? OFF_TAB + ch * T_CH : (h ? ALT1 : ALT0) + A_YIN + ch * Y_CH) + (8 * (warp & 3) + (r & 4) + 2 * (warp >> 2)) * 16;
        sel = lds16(sb + M_BMAP + (8 * warp + g) * 2);
        any = __reduce_or_sync(0xffffffffu, sel);
        sel >>= t >> 1;
        oo = (128 * (warp >> 2) + 8 * g + pos) * D_ + 8 * (t & 1);
        wu = UNI_WARP ? wuni : __shfl_sync(0xffffffffu, warp, 0);
    };
    struct MixIn { uint32_t gp[2]; uint4 e[2]; };
    auto mix_load = [&](MixIn& q, int J) {
        const uint2 g2 = lds64(go ^ (16 * J));
        q.gp[0] = g2.x; q.gp[1] = g2.y;
#pragma unroll
        for (int k = 0; k < 2; k++) {
            const uint4 x = lds128(xo + J * 8192 + k * 512);
            q.e[k] = make_uint4(hi_mul_bf(q.gp[k], x.x), hi_mul_bf(q.gp[k], x.y), hi_mul_bf(q.gp[k], x.z), hi_mul_bf(q.gp[k], x.w));
        }
    };
    auto mix_calc = [&](MixIn& q, int J) {
#pragma unroll
        for (int k = 0; k < 2; k++) {
            uint32_t y[4];
            ldsm4t(ya + J * 512 + k * 16, y[0], y[1], y[2], y[3]);
            q.e[k] = make_uint4(lo_fma_bf(q.gp[k], y[0], q.e[k].x), lo_fma_bf(q.gp[k], y[1], q.e[k].y), lo_fma_bf(q.gp[k], y[2], q.e[k].z), lo_fma_bf(q.gp[k], y[3], q.e[k].w));
            if (J < 2) sts128_if(!((sel >> (4 * J + 2 * k)) & 1u), xo + J * 8192 + k * 512, q.e[k].x, q.e[k].y, q.e[k].z, q.e[k].w);
        }
    };
    auto mix_send = [&](const MixIn& q, int J) {
        if (J >= STG_FROM || (J >= 2 && ((any >> (4 * J)) & 15u))) {
#pragma unroll
            for (int k = 0; k < 2; k++) if (!((sel >> (4 * J + 2 * k)) & 1u)) *(uint4*)(out + (size_t)(512 * J + 256 * h + 64 * k) * D_ + 16 * pr + oo) = q.e[k];
        } else {
#pragma unroll
            for (int k = 0; k < 2 && J >= 2; k++) sts128(xo + J * 8192 + k * 512, q.e[k].x, q.e[k].y, q.e[k].z, q.e[k].w);
            asm volatile("fence.proxy.async.shared::cta;" ::: "memory");
            __syncwarp();
            asm volatile("{ .reg .pred p; elect.sync _|p, 0xffffffff;\n\t@p cp.async.bulk.tensor.5d.global.shared::cta.bulk_group [%0, {%2, %3, %3, %4, %5}], [%1]; }"
                         :: "l"(tm_o), "r"(sb + OFF_S + h * 32768 + J * 8192 + (wu & 3) * 2048 + (wu >> 2) * 1024),
                            "r"(16 * pr), "r"(0), "r"(32 * J + 16 * h + 8 * (wu >> 2)), "r"(wu & 3) : "memory");
        }
    };
    MixIn q, q2, q3;
    const uint32_t zq = zr + zr;
#pragma unroll
    for (int j = 0; j < 6; j++) {
        if (j == SEND0_AT) mix_send(q, 0);
        if (j == SEND1_AT) mix_send(q, 1);
        if (j == MIX0_AT) mbar_wait_n<2, 8 * (B_Y - B_G)>(bars + 8 * B_G);
        else if (j == MIX1_AT) mbar_spin(bars + 8 * (B_Y + 1));
        else if (j > 0 && (FENCES & 16)) FENCE();
        uint32_t H[7][2];
        mma_h_z(H[3][0], H[3][1], B35, u.d0, u.dm1); mma_h_z(H[4][0], H[4][1], B35, u.c1, u.c0);
        mma_h_z(H[5][0], H[5][1], B35, u.d2, u.d1); mma_h_z(H[6][0], H[6][1], B35, u.c3, u.c2);
        mma_h_z(H[2][0], H[2][1], B35, u.cm1, u.cm2); mma_h_z(H[1][0], H[1][1], B35, u.em2, u.em3); mma_h_z(H[0][0], H[0][1], B35, u.cm3, u.cm4);
        if (j < 5) load2(u, j + 1);
        if (j > 0) finish(j + 1);
        if (j == MIX0_AT) { mix_setup(); mix_load(q, 0); mix_calc(q, 0); }
        if (j == MIX1_AT) { mix_load(q, 1); mix_calc(q, 1); }
        if (j == 5) { mix_load(q2, 2); mix_load(q3, 3); }
        const int n = j < 4 ? 3 : 6 - j;
#pragma unroll
        for (int s = 0; s < 2; s++) {
            const int o = 3 - s;
            const uint32_t qe[4] = {H[o][0] ^ zr, H[o + 1][0] ^ zq, H[o][1] ^ zr, H[o + 1][1] ^ zq};
            const uint32_t qg[4] = {hsub(H[o + 2][0], H[o][0]), hsub2(H[o + 3][0], H[o + 1][0]), hsub(H[o + 2][1], H[o][1]), hsub2(H[o + 3][1], H[o + 1][1])};
            const uint32_t qf[4] = {hsub(H[o - 2][0], H[o][0]), hsub2(H[o - 1][0], H[o + 1][0]), hsub(H[o - 2][1], H[o][1]), hsub2(H[o - 1][1], H[o + 1][1])};
#pragma unroll
            for (int i = 0; i < n; i++) mma_h(M[j + 2 + i], qe, QS[s][i].x, QS[s][i].y);
#pragma unroll
            for (int i = 0; i < n; i++) mma_h(Yo[j + 2 + i], qg, Q[s][i].x, Q[s][i].y);
#pragma unroll
            for (int i = 0; i < n; i++) mma_h(Ye[j + 2 + i], qf, Q[s + 2][i].x, Q[s + 2][i].y);
        }
    }
    finish(7);
    if (lead) { TSTAMP(5); CSTAMP(29); }
    if (SEND0_AT == 6) mix_send(q, 0);
    if (SEND1_AT == 6) mix_send(q, 1);
    mbar_spin(bars + 8 * (B_Y + 2));
    asm volatile("cp.async.bulk.commit_group;" ::: "memory");
    mix_calc(q2, 2);
    mix_send(q2, 2);
    asm volatile("cp.async.bulk.wait_group 0;" ::: "memory");
    __syncwarp();
    if (lane == 0) mbar_arrive(bars + 8 * B_SD);
    mbar_spin(bars + 8 * (B_Y + 3));
    if (lead) TSTAMP(6);
    mix_calc(q3, 3);
    mix_send(q3, 3);
    asm volatile("cp.async.bulk.commit_group;" ::: "memory");
    asm volatile("cp.async.bulk.wait_group.read 0;" ::: "memory");
}

__global__ void __cluster_dims__(2, 1, 1) __launch_bounds__(NTHREADS, 1)
fused_kernel(const Params p, const __grid_constant__ CUtensorMap tm_gu, const __grid_constant__ CUtensorMap tm_down, const __grid_constant__ CUtensorMap tm_x,
             const __grid_constant__ CUtensorMap tm_r, const __grid_constant__ CUtensorMap tm_o) {
    extern __shared__ __align__(1024) unsigned char smem[];
    const uint32_t sb = __shfl_sync(0xffffffffu, smem_u32(smem), 0);
    int tid;
    asm volatile("mov.u32 %0, %%tid.x;" : "=r"(tid));
    const int pw = tid >> 5, lane = tid & 31;
    const int kc = ((blockIdx.x >> 1) + 60) & 63, lo = kc < 32, hi = kc >= 60, kq = lo ? kc >> 3 : ((kc - 32) * 37) >> 8;
    const int h = blockIdx.x & 1;
    const int pr = (hi ? 1 : 4) * kc - (lo ? 31 : hi ? 0 : 27) * kq - ((lo | hi) ? 0 : 96);
    const int c = 2 * pr + h;
    const int fb = FB_BLK ? (int)blockIdx.x : c;
    const uint32_t bars = sb + M_BARS;

    uint2 v_la, v_ai, v_cr, v_ci;
    uint32_t ldt16, dsk16;
    {
        const uint32_t ch = 8 * c + pw - MAIN_W0, po = ch * 128 + 4 * lane;
        asm volatile("{ .reg .pred q; setp.ge.u32 q, %16, 8; @q bra.uni L%=;\n\t"
                     "ld.global.nc.v2.u32 {%0,%1}, [%10];\n\tld.global.nc.v2.u32 {%2,%3}, [%11];\n\tld.global.nc.u16 %8, [%14];\n\t"
                     "ld.global.nc.v2.u32 {%4,%5}, [%12];\n\tld.global.nc.v2.u32 {%6,%7}, [%13];\n\tld.global.nc.u16 %9, [%15];\nL%=:\n\t}"
                     : "=r"(v_la.x), "=r"(v_la.y), "=r"(v_ai.x), "=r"(v_ai.y), "=r"(v_cr.x), "=r"(v_cr.y), "=r"(v_ci.x), "=r"(v_ci.y), "=r"(ldt16), "=r"(dsk16)
                     : "l"(p.logA + po), "l"(p.Aim + po), "l"(p.Cre + po), "l"(p.Cim + po), "l"(p.logdt + ch), "l"(p.Dskip + ch), "r"(pw - MAIN_W0));
    }

    if (blockIdx.x >= 128) {
        if (blockIdx.x != 128) return;
        const unsigned tag = (ld_epoch(p.ex) + 1) & 0xffffu;
        const uint32_t idx0 = 2047 - (512 * (tid & 3) + (tid >> 3) + 256 * ((tid >> 2) & 1));
        const uint32_t list = sb + 128;
#pragma unroll 1
        for (int pass = 0; pass < 2; pass++) {
            if (tid == 0) sts32(sb + 64, 0);
            sts128(list + 16 * tid, 0, 0, 0, 0);
            uint4 a = make_uint4(lane == 0 ? 0x10000u : 0u, 0, 0, 0);
            bool ok = pass == 0;
#pragma unroll 1
            for (int it = 0; it < (1 << 22) && !ok; it++) {
                a = ld_gpu128(&p.ex->r[tid]);
                ok = (((a.x ^ tag) | (a.y ^ tag) | (a.z ^ tag) | (a.w ^ tag)) & 0xffffu) == 0;
            }
            if (!ok) __trap();
            const uint32_t key[4] = {(a.x & 0xffff0000u) | idx0, (a.y & 0xffff0000u) | (idx0 - 64), (a.z & 0xffff0000u) | (idx0 - 128), (a.w & 0xffff0000u) | (idx0 - 192)};
            const uint32_t wm = __reduce_max_sync(0xffffffffu, max(max(key[0], key[1]), max(key[2], key[3])));
            if (lane == 0) sts32(sb + pw * 4, wm);
            __syncthreads();
            const uint2 q = lds64(sb + 8 * (lane & 7));
            const uint32_t thr = __reduce_min_sync(0xffffffffu, max(q.x, q.y));
            if (tid == 0) TSTAMP(0);
            const uint32_t n = (key[0] >= thr) + (key[1] >= thr) + (key[2] >= thr) + (key[3] >= thr);
            if (n) {
                uint32_t pos;
                asm volatile("atom.shared.add.u32 %0, [%1], %2;" : "=r"(pos) : "r"(sb + 64), "r"(n) : "memory");
#pragma unroll
                for (int i = 0; i < 4; i++) if (key[i] >= thr) { sts32(list + 4 * pos, key[i]); pos++; }
            }
            __syncthreads();
            const int ncand = (int)lds32(sb + 64);
            const uint2 l0 = lds64(list + 8 * lane);
#pragma unroll 1
            for (int j = pw; j < ncand; j += 16) {
                const uint32_t mine = lds32(list + 4 * j);
                int rank = __popc(__ballot_sync(0xffffffffu, l0.x > mine)) + __popc(__ballot_sync(0xffffffffu, l0.y > mine));
#pragma unroll 1
                for (int i = 64; i < ncand; i += 32) rank += __popc(__ballot_sync(0xffffffffu, lds32(list + 4 * (i + lane)) > mine));
                if (rank < 8 && lane == 0) asm volatile("st.relaxed.gpu.global.v2.u32 [%0], {%1, %2};" :: "l"(&p.ex->top[rank]), "r"(mine), "r"(pass ? tag : tag ^ 0x8000u) : "memory");
            }
            if (tid == 0) TSTAMP(1);
            __syncthreads();
        }
        if (tid == 0) TSDUMP(3u);
        return;
    }

    if (pw != 12) asm volatile("barrier.cluster.arrive.relaxed.aligned;" ::: "memory");

    if (pw >= MAIN_W0 && pw < MAIN_W0 + 8) {
        [[maybe_unused]] const int wuni = __shfl_sync(0xffffffffu, pw - MAIN_W0, 0);
        const int warp = UNI_WARP ? wuni : pw - MAIN_W0;
        [[maybe_unused]] const bool lead = (tid == 32 * MAIN_W0);
        asm volatile("setmaxnreg.inc.sync.aligned.u32 " MAIN_REGS ";");
        cluster_next();
        [[maybe_unused]] const int d = 8 * c + warp;
        const int g = lane >> 2, t = lane & 3, mi = lane >> 3, r = lane & 7;
        const uint32_t TB = sb + OFF_TAB + warp * T_CH;
        const uint32_t UB = sb + OFF_U + warp * U_CH;
        const uint32_t zr = ZR;

        uint32_t Ra[2][2], Rb[2][2], Rc[2], Rl[2];
        int esum;
        {
            const float dt = bf_round(exp_acc(__uint_as_float(ldt16 << 16)));
            const uint32_t ec = max(warp_max16(amax2_bf(amax2_bf(v_cr.x, v_cr.y), amax2_bf(v_ci.x, v_ci.y))) >> 7, 6u);
            const float cf = __uint_as_float((__float_as_uint(dt) & 0x7fffffu) | ((260u - ec) << 23));
            esum = (int)ec + (int)(__float_as_uint(dt) >> 23) - 274;
            kernel_gen(v_la, v_ai, v_cr, v_ci, dt, cf, TB, UB, bars + 8 * B_KD, lane, zr, Ra, Rb, Rc, Rl);
        }
        if (lead) TSTAMP(2);

        {
            uint32_t mk = amax2_h(amax2_h(amax2_h(Ra[0][0], Ra[0][1]), amax2_h(Ra[1][0], Ra[1][1])), amax2_h(amax2_h(Rb[0][0], Rb[0][1]), amax2_h(Rb[1][0], Rb[1][1])));
            mk = amax2_h(amax2_h(mk, hmul(Rl[0], 0x34003400u)), amax2_h(Rc[0], Rc[1]));
            const int eb = (dsk16 >> 7) & 0xff, ek = max((int)(warp_max16(mk) >> 10), eb ? eb - 127 - esum : 0), en = eb - esum - 3 - ek;
            const float ds = (lane == 0 && eb && en > 0) ? __uint_as_float(((dsk16 & 0x807fu) << 16) | (en << 23)) : 0.f;
            const float fs = __uint_as_float(max(139 - ek, 1) << 23);
            const uint32_t ks = pack_h(fs, fs);
            uint32_t va[4], vb[4];
#pragma unroll
            for (int i = 0; i < 4; i++) { va[i] = hmul(Ra[i >> 1][i & 1], ks); vb[i] = hmul(Rb[i >> 1][i & 1], ks); }
            va[0] = hadd(va[0], pack_h(ds, 0.f));
            const uint32_t k512 = __shfl_sync(0xffffffffu, vb[0], 2) & 0xffffu, k255 = __shfl_sync(0xffffffffu, va[3], 31);
#pragma unroll
            for (int i = 0; i < 4; i++) {
                const uint32_t pv = __shfl_sync(0xffffffffu, lane == 31 ? (i ? va[i - 1] : 0u) : va[i], lane - 1);
                sts64(TB + 48 + 256 * i + 8 * lane, __byte_perm(pv, va[i], 0x5432), va[i]);
            }
#pragma unroll
            for (int i = 0; i < 4; i++) {
                const uint32_t nx = __shfl_sync(0xffffffffu, lane == 0 ? (i < 3 ? vb[i + (i < 3)] : k512) : vb[i], lane + 1 + 2 * (lane & 1));
                const uint32_t aa = __byte_perm(vb[i], 0, 0x1010);
                sts128_if(t < 2, TB + 1072 + 256 * i + 32 * g + 16 * t, (i == 0 && lane == 0) ? __byte_perm(k255, aa, 0x5432) : aa ^ zr, aa, vb[i] ^ zr, __byte_perm(vb[i], nx, 0x5432));
            }
            const uint32_t k0 = lane == 3 ? k512 : 0u, kk = k0 * 0x10001u;
            sts128_if(lane < 8, TB + 16 * lane + (lane < 3 ? 0 : 2048), kk, kk ^ zr, kk + zr, k0);
            sts128(TB + T_R2 + 16 * lane, vb[0], vb[1], vb[2], vb[3]);
            esum += (int)ek;
            sts128(TB + T_R2 + 512 + 16 * lane, hmul(Rc[0], ks), hmul(Rc[1], ks), hmul(Rl[0], ks), (uint32_t)esum);
            __syncwarp();
            if (lane == 0) mbar_arrive(bars + 8 * B_TS);
        }
        if (lead) TSTAMP(11);

        convolve(sb, h, zr, pr, wuni, p.out, &tm_o DBG_ARGS);
        { LANE_VARS; if (lead) { TSTAMP(7); TSDUMP(0x3c000cffu); } }
    } else if (pw < 4) {
        const int v = UNI_V ? __shfl_sync(0xffffffffu, pw, 0) : pw, at = tid;
        const int g = lane >> 2, t = lane & 3, mi = lane >> 3, r = lane & 7;
        const uint32_t dalt = (h ? ALT1 : ALT0) + A_SLOT - ALT_SLOT * 8192;
        cp16(sb + OFF_GP + tid * 16, p.wr + tid * 8);
        cp16(sb + OFF_GP + 2048 + tid * 16, p.gatew + tid * 8);
        const unsigned epoch = ld_epoch(p.ex);
        if (tid == 0) sts128(sb + OFF_S - 16, 0, 0, 0, 0);
        const unsigned tag = (epoch + 1) & 0xffffu;
        const int ftok = 2 * ((at >> 2) & 3) + (at & 1), fch = (at >> 4) + 8 * ((at >> 1) & 1);
        uint32_t eu;
        {
            cluster_next();
            cp_wait_all();
            bar_sync(1, 128);
            const uint32_t wo = sb + OFF_GP + 512 * v + 64 * ((g >> 1) & 1) + 16 * t + 4 * (g & 1);
            uint32_t w0[4], w1[4];
#pragma unroll
            for (int cb = 0; cb < 4; cb++) { w0[cb] = lds32(wo + 128 * cb); w1[cb] = lds32(wo + 128 * cb + 8); }
            const uint32_t go = sb + OFF_GP + 2048 + 512 * v + 64 * (g & 1) + 16 * t;
            const uint32_t ro = sb + M_RG + (g >> 1) * 32 + (2 * v + (g & 1)) * 4;
            const uint32_t xo = sb + OFF_XROW + (g >> 1) * 2048 + 512 * v + 64 * (g & 1) + 16 * t;
            const uint32_t one0 = 0x3F803F80u ^ p.zero, one1 = 0x3F803F80u + p.zero;
            auto row_sum = [&](uint32_t a) {
                const uint4 x = lds128(a), y = lds128(a + 16);
                return ((__uint_as_float(x.x) + __uint_as_float(x.y)) + (__uint_as_float(x.z) + __uint_as_float(x.w)))
                     + ((__uint_as_float(y.x) + __uint_as_float(y.y)) + (__uint_as_float(y.z) + __uint_as_float(y.w)));
            };
            const int dl = 8 * (r >> 1) + 4 - 2 * mi - (r & 1);
            const uint32_t so = sb + OFF_S + (v >> 1) * 32768 + (dl & 6) * 1024 + (8 * (v & 1) + (dl >> 4)) * 128 + (dl & 1) * 64 + (dl & 8) * 4 + ((dl & 16) ^ (h << 4));
            const uint32_t so2 = so + (dl >= 0 ? 0 : v == 2 ? -30720 : v == 0 ? 26624 : 0), so1 = (dl < 0 && v == 0) ? sb + OFF_S - 16 : so2;
            auto src = [&](int k) { return (k == 0 ? so1 : (k & 3) == 0 ? so2 : so) + (k >> 2) * 8192 + (k & 3) * 256; };
            uint32_t xr[16][4], mx = 0, idb = 0;
            auto slice = [&](int k) { ldsm4t(src(k), xr[k][0], xr[k][1], xr[k][2], xr[k][3]); };
            auto to_half = [&](uint32_t (&q)[4]) {
                float f0[4], f1[4];
                widen_bf(f0, q[0], q[1], idb); widen_bf(f1, q[2], q[3], idb);
                q[0] = pack_h(f0[0], f0[1]); q[1] = pack_h(f0[2], f0[3]); q[2] = pack_h(f1[0], f1[1]); q[3] = pack_h(f1[2], f1[3]);
            };
            auto track = [&](int k) { mx = amax2_bf(amax2_bf(mx, amax2_bf(xr[k][0], xr[k][1])), amax2_bf(xr[k][2], xr[k][3])); };
            auto cta_exp = [&]() {
                const uint32_t wm = warp_max16(mx);
                if (lane == 0) sts32(sb + M_MX + v * 4, wm);
                bar_sync(1, 128);
                const uint4 m4 = lds128(sb + M_MX);
                return max(max(m4.x, m4.y), max(m4.z, m4.w)) >> 7;
            };
            auto set_scale = [&]() { const uint32_t sc = (257u - eu) << 7; idb = (g == 2 * t) ? sc : (g == 2 * t + 1) ? sc << 16 : 0u; };
            uint4 x[4], gw[4];
#pragma unroll
            for (int cb = 0; cb < 4; cb++) gw[cb] = lds128(go + 128 * cb);
            auto gate = [&](int i) {
                float e0[4] = {0.f, 0.f, 0.f, 0.f}, e1[4] = {0.f, 0.f, 0.f, 0.f};
#pragma unroll
                for (int cb = 0; cb < 4; cb++)
                    mma_bf((cb & 1) ? e1 : e0, hmul2_bf(x[cb].x, gw[cb].x), hmul2_bf(x[cb].y, gw[cb].y), hmul2_bf(x[cb].z, gw[cb].z), hmul2_bf(x[cb].w, gw[cb].w), one0, one1);
                if (t == 0) stsf(ro + 512 + 128 * i, (e0[0] + e0[3]) + (e1[0] + e1[3]));
            };
#pragma unroll
            for (int i = 0; i < 4; i++) {
                if (i == 0) mbar_spin(bars + 8 * B_X); else mbar_wait_n<2, 8 * (B_X - B_S + 1)>(bars + 8 * (B_S + i - 1));
#pragma unroll
                for (int cb = 0; cb < 4; cb++) x[cb] = lds128(xo + 8192 * i + 128 * cb);
#pragma unroll
                for (int k = max(4 * i - 4, 0); k < 4 * i; k++) slice(k);
                float d0[4] = {0.f, 0.f, 0.f, 0.f}, d1[4] = {0.f, 0.f, 0.f, 0.f};
#pragma unroll
                for (int cb = 0; cb < 4; cb++) mma_bf((cb & 1) ? d1 : d0, x[cb].x, x[cb].y, x[cb].z, x[cb].w, w0[cb], w1[cb]);
                if (t == (g & 1)) stsf(ro + 128 * i, (d0[0] + d0[3]) + (d1[0] + d1[3]));
                if (i == 3) break;
                gate(i);
#pragma unroll
                for (int k = max(4 * i - 4, 0); k < 4 * i; k++) track(k);
                if (i == 1) {
                    eu = min(cta_exp() + 3u, 255u);
                    set_scale();
                }
#pragma unroll
                for (int k = max(4 * i - 4, 0); k < 4 * i; k++) to_half(xr[k]);
            }
            bar_sync(4, 256);
            if (at < 16) {
                const uint32_t rb = pack_bf(0.f, row_sum(sb + M_RG + at * 32));
                st_gpu32((uint32_t*)p.ex->r + 16 * c + at, ((rb ^ (((int)rb >> 31) | 0x80000000u)) & 0xffff0000u) | tag);
            }
            if (at == 32) mbar_arrive(bars + 8 * B_XF);
            if (at == 0) TSTAMP(8);
#pragma unroll
            for (int k = 8; k < 12; k++) { track(k); to_half(xr[k]); }
            mbar_spin(bars + 8 * (B_S + 3));
            if (at == 0) TSTAMP(9);
#pragma unroll
            for (int k = 12; k < 16; k++) slice(k);
            uint32_t utail = 0;
            if (at < 64 && r >= 5) utail = lds16(sb + OFF_S + 57344 + 1952 + ((12 - r) & 6) * 1024 + (r & 1) * 64 + ((h ^ 1) << 4) + 2 * (at >> 3));
#pragma unroll
            for (int k = 12; k < 16; k++) { track(k); to_half(xr[k]); }
            mx = amax2_bf(mx, utail);
            uint32_t over;
            asm volatile("{ .reg .pred p, q; setp.ne.u32 p, %1, 0; bar.red.or.pred q, 1, 128, p; selp.u32 %0, 1, 0, q; }"
                         : "=r"(over) : "r"((uint32_t)(max(mx & 0x7f80u, (mx >> 16) & 0x7f80u) > (eu << 7))) : "memory");
            mbar_spin(bars + 8 * B_KD);
            const uint32_t uo = sb + OFF_U + g * U_CH + t * U_PL;
            auto put = [&](int k, const uint32_t (&q)[4]) { sts128(uo + (8 + 4 * v + 16 * (k >> 2) + (k & 3)) * 16, q[0], q[1], q[2], q[3]); };
            if (!over) {
#pragma unroll
                for (int k = 0; k < 16; k++) put(k, xr[k]);
            } else {
                eu = cta_exp();
                set_scale();
#pragma unroll 1
                for (int k = 0; k < 16; k++) {
                    uint32_t q[4];
                    ldsm4t(src(k), q[0], q[1], q[2], q[3]);
                    to_half(q);
                    put(k, q);
                }
            }
            sts128(uo + v * 32, 0, 0, 0, 0); sts128(uo + v * 32 + 16, 0, 0, 0, 0);
            if (at < 64) sts16(sb + OFF_U + (at >> 3) * U_CH + 72 * 16 + r * 2, pack_h(bf_lo(utail) * bf_lo((257u - eu) << 7), 0.f));
            __syncwarp();
            if (lane == 0) mbar_arrive(bars + 8 * B_U);
#pragma unroll
            for (int cb = 0; cb < 4; cb++) gw[cb] = lds128(go + 128 * cb);
            gate(3);
            bar_sync(1, 128);
            if (at < 16) {
                const float gv = bf_round(sigmoid_f(bf_round(row_sum(sb + M_RG + 512 + at * 32))));
                st_gpu32((uint32_t*)p.ex->g + 1024 * h + 16 * (8 * (pr & 7) + (pr >> 3)) + (at ^ (2 * (pr >> 4) + 8 * (pr & 1))), pack_bf(gv, 1.f - gv));
            }
            if (at == 0) TSTAMP(23);
        }
        const int ct = v & 1, kh = v >> 1;
        uint32_t wa[GU_PRE][4][4];
        uint32_t ta, tb;
        {
            const int krow0 = 8 * (mi >> 1) + r;
            const uint32_t off0 = krow0 * 64 + (((2 * ct + (mi & 1)) ^ ((krow0 >> 1) & 3)) << 4);
            ta = sb + OFF_RING + kh * 2048 + off0 + p.swap_gu; tb = ta + 4096 - 2 * p.swap_gu;
        }
        auto gu_load = [&](uint32_t (&a)[4][4], int s) {
            const uint32_t o = (s % NSLOT) * 8192 + (s % NSLOT >= ALT_SLOT ? dalt : 0);
            ldsm4t(ta + o, a[0][0], a[0][1], a[0][2], a[0][3]);
            ldsm4t(tb + o, a[1][0], a[1][1], a[1][2], a[1][3]);
            ldsm4t(ta + o + 1024, a[2][0], a[2][1], a[2][2], a[2][3]);
            ldsm4t(tb + o + 1024, a[3][0], a[3][1], a[3][2], a[3][3]);
        };
        auto gu_release = [&](const uint32_t (&a)[4][4], int s) {
            if (s < B_S - B_EMPTY && lane == 0) mbar_arrive(bars + 8 * (B_EMPTY + s) + (a[0][0] & a[1][0] & a[2][0] & a[3][0] & p.zero));
        };
        auto gu_park = [&](auto S0, auto N) {
            constexpr int s0 = decltype(S0)::value, n = decltype(N)::value;
            if (fb < NGU_CTA) {
                mbar_wait_n<n, 8>(bars + 8 * s0);
#pragma unroll
                for (int s = s0; s < s0 + n; s++) gu_load(wa[s], s);
#pragma unroll
                for (int s = s0; s < s0 + n; s++) gu_release(wa[s], s);
            }
        };
        gu_park(IC<0>(), IC<4>());
        asm volatile("barrier.cluster.wait.acquire.aligned;" ::: "memory");
        mbar_wait(bars + 8 * B_TS);
#pragma unroll 1
        for (int i = 0; i < 2; i++) {
            const int es = group_tables(sb + OFF_TAB + (v + 4 * i) * T_CH, lane) + (int)eu;
            if (lane < 2) { const uint32_t o = mapa(sb, lane); st_async4(o + M_SC + (8 * h + v + 4 * i) * 4, (uint32_t)min(max(es, 1), 254) * 0x800080u, o + M_BARS + 8 * B_SC); }
        }
        __syncwarp();
        if (lane == 0) mbar_arrive(bars + 8 * B_TD);
        gu_park(IC<4>(), IC<GU_PRE - 4>());
        if (fb < NGU_CTA) {
            float dgt[4] = {0.f, 0.f, 0.f, 0.f}, dup[4] = {0.f, 0.f, 0.f, 0.f}, dg2[4] = {0.f, 0.f, 0.f, 0.f}, du2[4] = {0.f, 0.f, 0.f, 0.f};
            const uint32_t xo = sb + OFF_XSEL + r * XS_ROW + 64 * kh + 16 * mi;
            auto gu_mma = [&](const uint32_t (&a)[4][4], const uint32_t (&b)[4]) {
                mma_bf(dgt, a[0][0], a[0][1], a[0][2], a[0][3], b[0], b[1]);
                mma_bf(dup, a[1][0], a[1][1], a[1][2], a[1][3], b[0], b[1]);
                mma_bf(dg2, a[2][0], a[2][1], a[2][2], a[2][3], b[2], b[3]);
                mma_bf(du2, a[3][0], a[3][1], a[3][2], a[3][3], b[2], b[3]);
            };
            auto gu_batch = [&](auto S0, auto N) {
                constexpr int s0 = decltype(S0)::value, n = decltype(N)::value;
                uint32_t b[n][4];
                mbar_wait_n<n, 8>(bars + 8 * s0);
#pragma unroll
                for (int i = 0; i < n; i++) { ldsm4(xo + 128 * (s0 + i), b[i][0], b[i][1], b[i][2], b[i][3]); gu_load(wa[i], s0 + i); }
#pragma unroll
                for (int i = 0; i < n; i++) gu_mma(wa[i], b[i]);
#pragma unroll
                for (int i = 0; i < n; i++) gu_release(wa[n - 1], s0 + i);
            };
            mbar_spin(bars + 8 * B_XS);
            if (at == 0) TSTAMP(12);
#pragma unroll
            for (int s = 0; s < GU_PRE; s++) { uint32_t b[4]; ldsm4(xo + 128 * s, b[0], b[1], b[2], b[3]); gu_mma(wa[s], b); }
            gu_batch(IC<6>(), IC<2>());
            mbar_spin(bars + 8 * (B_XS + 1));
            gu_batch(IC<8>(), IC<4>()); gu_batch(IC<12>(), IC<3>()); gu_batch(IC<15>(), IC<1>());
#pragma unroll
            for (int i = 0; i < 4; i++) { dgt[i] += dg2[i]; dup[i] += du2[i]; }
            if (at == 0) TSTAMP(13);
            const uint32_t red = sb + M_RG, hs = sb + OFF_XSEL;
            sts128(red + ((v ^ 2) * 32 + lane) * 16, __float_as_uint(kh ? dgt[0] : dgt[2]), __float_as_uint(kh ? dgt[1] : dgt[3]),
                   __float_as_uint(kh ? dup[0] : dup[2]), __float_as_uint(kh ? dup[1] : dup[3]));
            bar_sync(1, 128);
            const uint4 oth = lds128(red + at * 16);
#pragma unroll
            for (int i = 0; i < 2; i++) {
                const float gv = bf_round((kh ? dgt[2 + i] : dgt[i]) + __uint_as_float(i ? oth.y : oth.x));
                const float uv = bf_round((kh ? dup[2 + i] : dup[i]) + __uint_as_float(i ? oth.w : oth.z));
                const float sl = bf_round(gv * sigmoid_f(gv));
                uint32_t hv = pack_bf(sl * uv, 0.f) & 0xffffu;
                hv = (hv == 0x8000u) ? 0x8000u : (hv ^ 0x8000u);
                sts16(hs + (2 * t + i) * 64 + (g >> 1) * 16 + (2 * ct + kh) * 4 + (g & 1) * 2, hv);
            }
            bar_sync(1, 128);
            if (v == 0) st_gpu128(&p.ex->h[32 * fb + lane], lds128(hs + lane * 16));
        }
        else mbar_wait(bars + 8 * (B_XS + 1));
        if (at == 0) TSTAMP(14);
        {
            mbar_wait(bars + 8 * B_G);
            const int row = (int)lds32(sb + M_IDX + ftok * 4);
            const int w = row & 7, jj = (row >> 3) & 7;
            const uint32_t xa = sb + OFF_S + h * 32768 + (row >> 9) * 8192 + (w & 6) * 1024 + ((row >> 4) & 15) * 128 + (w & 1) * 64 + (jj & 1) * 32 + ((2 * fch) ^ (row & 16));
            const float xv = bf_lo(lds16(xa));
            const uint32_t gp = lds32(sb + OFF_GP + (8 * w + jj) * 64 + ((4 * (row >> 9) + ((row >> 6) & 3)) ^ ((jj & 6) + 8 * (w & 1))) * 4);
            const uint32_t ya = sb + (((fch >> 3) == h) ? OFF_TAB + (fch & 7) * T_CH : (h ? ALT1 : ALT0) + A_YIN + (fch & 7) * Y_CH) + (row >> 9) * 512 + (4 * w + ((row >> 6) & 3)) * 16 + jj * 2;
            const float rs = bf_round(sigmoid_f(ldsf(sb + M_RSEL + ftok * 4)));
            uint4 hq[14];
            {
                const uint4* hsrc = &p.ex->h[(56 * h + 2 * v) * 32 + lane];
                mbar_wait(bars + 8 * (B_FULL + NST_GU + H_WAIT));
                if (at == 0) TSTAMP(15);
#pragma unroll
                for (int i = 0; i < 14; i++) hq[i] = ld_gpu128(hsrc + (8 * (i >> 1) + (i & 1)) * 32);
                bool ok = false;
#pragma unroll 1
                for (int it = 0; it < (1 << 22); it++) {
                    uint32_t mn = 0xffffffffu;
#pragma unroll
                    for (int i = 0; i < 14; i++) mn = min(mn, hq[i].x);
                    ok = __all_sync(0xffffffffu, mn != 0);
                    if (ok) break;
                    if (PSLEEP > 0) __nanosleep(PSLEEP);
#pragma unroll
                    for (int i = 0; i < 14; i++) if (hq[i].x == 0) hq[i] = ld_gpu128(hsrc + (8 * (i >> 1) + (i & 1)) * 32);
                }
                if (!ok) __trap();
            }
            if (at == 0) TSTAMP(16);
            mbar_wait_n<DN_PRE, 8>(bars + 8 * (B_FULL + NST_GU));
            float dd[4][4];
#pragma unroll
            for (int j = 0; j < 4; j++) { dd[j][0] = dd[j][1] = dd[j][2] = dd[j][3] = 0.f; }
            const int krow0 = 64 * (v & 1) + 8 * (mi >> 1) + r;
            const uint32_t td = sb + OFF_RING + (v >> 1) * 4096 + krow0 * 32 + (((mi & 1) ^ ((krow0 >> 2) & 1)) << 4);
#pragma unroll
            for (int s = 0; s < 7; s++) {
                if (s >= DN_PRE) mbar_spin(bars + 8 * (B_FULL + NST_GU + s));
                const uint32_t tile = td + ((NST_GU + s) % NSLOT) * 8192 + ((NST_GU + s) % NSLOT >= ALT_SLOT ? dalt : 0);
                uint32_t a[4][4];
#pragma unroll
                for (int j = 0; j < 4; j++) ldsm4t(tile + j * 512, a[j][0], a[j][1], a[j][2], a[j][3]);
                mma_bf(dd[0], a[0][0], a[0][1], a[0][2], a[0][3], hq[2 * s].x, hq[2 * s].y);
                mma_bf(dd[1], a[1][0], a[1][1], a[1][2], a[1][3], hq[2 * s].z, hq[2 * s].w);
                mma_bf(dd[2], a[2][0], a[2][1], a[2][2], a[2][3], hq[2 * s + 1].x, hq[2 * s + 1].y);
                mma_bf(dd[3], a[3][0], a[3][1], a[3][2], a[3][3], hq[2 * s + 1].z, hq[2 * s + 1].w);
            }
            uint32_t ds[4];
#pragma unroll
            for (int j = 0; j < 4; j++) ds[j] = __float_as_uint((dd[0][j] + dd[1][j]) + (dd[2][j] + dd[3][j]));
            if (at == 0) TSTAMP(17);
            const uint32_t o = mapa(sb, h ^ 1);
            st_async16(o + OFF_DP + (128 * h + at) * 16, ds[0], ds[1], ds[2], ds[3], o + M_BARS + 8 * B_DP);
            sts128(sb + OFF_DP + (128 * h + at) * 16, ds[0], ds[1], ds[2], ds[3]);
            __syncwarp();
            if (lane == 0) mbar_arrive(bars + 8 * B_DP);
            mbar_spin(bars + 8 * B_DP);
            float pt[8];
#pragma unroll
            for (int k = 0; k < 8; k++) pt[k] = ldsf(sb + OFF_DP + k * 512 + at * 4);
            const float tot = -(((pt[0] + pt[1]) + (pt[2] + pt[3])) + ((pt[4] + pt[5]) + (pt[6] + pt[7])));
            const float eb = bf_round(bf_hi(gp) * bf_round(xv + bf_round(bf_round(tot) * rs)));
            mbar_wait_n<3, 8>(bars + 8 * (B_Y + 2));
            if (((row >> 8) & 1) == h) p.out[(size_t)row * D_ + 16 * pr + fch] = __float2bfloat16_rn(fmaf(bf_lo(gp), bf_lo(lds16(ya)), eb));
        }
        if (at == 0) { TSTAMP(18); TSDUMP(fb < NGU_CTA ? 0x0087f300u : 0x0087c300u); if (c == 0) *(volatile unsigned*)&p.ex->epoch = epoch + 1; }
    } else {
        const uint32_t t_start = now_ns();
        asm volatile("setmaxnreg.dec.sync.aligned.u32 " HELP_REGS ";");
        if (pw != 12) {
            if (pw >= 14) {
#pragma unroll
                for (int k = 0; k < 5; k++) {
                    const int w = 1 + 2 * k, e = (tid & 63) - 32;
                    sts32(sb + OFF_BAND + k * 256 + (tid & 63) * 4, ((e >= 0 && e < w) ? 0x3C00u : 0u) | ((e + 1 >= 0 && e + 1 < w) ? 0x3C000000u : 0u));
                }
                cluster_next();
            } else {
                if (lane == 0) {
                    asm volatile("prefetch.tensormap [%0];" :: "l"(&tm_r) : "memory");
                    asm volatile("prefetch.tensormap [%0];" :: "l"(&tm_x) : "memory");
                }
                sts32(sb + M_BMAP + lane * 4, 0);
                __syncwarp();
                cluster_next();
                uint4* gz = &p.ex->g[256 * h + 4 * (8 * (pr & 7) + (pr >> 3)) + (lane & 3)];
                uint4* hz = fb < NGU_CTA ? &p.ex->h[32 * fb + lane] : gz;
                st_gpu128(gz, make_uint4(0, 0, 0, 0)); st_gpu128(hz, make_uint4(0, 0, 0, 0));
                if ((ld_gpu128(gz).x | ld_gpu128(hz).x) != 0) __trap();
            }
        } else {
            if (lane == 0) {
#pragma unroll
                for (int k = 0; k < 4; k++) { mbar_init(bars + 8 * (B_X + k), 1); mbar_init(bars + 8 * (B_S + k), 1); }
                asm volatile("fence.proxy.async.shared::cta;" ::: "memory");
                asm volatile("fence.mbarrier_init.release.cluster;" ::: "memory");
            }
            __syncwarp();
            asm volatile("barrier.cluster.arrive.relaxed.aligned;" ::: "memory");
            tma4d_warp(sb + OFF_XROW, &tm_r, 4 * h, pr, bars + 8 * B_X);
            asm volatile("barrier.cluster.wait.acquire.aligned;" ::: "memory");
            if (lane == 0) TSTAMP(20);
#pragma unroll
            for (int i = 0; i < 4; i++) {
                tma5d_both(sb + OFF_S + (4 * h + i) * 8192, &tm_x, 16 * pr, 32 * i + 16 * h, bars + 8 * (B_S + i));
                if (i < 3) tma4d_warp(sb + OFF_XROW + (i + 1) * 8192, &tm_r, 8 * (i + 1) + 4 * h, pr, bars + 8 * (B_X + i + 1));
            }
            if (lane == 0) {
                TSTAMP(24);
#pragma unroll
                for (int k = 0; k < 4; k++) { mbar_expect(bars + 8 * (B_X + k), 8192); mbar_expect(bars + 8 * (B_S + k), 16384); }
                asm volatile("prefetch.tensormap [%0];" :: "l"(&tm_gu) : "memory");
                asm volatile("prefetch.tensormap [%0];" :: "l"(&tm_down) : "memory");
                asm volatile("prefetch.tensormap [%0];" :: "l"(&tm_o) : "memory");
#pragma unroll
                for (int k = 0; k < B_S; k++) mbar_init(bars + 8 * k, k < B_EMPTY ? 1 : 4);
#pragma unroll
                for (int k = B_XS; k < B_X; k++) mbar_init(bars + 8 * k, (k >= B_Y && k < B_SD) ? 9 : (k == B_KD || k == B_TS || k == B_SD) ? 8 : (k == B_TD || k == B_U) ? 4 : k == B_XS + 1 ? 2 : k == B_DP ? 5 : 1);
#pragma unroll
                for (int k = 0; k < B_EMPTY; k++) mbar_expect(bars + 8 * k, 8192);
#pragma unroll
                for (int k = B_XS; k < B_SD; k++) if (k != B_TD && k != B_G) mbar_expect(bars + 8 * k, k < B_TD ? (fb < NGU_CTA ? 8192 : 0) : k == B_SC ? 64 : k == B_DP ? 2048 : k == B_NONE ? 0 : 4096);
                asm volatile("fence.proxy.async.shared::cta;" ::: "memory");
                asm volatile("fence.mbarrier_init.release.cluster;" ::: "memory");
            }
            __syncwarp();
            asm volatile("barrier.cluster.arrive.relaxed.aligned;" ::: "memory");
        }
        bar_arrive(4, 256);
        bar_sync(6, 128);
        if (pw == 15) {
            const unsigned tag = (ld_epoch(p.ex) + 1) & 0xffffu;
            const int tok = lane & 7;
            uint32_t top = 0;
            bool ok = false;
            mbar_wait(bars + 8 * B_XF);
#pragma unroll 1
            for (int it = 0; it < (1 << 22); it++) {
                uint32_t tg;
                asm volatile("ld.relaxed.gpu.global.v2.u32 {%0,%1}, [%2];" : "=r"(top), "=r"(tg) : "l"(&p.ex->top[tok]) : "memory");
                ok = __all_sync(0xffffffffu, tg == tag);
                if (ok) break;
            }
            if (!ok) __trap();
            if (lane == 0) TSTAMP(25);
            const int row = 2047 - (int)(top & 0xffffu);
            if (fb < NGU_CTA) {
#pragma unroll
                for (int k = 0; k < 8; k++) {
                    const int tk = 4 * h + ((k + pr) & 3), hf = k >> 2;
                    bulk_load_both(sb + OFF_XSEL + tk * XS_ROW + 1024 * hf, p.u + (size_t)__shfl_sync(0xffffffffu, row, tk) * D_ + 512 * hf, 1024, bars + 8 * (B_XS + hf));
                }
            }
            if (lane == 0) TSTAMP(21);
            if (lane < 8) {
                const uint32_t ord = top >> 16;
                sts32(sb + M_RSEL + tok * 4, ((ord & 0x8000u) ? (ord & 0x7fffu) : (~ord & 0xffffu)) << 16);
                sts32(sb + M_IDX + tok * 4, (uint32_t)row);
                if (((row >> 8) & 1) == h) asm volatile("red.shared.or.b32 [%0], %1;" :: "r"(sb + M_BMAP + ((row >> 7) & 1) * 64 + (row & 6) * 8 + ((row >> 4) & 3) * 4),
                                                   "r"(1u << (4 * (row >> 9) + ((row >> 5) & 2) + (row & 1) + 2 * (row & 8))) : "memory");
            }
            __syncwarp();
            if (lane == 0) { mbar_arrive(bars + 8 * (B_XS + 1)); TSDUMP(0x02200000u); }
            mbar_wait_n<2, 8>(bars + 8 * (B_XS + 1));
            if (lane == 0) bulk_load(sb + OFF_GP, &p.ex->g[256 * h], 4096, bars + 8 * B_GL);
            __syncwarp();
            mbar_wait(bars + 8 * B_GL);
            uint32_t mn = 0xffffffffu;
#pragma unroll
            for (int i = 0; i < 8; i++) { const uint4 a = lds128(sb + OFF_GP + (32 * i + lane) * 16); mn = min(min(mn, min(a.x, a.y)), min(a.z, a.w)); }
            if (mn == 0) {
#pragma unroll 1
                for (int i = lane, it = 0; i < 256; ) {
                    const uint4 a = ld_gpu128(&p.ex->g[256 * h + i]);
                    if (min(min(a.x, a.y), min(a.z, a.w)) != 0) { sts128(sb + OFF_GP + i * 16, a.x, a.y, a.z, a.w); i += 32; }
                    else if (++it > (1 << 22)) __trap();
                }
            }
            __syncwarp();
            if (lane == 0) { TSTAMP(30); TSDUMP(1u << 30); }
            if (lane == 0) mbar_arrive(bars + 8 * B_G);
            return;
        }
        const int s0 = fb < NGU_CTA ? 0 : NST_GU, s = lane, dn = s >= NST_GU;
        const int slot = s < NSLOT ? s : s < 2 * NSLOT ? s - NSLOT : s - 2 * NSLOT, depth = dn ? DEPTH_D : DEPTH_G;
        const uint32_t dst = sb + OFF_RING + slot * 8192 + (slot >= ALT_SLOT ? (h ? ALT1 : ALT0) + A_SLOT - ALT_SLOT * 8192 : 0);
        const uint32_t due = (t_start + T_W + h * (DT_G / 2) + DT_G * s + (dn ? (DT_D - DT_G) * (s - NST_GU) : 0)) & ~63u;
        const uint32_t w_slot = bars + 8 * (s >= s0 + NSLOT ? B_EMPTY + s - NSLOT : slot >= ALT_SLOT ? B_U : s >= X_SLOT ? B_XF : B_NONE);
        const uint32_t w_depth = bars + 8 * (s >= s0 + depth ? B_FULL + s - depth : B_NONE);
        const CUtensorMap* tm = dn ? &tm_down : &tm_gu;
        const int cx = dn ? 16 * pr : 32 * fb, cy = dn ? 1792 * h + 256 * (s - NST_GU) : 64 * s;
#pragma unroll 1
        for (int k = s0 + pw - 12; k < NST; k += 3) {
            if (lane == k) {
#pragma unroll 1
                for (int n = 0; n < 1000; n++) {
                    const uint32_t now = now_ns();
                    if ((int)(due - now) <= 0) break;
                    __nanosleep(min((now ^ due) >> 1, 1023u));
                }
                mbar_wait2(w_slot, w_depth);
                tma3d(dst, tm, cx, cy, 0, bars + 8 * (B_FULL + s));
            }
            __syncwarp();
        }
    }
}

typedef CUresult (*EncodeFn)(CUtensorMap*, CUtensorMapDataType, cuuint32_t, void*, const cuuint64_t*, const cuuint64_t*,
                             const cuuint32_t*, const cuuint32_t*, CUtensorMapInterleave, CUtensorMapSwizzle,
                             CUtensorMapL2promotion, CUtensorMapFloatOOBfill);

void make_map(EncodeFn f, CUtensorMap* m, const void* ptr, int rank, const cuuint64_t* dims, const cuuint64_t* strides, const cuuint32_t* box, CUtensorMapSwizzle sw) {
    const cuuint32_t es[5] = {1, 1, 1, 1, 1};
    f(m, CU_TENSOR_MAP_DATA_TYPE_BFLOAT16, rank, (void*)ptr, dims, strides, box, es, CU_TENSOR_MAP_INTERLEAVE_NONE, sw,
      CU_TENSOR_MAP_L2_PROMOTION_L2_128B, CU_TENSOR_MAP_FLOAT_OOB_FILL_NONE);
}

}

extern "C" void kernel_launch(void* const* d_in, const int* in_sizes, int n_in, void* d_out, int out_size) {
    static EncodeFn enc = nullptr;
    static void* ex = nullptr;
    if (!enc) {
        void* fn = nullptr;
        cudaDriverEntryPointQueryResult qr;
        cudaGetDriverEntryPoint("cuTensorMapEncodeTiled", &fn, cudaEnableDefault, &qr);
        enc = (EncodeFn)fn;
        cudaFuncSetAttribute(fused_kernel, cudaFuncAttributeMaxDynamicSharedMemorySize, SMEM_BYTES);
        cudaGetSymbolAddress(&ex, g_ex);
    }
    CUtensorMap tgu, td, tx, tr, to;
    const char *wg = (const char*)d_in[9], *wu = (const char*)d_in[10];
    const bool swap = wu < wg;
    {
        const cuuint64_t dims[3] = {F_, D_, 2}, str[2] = {F_ * 2, (cuuint64_t)(swap ? wg - wu : wu - wg)};
        const cuuint32_t box[3] = {32, 64, 2};
        make_map(enc, &tgu, swap ? wu : wg, 3, dims, str, box, CU_TENSOR_MAP_SWIZZLE_64B);
    }
    {
        const cuuint64_t dims[3] = {D_, F_, 1}, str[2] = {D_ * 2, (cuuint64_t)D_ * 2 * F_};
        const cuuint32_t box[3] = {16, 256, 1};
        make_map(enc, &td, d_in[11], 3, dims, str, box, CU_TENSOR_MAP_SWIZZLE_32B);
    }
    {
        const cuuint64_t dims[5] = {D_, 2, 2, L_ / 16, 4}, str[4] = {D_ * 2 * 8, D_ * 2, D_ * 2 * 16, D_ * 2 * 2};
        const cuuint32_t box[5] = {16, 2, 2, 16, 4}, obox[5] = {16, 2, 2, 8, 1};
        make_map(enc, &tx, d_in[0], 5, dims, str, box, CU_TENSOR_MAP_SWIZZLE_32B);
        make_map(enc, &to, d_out, 5, dims, str, obox, CU_TENSOR_MAP_SWIZZLE_32B);
    }
    {
        const cuuint64_t dims[4] = {256, 4, L_ / 64, 64}, str[3] = {512, D_ * 2 * 64, D_ * 2};
        const cuuint32_t box[4] = {256, 4, 4, 1};
        make_map(enc, &tr, d_in[0], 4, dims, str, box, CU_TENSOR_MAP_SWIZZLE_NONE);
    }
    Params p;
    p.u = (const bf16*)d_in[0]; p.logA = (const bf16*)d_in[1]; p.Aim = (const bf16*)d_in[2];
    p.Cre = (const bf16*)d_in[3]; p.Cim = (const bf16*)d_in[4]; p.logdt = (const bf16*)d_in[5];
    p.Dskip = (const bf16*)d_in[6]; p.wr = (const bf16*)d_in[8]; p.gatew = (const bf16*)d_in[12];
    p.out = (bf16*)d_out;
    p.ex = (Exchange*)ex;
    p.zero = 0;
    p.swap_gu = swap ? 4096 : 0;
    fused_kernel<<<NCTA, NTHREADS, SMEM_BYTES>>>(p, tgu, td, tx, tr, to);
}
```

```cpp
#include <cuda_runtime.h>
#include <cuda_bf16.h>
#include <cuda_fp16.h>
#include <cuda.h>
#include <stdint.h>

typedef __nv_bfloat16 bf16;

namespace {

constexpr int L_ = 2048, D_ = 1024, F_ = 3584;
constexpr int NCTA = 130;
constexpr int NTHREADS = 512;
constexpr int MAIN_W0 = 4;
#define T_W 1600
#define DT_G 316
#define DT_D 344
#define DEPTH_G 5
#define DEPTH_D 3
#define H_WAIT 2
#define DN_PRE 5
#define PSLEEP 0
#define GU_BATCH 0
#define FENCES 16
#define MIX0_AT 2
#define MIX1_AT 4
#define SEND0_AT (MIX0_AT + 1)
#define SEND1_AT (MIX1_AT + 1)
#define DUP_MOV 2
#define KD_AT 7
#define KD_ORDER 0
#define STG_FROM 4
#define DV 0
#define SO 0
#define DU 1
#define FB_BLK 1
#define ZR p.zero
#define UNI_WARP 1
#define UNI_V 1
#define A_REUSE 0
#define MAIN_REGS "176"
#define HELP_REGS "32"
constexpr int kDenseUnroll = DU;
constexpr int GU_PRE = 6;
constexpr int NGU_CTA = 112;

constexpr int NSLOT    = 10;
constexpr int NST_GU   = 16, NST = 23;
constexpr int OFF_RING = 0;
constexpr int OFF_XROW = 53248, X_SLOT = 6;
constexpr int OFF_XSEL = 69632, XS_ROW = 2064;
constexpr int OFF_DP   = OFF_XSEL + 8192;
constexpr int OFF_S    = 87040;
constexpr int ALT0     = OFF_S + 32768, ALT1 = OFF_S - 512;
constexpr int A_YIN    = 32, Y_CH = 2064;
constexpr int A_SLOT   = 16896, ALT_SLOT = 8;
constexpr int U_PL     = 1184;
constexpr int U_CH     = 4752;
constexpr int OFF_U    = 153088;
constexpr int T_CH     = 4112;
constexpr int OFF_TAB  = 191104;
constexpr int T_R2     = 2176, T2_S = 208;
constexpr int T_R3     = 3040, T3_S = 336;
constexpr int T_ES     = 4096;
constexpr int OFF_GP   = 224000;
constexpr int OFF_BAND = 228096;
constexpr int OFF_MISC = 229376;
constexpr int M_BARS   = OFF_MISC;
constexpr int M_IDX    = OFF_MISC + 704;
constexpr int M_RSEL   = OFF_MISC + 736;
constexpr int M_BMAP   = OFF_MISC + 768;
constexpr int M_MX     = OFF_MISC + 896;
constexpr int M_SC     = OFF_MISC + 960;
constexpr int M_RG     = OFF_MISC + 1024;
constexpr int SMEM_BYTES = OFF_MISC + 3072;

constexpr int B_FULL = 0, B_EMPTY = NST, B_S = B_EMPTY + NST - NSLOT, B_XS = B_S + 4, B_TD = B_XS + 2, B_SC = B_TD + 1, B_G = B_SC + 1, B_GL = B_G + 1, B_NONE = B_GL + 1, B_DP = B_NONE + 1, B_Y = B_DP + 1,
              B_SD = B_Y + 4, B_KD = B_SD + 1, B_U = B_KD + 1, B_TS = B_U + 1, B_XF = B_TS + 1, B_X = B_XF + 1, NBAR = B_X + 4;
static_assert(NBAR <= 84, "barrier area");

struct Exchange {
    unsigned epoch, pad[31];
    uint4 h[8 * F_ / 8];
    uint4 r[L_ / 4];
    uint4 g[L_ / 4];
    uint2 top[16];
};
__device__ __align__(128) Exchange g_ex;

struct Params {
    const bf16 *logA, *Aim, *Cre, *Cim, *logdt, *Dskip, *u, *wr, *gatew;
    bf16* out;
    Exchange* ex;
    uint32_t zero;
    uint32_t swap_gu;
};

#define TSTAMP(i) do {} while (0)
#define CSTAMP(i) do {} while (0)
#define TSDUMP(mask) do {} while (0)
#define DBG_PARAMS
#define DBG_ARGS

__device__ __forceinline__ uint32_t smem_u32(const void* p) { return (uint32_t)__cvta_generic_to_shared(p); }
__device__ __forceinline__ void mbar_init(uint32_t b, uint32_t c) { asm volatile("mbarrier.init.shared::cta.b64 [%0], %1;" :: "r"(b), "r"(c) : "memory"); }
__device__ __forceinline__ void mbar_expect(uint32_t b, uint32_t tx) { asm volatile("mbarrier.arrive.expect_tx.shared::cta.b64 _, [%0], %1;" :: "r"(b), "r"(tx) : "memory"); }
__device__ __forceinline__ void mbar_arrive(uint32_t b) { asm volatile("mbarrier.arrive.shared::cta.b64 _, [%0];" :: "r"(b) : "memory"); }
#define WSLEEP "100"
#define W2SLEEP "40"
__device__ __forceinline__ void mbar_wait(uint32_t b) {
    asm volatile("{\n\t.reg .pred p, q;\n\t.reg .u32 n;\n\tmov.u32 n, 0;\n"
                 "W%=:\n\tmbarrier.try_wait.parity.shared::cta.b64 p, [%0], 0;\n\t"
                 "@p bra D%=;\n\tnanosleep.u32 " WSLEEP ";\n\tadd.u32 n, n, 1;\n\tsetp.lt.u32 q, n, 4194304;\n\t@q bra W%=;\n"
                 "D%=:\n\t}" :: "r"(b) : "memory");
}
__device__ __forceinline__ void mbar_spin(uint32_t b) {
    asm volatile("{\n\t.reg .pred p, q;\n\t.reg .u32 n;\n\tmov.u32 n, 0;\n"
                 "W%=:\n\tmbarrier.try_wait.parity.shared::cta.b64 p, [%0], 0;\n\t"
                 "@p bra D%=;\n\tadd.u32 n, n, 1;\n\tsetp.lt.u32 q, n, 4194304;\n\t@q bra W%=;\n"
                 "D%=:\n\t}" :: "r"(b) : "memory");
}
__device__ __forceinline__ void mbar_wait2(uint32_t a, uint32_t b) {
    asm volatile("{\n\t.reg .pred p, q;\n\t.reg .u32 n;\n\tmov.u32 n, 0;\n"
                 "W%=:\n\tmbarrier.try_wait.parity.shared::cta.b64 p, [%0], 0;\n\tmbarrier.try_wait.parity.shared::cta.b64 q, [%1], 0;\n\tand.pred p, p, q;\n\t"
                 "@p bra D%=;\n\tnanosleep.u32 " W2SLEEP ";\n\tadd.u32 n, n, 1;\n\tsetp.lt.u32 q, n, 4194304;\n\t@q bra W%=;\n"
                 "D%=:\n\t}" :: "r"(a), "r"(b) : "memory");
}
template <int N, int STEP>
__device__ __forceinline__ void mbar_wait_n(uint32_t b) {
#pragma unroll 1
    for (int n = 0; n < 4194304; n++) {
        uint32_t ok = 1;
#pragma unroll
        for (int i = 0; i < N; i++) {
            uint32_t d;
            asm volatile("{ .reg .pred p; mbarrier.try_wait.parity.shared::cta.b64 p, [%1], 0; selp.u32 %0, 1, 0, p; }" : "=r"(d) : "r"(b + STEP * i) : "memory");
            ok &= d;
        }
        if (ok) break;
    }
}
__device__ __forceinline__ unsigned ld_epoch(const Exchange* e) { unsigned v; asm volatile("ld.volatile.global.u32 %0, [%1];" : "=r"(v) : "l"(e) : "memory"); return v; }
__device__ __forceinline__ uint32_t now_ns() { uint32_t t; asm volatile("mov.u32 %0, %globaltimer_lo;" : "=r"(t)); return t; }
__device__ __forceinline__ uint32_t mapa(uint32_t addr, uint32_t rank) { uint32_t r; asm("mapa.shared::cluster.u32 %0, %1, %2;" : "=r"(r) : "r"(addr), "r"(rank)); return r; }
__device__ __forceinline__ void bulk_load(uint32_t dst, const void* src, uint32_t bytes, uint32_t bar) {
    asm volatile("cp.async.bulk.shared::cluster.global.mbarrier::complete_tx::bytes [%0], [%1], %2, [%3];" :: "r"(dst), "l"(src), "r"(bytes), "r"(bar) : "memory");
}
__device__ __forceinline__ void bulk_load_both(uint32_t dst, const void* src, uint32_t bytes, uint32_t bar) {
    asm volatile("{ .reg .pred p; elect.sync _|p, 0xffffffff;\n\t@p cp.async.bulk.shared::cluster.global.mbarrier::complete_tx::bytes.multicast::cluster [%0], [%1], %2, [%3], %4; }"
                 :: "r"(dst), "l"(src), "r"(bytes), "r"(bar), "h"((unsigned short)3) : "memory");
}
__device__ __forceinline__ void tma3d(uint32_t dst, const CUtensorMap* tm, int c0, int c1, int c2, uint32_t bar) {
    asm volatile("cp.async.bulk.tensor.3d.shared::cluster.global.mbarrier::complete_tx::bytes [%0], [%1, {%3, %4, %5}], [%2];"
        :: "r"(dst), "l"(tm), "r"(bar), "r"(c0), "r"(c1), "r"(c2) : "memory");
}
__device__ __forceinline__ void tma4d_warp(uint32_t dst, const CUtensorMap* tm, int c2, int c3, uint32_t bar) {
    asm volatile("{ .reg .pred p; elect.sync _|p, 0xffffffff;\n\t@p cp.async.bulk.tensor.4d.shared::cluster.global.mbarrier::complete_tx::bytes [%0], [%1, {%5, %5, %3, %4}], [%2]; }"
        :: "r"(dst), "l"(tm), "r"(bar), "r"(c2), "r"(c3), "r"(0) : "memory");
}
__device__ __forceinline__ void tma5d_both(uint32_t dst, const CUtensorMap* tm, int c0, int c3, uint32_t bar) {
    asm volatile("{ .reg .pred p; elect.sync _|p, 0xffffffff;\n\t@p cp.async.bulk.tensor.5d.shared::cluster.global.mbarrier::complete_tx::bytes.multicast::cluster [%0], [%1, {%3, %5, %5, %4, %5}], [%2], %6; }"
        :: "r"(dst), "l"(tm), "r"(bar), "r"(c0), "r"(c3), "r"(0), "h"((unsigned short)3) : "memory");
}
__device__ __forceinline__ void cluster_next() { asm volatile("barrier.cluster.wait.acquire.aligned;\n\tbarrier.cluster.arrive.relaxed.aligned;" ::: "memory"); }
__device__ __forceinline__ void st_async16(uint32_t dst, uint32_t x, uint32_t y, uint32_t z, uint32_t w, uint32_t bar) {
    asm volatile("st.async.weak.shared::cluster.mbarrier::complete_tx::bytes.v4.b32 [%0], {%1,%2,%3,%4}, [%5];"
                 :: "r"(dst), "r"(x), "r"(y), "r"(z), "r"(w), "r"(bar) : "memory");
}
__device__ __forceinline__ void st_async4(uint32_t dst, uint32_t v, uint32_t bar) {
    asm volatile("st.async.weak.shared::cluster.mbarrier::complete_tx::bytes.b32 [%0], %1, [%2];" :: "r"(dst), "r"(v), "r"(bar) : "memory");
}
__device__ __forceinline__ void bar_sync(int id, int n) { asm volatile("bar.sync %0, %1;" :: "r"(id), "r"(n) : "memory"); }
__device__ __forceinline__ void bar_arrive(int id, int n) { asm volatile("bar.arrive %0, %1;" :: "r"(id), "r"(n) : "memory"); }
__device__ __forceinline__ void cp16(uint32_t dst, const void* src) { asm volatile("cp.async.cg.shared.global [%0], [%1], 16;" :: "r"(dst), "l"(src) : "memory"); }
__device__ __forceinline__ void cp_wait_all() { asm volatile("cp.async.wait_all;" ::: "memory"); }
__device__ __forceinline__ uint32_t ldg16(const void* p) { uint32_t v; asm volatile("ld.global.nc.u16 %0, [%1];" : "=r"(v) : "l"(p)); return v; }
__device__ __forceinline__ uint2 ldg64(const void* p) { uint2 v; asm volatile("ld.global.nc.v2.u32 {%0,%1}, [%2];" : "=r"(v.x), "=r"(v.y) : "l"(p)); return v; }
__device__ __forceinline__ uint4 ldg128(const void* p) { uint4 v; asm volatile("ld.global.nc.v4.u32 {%0,%1,%2,%3}, [%4];" : "=r"(v.x), "=r"(v.y), "=r"(v.z), "=r"(v.w) : "l"(p)); return v; }
__device__ __forceinline__ uint4 ld_gpu128(const void* p) { uint4 v; asm volatile("ld.relaxed.gpu.global.v4.u32 {%0,%1,%2,%3}, [%4];" : "=r"(v.x), "=r"(v.y), "=r"(v.z), "=r"(v.w) : "l"(p) : "memory"); return v; }
__device__ __forceinline__ void st_gpu32(void* p, uint32_t v) { asm volatile("st.relaxed.gpu.global.u32 [%0], %1;" :: "l"(p), "r"(v) : "memory"); }
__device__ __forceinline__ void st_gpu128(void* p, const uint4& v) { asm volatile("st.relaxed.gpu.global.v4.u32 [%0], {%1,%2,%3,%4};" :: "l"(p), "r"(v.x), "r"(v.y), "r"(v.z), "r"(v.w) : "memory"); }

__device__ __forceinline__ void ldsm4(uint32_t a, uint32_t& r0, uint32_t& r1, uint32_t& r2, uint32_t& r3) {
    asm volatile("ldmatrix.sync.aligned.m8n8.x4.shared.b16 {%0,%1,%2,%3}, [%4];" : "=r"(r0), "=r"(r1), "=r"(r2), "=r"(r3) : "r"(a) : "memory");
}
__device__ __forceinline__ void ldsm2(uint32_t a, uint32_t& r0, uint32_t& r1) {
    asm volatile("ldmatrix.sync.aligned.m8n8.x2.shared.b16 {%0,%1}, [%2];" : "=r"(r0), "=r"(r1) : "r"(a) : "memory");
}
__device__ __forceinline__ void ldsm4t(uint32_t a, uint32_t& r0, uint32_t& r1, uint32_t& r2, uint32_t& r3) {
    asm volatile("ldmatrix.sync.aligned.m8n8.x4.trans.shared.b16 {%0,%1,%2,%3}, [%4];" : "=r"(r0), "=r"(r1), "=r"(r2), "=r"(r3) : "r"(a) : "memory");
}
__device__ __forceinline__ uint32_t lds16(uint32_t a) { uint32_t v; asm volatile("ld.shared.u16 %0, [%1];" : "=r"(v) : "r"(a) : "memory"); return v; }
__device__ __forceinline__ uint32_t lds32(uint32_t a) { uint32_t v; asm volatile("ld.shared.u32 %0, [%1];" : "=r"(v) : "r"(a) : "memory"); return v; }
__device__ __forceinline__ uint2 lds64(uint32_t a) { uint2 v; asm volatile("ld.shared.v2.u32 {%0,%1}, [%2];" : "=r"(v.x), "=r"(v.y) : "r"(a) : "memory"); return v; }
__device__ __forceinline__ uint4 lds128(uint32_t a) { uint4 v; asm volatile("ld.shared.v4.u32 {%0,%1,%2,%3}, [%4];" : "=r"(v.x), "=r"(v.y), "=r"(v.z), "=r"(v.w) : "r"(a) : "memory"); return v; }
__device__ __forceinline__ void sts16(uint32_t a, uint32_t v) { asm volatile("st.shared.u16 [%0], %1;" :: "r"(a), "r"(v) : "memory"); }
__device__ __forceinline__ void sts32(uint32_t a, uint32_t v) { asm volatile("st.shared.u32 [%0], %1;" :: "r"(a), "r"(v) : "memory"); }
__device__ __forceinline__ void sts64(uint32_t a, uint32_t x, uint32_t y) { asm volatile("st.shared.v2.u32 [%0], {%1,%2};" :: "r"(a), "r"(x), "r"(y) : "memory"); }
__device__ __forceinline__ void sts128(uint32_t a, uint32_t x, uint32_t y, uint32_t z, uint32_t w) { asm volatile("st.shared.v4.u32 [%0], {%1,%2,%3,%4};" :: "r"(a), "r"(x), "r"(y), "r"(z), "r"(w) : "memory"); }
__device__ __forceinline__ void sts16_if(bool p, uint32_t a, uint32_t v) { asm volatile("{ .reg .pred q; setp.ne.u32 q, %2, 0; @q st.shared.u16 [%0], %1; }" :: "r"(a), "h"((unsigned short)v), "r"((uint32_t)p) : "memory"); }
__device__ __forceinline__ void sts128_if(bool p, uint32_t a, uint32_t x, uint32_t y, uint32_t z, uint32_t w) {
    asm volatile("{ .reg .pred q; setp.ne.u32 q, %5, 0; @q st.shared.v4.u32 [%0], {%1,%2,%3,%4}; }" :: "r"(a), "r"(x), "r"(y), "r"(z), "r"(w), "r"((uint32_t)p) : "memory");
}
__device__ __forceinline__ void stsf(uint32_t a, float v) { asm volatile("st.shared.f32 [%0], %1;" :: "r"(a), "f"(v) : "memory"); }
__device__ __forceinline__ float ldsf(uint32_t a) { float v; asm volatile("ld.shared.f32 %0, [%1];" : "=f"(v) : "r"(a) : "memory"); return v; }

__device__ __forceinline__ void mma_bf(float (&d)[4], uint32_t a0, uint32_t a1, uint32_t a2, uint32_t a3, uint32_t b0, uint32_t b1) {
    asm volatile("mma.sync.aligned.m16n8k16.row.col.f32.bf16.bf16.f32 {%0,%1,%2,%3}, {%4,%5,%6,%7}, {%8,%9}, {%0,%1,%2,%3};"
        : "+f"(d[0]), "+f"(d[1]), "+f"(d[2]), "+f"(d[3]) : "r"(a0), "r"(a1), "r"(a2), "r"(a3), "r"(b0), "r"(b1));
}
__device__ __forceinline__ void widen_bf(float (&d)[4], uint32_t a0, uint32_t a1, uint32_t b) {
    asm volatile("mma.sync.aligned.m16n8k8.row.col.f32.bf16.bf16.f32 {%0,%1,%2,%3}, {%4,%5}, {%6}, {%7,%7,%7,%7};"
        : "=f"(d[0]), "=f"(d[1]), "=f"(d[2]), "=f"(d[3]) : "r"(a0), "r"(a1), "r"(b), "f"(0.f));
}
__device__ __forceinline__ void widen_h(float (&d)[4], const uint32_t (&a)[2], uint32_t b) {
    asm volatile("mma.sync.aligned.m16n8k8.row.col.f32.f16.f16.f32 {%0,%1,%2,%3}, {%4,%5}, {%6}, {%7,%7,%7,%7};"
        : "=f"(d[0]), "=f"(d[1]), "=f"(d[2]), "=f"(d[3]) : "r"(a[0]), "r"(a[1]), "r"(b), "f"(0.f));
}
__device__ __forceinline__ void widen_add_h(float (&d)[4], const uint32_t (&a)[2], uint32_t b, const float (&c)[4]) {
    asm volatile("mma.sync.aligned.m16n8k8.row.col.f32.f16.f16.f32 {%0,%1,%2,%3}, {%4,%5}, {%6}, {%7,%8,%9,%10};"
        : "=f"(d[0]), "=f"(d[1]), "=f"(d[2]), "=f"(d[3]) : "r"(a[0]), "r"(a[1]), "r"(b), "f"(c[0]), "f"(c[1]), "f"(c[2]), "f"(c[3]));
}
__device__ __forceinline__ void mma_h(uint32_t (&d)[2], const uint32_t (&a)[4], uint32_t b0, uint32_t b1) {
    asm volatile("mma.sync.aligned.m16n8k16.row.col.f16.f16.f16.f16 {%0,%1}, {%2,%3,%4,%5}, {%6,%7}, {%0,%1};"
        : "+r"(d[0]), "+r"(d[1]) : "r"(a[0]), "r"(a[1]), "r"(a[2]), "r"(a[3]), "r"(b0), "r"(b1));
}
__device__ __forceinline__ void mma_h_z(uint32_t& d0, uint32_t& d1, const uint32_t (&a)[4], uint32_t b0, uint32_t b1) {
    asm volatile("mma.sync.aligned.m16n8k16.row.col.f16.f16.f16.f16 {%0,%1}, {%2,%3,%4,%5}, {%6,%7}, {%8,%8};"
        : "=r"(d0), "=r"(d1) : "r"(a[0]), "r"(a[1]), "r"(a[2]), "r"(a[3]), "r"(b0), "r"(b1), "r"(0u));
}
__device__ __forceinline__ void mma_h2(uint32_t& d0, uint32_t& d1, const uint32_t (&a)[4], uint32_t b0, uint32_t b1) {
    asm volatile("mma.sync.aligned.m16n8k16.row.col.f16.f16.f16.f16 {%0,%1}, {%2,%3,%4,%5}, {%6,%7}, {%0,%1};"
        : "+r"(d0), "+r"(d1) : "r"(a[0]), "r"(a[1]), "r"(a[2]), "r"(a[3]), "r"(b0), "r"(b1));
}
__device__ __forceinline__ void mma_h_k8(uint32_t& d0, uint32_t& d1, uint32_t a0, uint32_t a1, uint32_t b) {
    asm volatile("mma.sync.aligned.m16n8k8.row.col.f16.f16.f16.f16 {%0,%1}, {%2,%3}, {%4}, {%0,%1};" : "+r"(d0), "+r"(d1) : "r"(a0), "r"(a1), "r"(b));
}
__device__ __forceinline__ void mma_h_k8_z(uint32_t (&d)[2], uint32_t a0, uint32_t a1, uint32_t b) {
    asm volatile("mma.sync.aligned.m16n8k8.row.col.f16.f16.f16.f16 {%0,%1}, {%2,%3}, {%4}, {%5,%5};" : "=r"(d[0]), "=r"(d[1]) : "r"(a0), "r"(a1), "r"(b), "r"(0u));
}
__device__ __forceinline__ uint32_t pack_bf(float lo, float hi) { uint32_t r; asm("cvt.rn.bf16x2.f32 %0, %1, %2;" : "=r"(r) : "f"(hi), "f"(lo)); return r; }
__device__ __forceinline__ uint32_t pack_h(float lo, float hi) { uint32_t r; asm("cvt.rn.f16x2.f32 %0, %1, %2;" : "=r"(r) : "f"(hi), "f"(lo)); return r; }
__device__ __forceinline__ float bf_lo(uint32_t v) { return __uint_as_float(v << 16); }
__device__ __forceinline__ float bf_hi(uint32_t v) { return __uint_as_float(v & 0xffff0000u); }
__device__ __forceinline__ float bf_round(float x) { return __uint_as_float(pack_bf(0.f, x) & 0xffff0000u); }
__device__ __forceinline__ uint32_t hmul2_bf(uint32_t a, uint32_t b) { uint32_t r; asm("mul.rn.bf16x2 %0, %1, %2;" : "=r"(r) : "r"(a), "r"(b)); return r; }
__device__ __forceinline__ uint32_t hadd2_bf(uint32_t a, uint32_t b) { uint32_t r; asm("add.rn.bf16x2 %0, %1, %2;" : "=r"(r) : "r"(a), "r"(b)); return r; }
__device__ __forceinline__ uint32_t hfma2_bf(uint32_t a, uint32_t b, uint32_t c) { uint32_t r; asm("fma.rn.bf16x2 %0, %1, %2, %3;" : "=r"(r) : "r"(a), "r"(b), "r"(c)); return r; }
__device__ __forceinline__ uint32_t hi_mul_bf(uint32_t a, uint32_t b) { uint32_t r; asm("{ .reg .b16 l, h; .reg .b32 t; mov.b32 {l, h}, %1; mov.b32 t, {h, h}; mul.rn.bf16x2 %0, t, %2; }" : "=r"(r) : "r"(a), "r"(b)); return r; }
__device__ __forceinline__ uint32_t lo_fma_bf(uint32_t a, uint32_t b, uint32_t c) { uint32_t r; asm("{ .reg .b16 l, h; .reg .b32 t; mov.b32 {l, h}, %1; mov.b32 t, {l, l}; fma.rn.bf16x2 %0, t, %2, %3; }" : "=r"(r) : "r"(a), "r"(b), "r"(c)); return r; }
__device__ __forceinline__ uint32_t amax2_bf(uint32_t m, uint32_t v) { uint32_t r; asm("max.xorsign.abs.bf16x2 %0, %1, %2;" : "=r"(r) : "r"(m), "r"(v)); return r; }
__device__ __forceinline__ uint32_t amax2_h(uint32_t m, uint32_t v) { uint32_t r; asm("max.xorsign.abs.f16x2 %0, %1, %2;" : "=r"(r) : "r"(m), "r"(v)); return r; }
__device__ __forceinline__ uint32_t hadd(uint32_t a, uint32_t b) { uint32_t r; asm("add.rn.f16x2 %0, %1, %2;" : "=r"(r) : "r"(a), "r"(b)); return r; }
__device__ __forceinline__ uint32_t hsub(uint32_t a, uint32_t b) { uint32_t r; asm("sub.rn.f16x2 %0, %1, %2;" : "=r"(r) : "r"(a), "r"(b)); return r; }
__device__ __forceinline__ uint32_t hsub2(uint32_t a, uint32_t b) { uint32_t r; asm("sub.rn.ftz.f16x2 %0, %1, %2;" : "=r"(r) : "r"(a), "r"(b)); return r; }
__device__ __forceinline__ uint32_t hmul(uint32_t a, uint32_t b) { uint32_t r; asm("mul.rn.f16x2 %0, %1, %2;" : "=r"(r) : "r"(a), "r"(b)); return r; }
__device__ __forceinline__ uint32_t hfma(uint32_t a, uint32_t b, uint32_t c) { uint32_t r; asm("fma.rn.f16x2 %0, %1, %2, %3;" : "=r"(r) : "r"(a), "r"(b), "r"(c)); return r; }
__device__ __forceinline__ uint32_t hfms(uint32_t a, uint32_t b, uint32_t c) { uint32_t r; asm("{ .reg .b32 t; neg.f16x2 t, %3; fma.rn.f16x2 %0, %1, %2, t; }" : "=r"(r) : "r"(a), "r"(b), "r"(c)); return r; }
__device__ __forceinline__ uint32_t warp_max16(uint32_t m) { return __reduce_max_sync(0xffffffffu, max(m & 0x7fffu, (m >> 16) & 0x7fffu)); }
__device__ __forceinline__ float ex2f(float x) { float r; asm("ex2.approx.ftz.f32 %0, %1;" : "=f"(r) : "f"(x)); return r; }

__device__ __forceinline__ float exp_acc(float x) {
    const float t = x * 1.4426950216293335f;
    const float r = fmaf(x, 1.4426950216293335f, -t) + x * 1.9259629911266175e-8f;
    return ex2f(t) * fmaf(r, 0.6931471805599453f, 1.f);
}
__device__ __forceinline__ float sigmoid_f(float x) { return __fdividef(1.f, 1.f + ex2f(-x * 1.4426950408889634f)); }
__device__ __forceinline__ void cexp(float l2, float th, float& zr, float& zi) {
    const float mag = ex2f(l2);
    const float k = (th * 0.15915494309189535f + 12582912.f) - 12582912.f;
    float r = fmaf(-k, 6.2831854820251465f, th);
    r = fmaf(-k, -1.7484555314695172e-7f, r);
    zr = mag * __cosf(r);
    zi = mag * __sinf(r);
}
struct hc { uint32_t re, im; };
__device__ __forceinline__ hc cmul(const hc& a, const hc& b) { return {hfms(a.re, b.re, hmul(a.im, b.im)), hfma(a.re, b.im, hmul(a.im, b.re))}; }
__device__ __forceinline__ hc cmulc(const hc& a, const hc& b) { return {hfma(a.re, b.re, hmul(a.im, b.im)), hfms(a.im, b.re, hmul(a.re, b.im))}; }
struct fc2 { float r[2], i[2]; };
__device__ __forceinline__ void csq(fc2& z) {
#pragma unroll
    for (int m = 0; m < 2; m++) {
        const float r = fmaf(z.r[m], z.r[m], -(z.i[m] * z.i[m]));
        asm("{ .reg .f32 t; mul.f32 t, %0, %1; mul.f32 %0, t, 0f40000000; }" : "+f"(z.i[m]) : "f"(z.r[m]));
        z.r[m] = r;
    }
}
__device__ __forceinline__ hc pk(const fc2& z) { return {pack_h(z.r[0], z.r[1]), pack_h(z.i[0], z.i[1])}; }
__device__ __forceinline__ void csq_conj(fc2& z) {
#pragma unroll
    for (int m = 0; m < 2; m++) {
        const float r = fmaf(z.r[m], z.r[m], -(z.i[m] * z.i[m]));
        asm("{ .reg .f32 t, n; neg.f32 n, %1; mul.f32 t, %0, n; mul.f32 %0, t, 0f40000000; }" : "+f"(z.i[m]) : "f"(z.r[m]));
        z.r[m] = r;
    }
}

struct Powers { hc C, z1, z2, z4, c8, c16, c32, c64, z128, z256, z512, z1024; };
__device__ __forceinline__ void kg_powers(Powers& q, uint32_t la, uint32_t ai, uint32_t cr, uint32_t ci, float dt, float cf) {
    fc2 z, y;
    const float dtl = -dt * 1.4426950408889634f;
    const uint32_t eb = pack_bf(ex2f(bf_lo(la) * 1.4426950408889634f), ex2f(bf_hi(la) * 1.4426950408889634f));
    const float l2[2] = {bf_lo(eb) * dtl, bf_hi(eb) * dtl}, th[2] = {bf_lo(ai) * dt, bf_hi(ai) * dt};
#pragma unroll
    for (int m = 0; m < 2; m++) { cexp(l2[m], th[m], z.r[m], z.i[m]); cexp(l2[m] * 128.f, th[m] * 128.f, y.r[m], y.i[m]); }
    q.C.re = pack_h(bf_lo(cr) * cf, bf_hi(cr) * cf);
    q.C.im = pack_h(bf_lo(ci) * cf, bf_hi(ci) * cf);
    q.z1 = pk(z); csq(z); q.z128 = pk(y); csq(y);
    q.z2 = pk(z); csq(z); q.z256 = pk(y); csq(y);
    q.z4 = pk(z); csq_conj(z); q.z512 = pk(y); csq(y);
    q.c8 = pk(z); csq(z); q.z1024 = pk(y);
    q.c16 = pk(z); csq(z);
    q.c32 = pk(z); csq(z);
    q.c64 = pk(z);
}
struct Rows { hc ta[8], tb[8], tc[8], pp[8]; };
#define PUT(a0, a1, row, a, b) sts128((((row) & 1) ? (a1) : (a0)) + (row) * 512, (a).re, (a).im, (b).re, (b).im)
template <bool FIRST>
__device__ __forceinline__ void kg_rows(Rows& w, const Powers& q, uint32_t t0, uint32_t t1, uint32_t u0, uint32_t u1, uint32_t uc, uint32_t zr, uint32_t (&Rl)[2]) {
    w.ta[0] = q.C; w.ta[1] = cmul(q.C, q.z1); w.ta[2] = cmul(q.C, q.z2); w.ta[4] = cmul(q.C, q.z4); w.tb[0] = cmul(q.C, q.z256); w.tb[4] = cmul(q.C, q.z512);
    PUT(t0, t1, 0, w.ta[0], w.tb[0]); PUT(t0, t1, 4, w.ta[4], w.tb[4]);
    w.tb[1] = cmul(w.ta[2], q.z256); w.tb[2] = cmul(w.ta[4], q.z256);
    PUT(t0, t1, 1, w.ta[1], w.tb[1]); PUT(t0, t1, 2, w.ta[2], w.tb[2]);
    w.ta[3] = cmul(w.ta[1], q.z2); w.ta[6] = cmul(w.ta[2], q.z4); w.ta[5] = cmul(w.ta[1], q.z4); w.tb[5] = cmul(w.ta[4], q.z512); w.tb[6] = cmul(w.tb[0], q.z512);
    PUT(t0, t1, 5, w.ta[5], w.tb[5]); PUT(t0, t1, 6, w.ta[6], w.tb[6]);
    w.tb[3] = cmul(w.ta[6], q.z256); w.ta[7] = cmul(w.ta[3], q.z4); w.tb[7] = cmul(w.tb[2], q.z512);
    PUT(t0, t1, 3, w.ta[3], w.tb[3]); PUT(t0, t1, 7, w.ta[7], w.tb[7]);
    sts64(uc, q.c64.re, q.c64.im);
    w.pp[0] = hc{0x3C003C00u ^ zr, zr}; w.pp[1] = q.c8; w.pp[2] = q.c16; w.pp[4] = q.c32;
    w.tc[0] = cmul(q.C, q.z1024); w.pp[3] = cmul(q.c8, q.c16); w.pp[5] = cmul(q.c8, q.c32); w.pp[6] = cmul(q.c16, q.c32);
    w.tc[2] = cmul(w.tc[0], q.z128); w.tc[4] = cmul(w.tc[0], q.z256); w.tc[1] = cmul(w.tc[0], q.z512); w.pp[7] = cmul(w.pp[3], q.c32);
    PUT(u0, u1, 0, w.tc[0], w.pp[0]); PUT(u0, u1, 1, w.tc[1], w.pp[1]); PUT(u0, u1, 2, w.tc[2], w.pp[2]); PUT(u0, u1, 4, w.tc[4], w.pp[4]);
    w.tc[6] = cmul(w.tc[2], q.z256); w.tc[3] = cmul(w.tc[2], q.z512); w.tc[5] = cmul(w.tc[4], q.z512);
    PUT(u0, u1, 3, w.tc[3], w.pp[3]); PUT(u0, u1, 5, w.tc[5], w.pp[5]); PUT(u0, u1, 6, w.tc[6], w.pp[6]);
    w.tc[7] = cmul(w.tc[6], q.z512);
    PUT(u0, u1, 7, w.tc[7], w.pp[7]);
    const uint32_t last = hfms(w.tc[0].re, q.z1024.re, hmul(w.tc[0].im, q.z1024.im));
    if (FIRST) mma_h_k8_z(Rl, 0x3C003C00u - zr, 0x3C003C00u + zr, last); else mma_h_k8(Rl[0], Rl[1], 0x3C003C00u - zr, 0x3C003C00u + zr, last);
}
#undef PUT
template <bool FIRST>
__device__ __forceinline__ void kg_products(uint32_t rt0, uint32_t rt1, uint32_t ru0, uint32_t ru1, uint32_t rc, uint32_t zr, uint32_t done, int lane,
                                            uint32_t (&Ra)[2][2], uint32_t (&Rb)[2][2], uint32_t (&Rc)[2]) {
    uint4 q1[8], q2[8], cw[8];
    if (!FIRST && KD_ORDER) {
#pragma unroll
        for (int ks = 0; ks < 8; ks++) { q2[ks] = lds128(((ks & 1) ? ru1 : ru0) + (ks >> 1) * 128); if (!(ks & 1)) cw[ks] = lds128(rc + ks * 32); if (ks < 2) q1[ks] = lds128(ks ? rt1 : rt0); }
#pragma unroll
        for (int ks = 2; ks < 8; ks++) q1[ks] = lds128(((ks & 1) ? rt1 : rt0) + (ks >> 1) * 128);
    } else
#pragma unroll
    for (int ks = 0; ks < 8; ks++) {
        q2[ks] = lds128(((ks & 1) ? ru1 : ru0) + (ks >> 1) * 128); if (!(ks & 1)) cw[ks] = lds128(rc + ks * 32); q1[ks] = lds128(((ks & 1) ? rt1 : rt0) + (ks >> 1) * 128);
    }
#pragma unroll
    for (int ks = 0; ks < 8; ks++) {
        const hc p0 = {q2[ks].z, q2[ks].w}, u = (ks & 1) ? hc{cw[ks & 6].z, cw[ks & 6].w} : hc{cw[ks].x, cw[ks].y};
        const hc p1 = cmul(p0, u), p2 = cmul(p1, u), p3 = cmul(p2, u);

        const uint32_t qa[4] = {p0.re ^ zr, p1.re, p0.im ^ zr, p1.im}, qb[4] = {p2.re, p3.re, p2.im, p3.im};
        if (!FIRST && ks == KD_AT) {
            uint32_t all = zr;
#pragma unroll
            for (int i = KD_AT; i < 8; i++) all &= q2[i].x & cw[i & 6].x;
            __syncwarp();
            if (lane == 0) mbar_arrive(done + all);
        }
        if (FIRST && ks == 0) {
            mma_h_z(Rc[0], Rc[1], qa, q2[ks].x, q2[ks].y); mma_h_z(Ra[0][0], Ra[0][1], qa, q1[ks].x, q1[ks].y); mma_h_z(Rb[0][0], Rb[0][1], qa, q1[ks].z, q1[ks].w);
            mma_h_z(Ra[1][0], Ra[1][1], qb, q1[ks].x, q1[ks].y); mma_h_z(Rb[1][0], Rb[1][1], qb, q1[ks].z, q1[ks].w);
        } else {
            mma_h(Rc, qa, q2[ks].x, q2[ks].y); mma_h(Ra[0], qa, q1[ks].x, q1[ks].y); mma_h(Rb[0], qa, q1[ks].z, q1[ks].w);
            mma_h(Ra[1], qb, q1[ks].x, q1[ks].y); mma_h(Rb[1], qb, q1[ks].z, q1[ks].w);
        }
    }
}
__device__ __forceinline__ void kernel_gen(const uint2& la, const uint2& ai, const uint2& cr, const uint2& ci, float dt, float cf, uint32_t TB, uint32_t UB, uint32_t done,
                                           int lane, uint32_t zr, uint32_t (&Ra)[2][2], uint32_t (&Rb)[2][2], uint32_t (&Rc)[2], uint32_t (&Rl)[2]) {
    const int g = lane >> 2, t = lane & 3;
    const uint32_t w0 = lane << 4, w1 = w0 ^ 64, r0 = g * 512 + (((g & 1) << 6) | (t << 4)), r1 = r0 ^ 64;
    const uint32_t t0 = TB + w0, t1 = TB + w1, u0 = UB + w0, u1 = UB + w1;
    const uint32_t uc = UB + 4096 + (lane >> 3) * 64 + t * 16 + (lane & 4) * 2;
    Powers p0, p1;
    Rows w;
    kg_powers(p0, la.x, ai.x, cr.x, ci.x, dt, cf);
    kg_rows<true>(w, p0, t0, t1, u0, u1, uc, zr, Rl);
    kg_powers(p1, la.y, ai.y, cr.y, ci.y, dt, cf);
    __syncwarp();
    kg_products<true>(TB + r0, TB + r1, UB + r0, UB + r1, UB + 4096 + t * 16, zr, done, lane, Ra, Rb, Rc);
    __syncwarp();
    asm volatile("barrier.cluster.wait.acquire.aligned;" ::: "memory");
    kg_rows<false>(w, p1, t0, t1, u0, u1, uc, zr, Rl);
    __syncwarp();
    kg_products<false>(TB + r0, TB + r1, UB + r0, UB + r1, UB + 4096 + t * 16, zr, done, lane, Ra, Rb, Rc);
    __syncwarp();
}

template <int V> struct IC { static constexpr int value = V; };

#define LANE_VARS \
    int tid_; asm volatile("mov.u32 %0, %%tid.x;" : "=r"(tid_)); \
    [[maybe_unused]] const int lane = tid_ & 31, warp = UNI_WARP ? wuni : (tid_ >> 5) - MAIN_W0, g = lane >> 2, t = lane & 3, mi = lane >> 3, r = lane & 7; \
    [[maybe_unused]] const uint32_t TB = sb + OFF_TAB + warp * T_CH, UB = sb + OFF_U + warp * U_CH; \
    [[maybe_unused]] const bool lead = (tid_ == 32 * MAIN_W0)

#define FENCE() do { if (zr) asm volatile("exit;"); } while (0)
template <int ORD>
__device__ __forceinline__ void stream(uint32_t (&D)[8][2], const uint32_t (&Q)[2][4], const uint32_t (&V)[8][2]) {
    if (ORD == 0) {
#pragma unroll
        for (int J = 0; J < 8; J++) mma_h(D[J], Q[0], V[J][0], V[J][1]);
#pragma unroll
        for (int J = 1; J < 8; J++) mma_h(D[J], Q[1], V[J - 1][0], V[J - 1][1]);
    } else if (ORD == 1) {
#pragma unroll
        for (int J = 1; J < 8; J++) mma_h(D[J], Q[1], V[J - 1][0], V[J - 1][1]);
#pragma unroll
        for (int J = 0; J < 8; J++) mma_h(D[J], Q[0], V[J][0], V[J][1]);
    } else {
#pragma unroll
        for (int J = 7; J >= 0; J--) mma_h(D[J], Q[0], V[J][0], V[J][1]);
#pragma unroll
        for (int J = 7; J >= 1; J--) mma_h(D[J], Q[1], V[J - 1][0], V[J - 1][1]);
    }
}
__device__ __forceinline__ void dense_step(uint32_t (&M)[8][2], uint32_t (&Ye)[8][2], uint32_t (&Yo)[8][2], uint32_t (&X)[8][2],
                                           uint32_t (&F)[8][2], uint32_t (&Bq)[2][4], uint32_t ua, uint32_t ta, uint32_t zr) {
    uint32_t E[8][2], A[2][4], S[2][4], G[8][2], Bn[2][2];
    auto load_e = [&]() {
#pragma unroll
        for (int jp = 0; jp < 4; jp++) ldsm4(ua + jp * 256, E[2 * jp][0], E[2 * jp][1], E[2 * jp + 1][0], E[2 * jp + 1][1]);
    };
    auto load_a = [&]() {
#pragma unroll
        for (int h = 0; h < 2; h++) {
            A[h][0] = A_REUSE ? Bq[h][3] ^ zr : lds32(ta + 1024 * h); A[h][1] = lds32(ta + 1024 * h + 32); A[h][3] = lds32(ta + 1024 * h + 64);
            A[h][2] = (DV & 8) ? lds32(ta + 1024 * h + 32 + zr) : A[h][1] ^ zr;
        }
    };
    if (DV & 1) { load_a(); load_e(); } else { load_e(); load_a(); }
    if (DV & 2) {
#pragma unroll
        for (int h = 0; h < 2; h++) { Bn[h][0] = lds32(ta + 1024 * h + 96); Bn[h][1] = lds32(ta + 1024 * h + 128); }
        stream<SO % 3>(Ye, Bq, F);
#pragma unroll
        for (int h = 0; h < 2; h++) { S[h][0] = hadd(A[h][0], A[h][3]); S[h][1] = hadd(A[h][1], Bn[h][0]); S[h][2] = hadd(A[h][2], Bn[h][0]); S[h][3] = hadd(A[h][3], Bn[h][1]); }
#pragma unroll
        for (int J = 0; J < 8; J++) { G[J][0] = hsub(X[J][0], E[J][0]); G[J][1] = hsub(X[J][1], E[J][1]); }
#pragma unroll
        for (int jp = 0; jp < 4; jp++) ldsm4(ua + 2 * U_PL + jp * 256 - 16, X[2 * jp][0], X[2 * jp][1], X[2 * jp + 1][0], X[2 * jp + 1][1]);
        if (DV & 4) FENCE();
        stream<(SO / 9) % 3>(M, S, E);
#pragma unroll
        for (int h = 0; h < 2; h++) { Bq[h][0] = A[h][3] ^ zr; Bq[h][1] = Bn[h][0]; Bq[h][2] = Bn[h][0] ^ zr; Bq[h][3] = Bn[h][1]; }
#pragma unroll
        for (int J = 0; J < 8; J++) { F[J][0] = hsub(X[J][0], E[J][0]); F[J][1] = hsub(X[J][1], E[J][1]); }
        stream<(SO / 3) % 3>(Yo, A, G);
        return;
    }
    stream<SO % 3>(Ye, Bq, F);
#pragma unroll
    for (int J = 0; J < 8; J++) { G[J][0] = hsub(X[J][0], E[J][0]); G[J][1] = hsub(X[J][1], E[J][1]); }
    if (DV & 4) FENCE();
#pragma unroll
    for (int jp = 0; jp < 4; jp++) ldsm4(ua + 2 * U_PL + jp * 256 - 16, X[2 * jp][0], X[2 * jp][1], X[2 * jp + 1][0], X[2 * jp + 1][1]);
#pragma unroll
    for (int h = 0; h < 2; h++) { Bq[h][1] = lds32(ta + 1024 * h + 96); Bq[h][3] = lds32(ta + 1024 * h + 128); Bq[h][0] = A[h][3] ^ zr; Bq[h][2] = Bq[h][1] ^ zr; }
    stream<(SO / 3) % 3>(Yo, A, G);
#pragma unroll
    for (int h = 0; h < 2; h++)
#pragma unroll
        for (int i = 0; i < 4; i++) S[h][i] = hadd(A[h][i], Bq[h][i]);
    if (DV & 16) FENCE();
    stream<(SO / 9) % 3>(M, S, E);
#pragma unroll
    for (int J = 0; J < 8; J++) { F[J][0] = hsub(X[J][0], E[J][0]); F[J][1] = hsub(X[J][1], E[J][1]); }
}

__device__ __forceinline__ void group_tables(uint32_t TB, int lane) {
    const int g = lane >> 2, t = lane & 3;
    const int g2 = t < 2 ? g - 1 : g;
    const uint32_t o2 = T_R2 + T2_S * (g2 & 3) + 8 * (8 * (t | 2) - 10 + (g2 >> 2)) + (t < 2 ? 4 : 0), sh = (t & 2) * 8;
    const uint32_t o3 = T_R3 + T3_S * (((g - 1) >> 1) & 1) + 8 * (7 + 4 * t + ((g - 1) >> 2)) + 4 * ((g - 1) & 1);
    const uint32_t o4 = 10 * (lane & 1) + ((uint32_t)(((uint64_t)(T_R3 + T3_S + 308) << 48 | (uint64_t)(T_R2 + 180) << 32 | (T_R2 + 176) << 16 | (T_R2 + 3 * T2_S + 172)) >> (8 * (lane & 6))) & 0xffffu);
#pragma unroll 1
    for (int n = 0; n < 2; n++, TB += 4 * T_CH) {
        const uint4 b4 = lds128(TB + T_R2 + 16 * (lane | 2)), c4 = lds128(TB + T_R2 + 512 + 16 * lane);
        uint32_t vb[4] = {b4.x >> sh, b4.y >> sh, b4.z >> sh, b4.w >> sh}, vc[2] = {c4.x, c4.y};
        const uint32_t k1024 = __shfl_sync(0xffffffffu, vc[0], 0) & 0xffffu;
        uint32_t kl = hadd(c4.z, __byte_perm(c4.z, 0, 0x1032));
        kl = hadd(kl, __shfl_xor_sync(0xffffffffu, kl, 1)); kl = hadd(kl, __shfl_xor_sync(0xffffffffu, kl, 2));
#pragma unroll
        for (int i = 0; i < 3; i++) sts128(TB + T_R2 + 16 * lane + 512 * i, 0, 0, 0, 0);
        if (lane == 0) { vb[0] = 0; vc[0] &= 0xffff0000u; }
        if (lane == 4) vc[0] = hsub(vc[0], k1024);
        __syncwarp();
#pragma unroll
        for (int i = 0; i < 4; i++) { sts16(TB + o2 + 16 * i, vb[i]); sts16(TB + o2 + 16 * i + 10, vb[i]); }
#pragma unroll
        for (int i = 0; i < 2; i++) {
            sts16(TB + o3 + 16 * i, vc[i]); sts16(TB + o3 + 16 * i + 10, vc[i]);
            sts16(TB + o3 + 16 * i + 128, vc[i] >> 16); sts16(TB + o3 + 16 * i + 138, vc[i] >> 16);
        }
        sts16(TB + o4, (lane & 7) < 6 ? k1024 : kl);
    }
}

struct Chunks { uint32_t c3, c2, c1, c0, cm1, cm2, cm3, cm4, d2, d1, d0, dm1, em2, em3; };
__device__ __forceinline__ void convolve(uint32_t sb, int h, uint32_t zr, int pr, int wuni, bf16* out, const CUtensorMap* tm_o DBG_PARAMS) {
    const uint32_t bars = sb + M_BARS;
    uint32_t M[8][2], Ye[8][2], Yo[8][2], F[8][2], Bq[2][4];
    {
        LANE_VARS;
        uint32_t X[8][2];
        uint32_t ua = UB + ((mi & 1) ? 0 : U_PL) + (8 + 8 * (mi >> 1) + r) * 16, ta = TB + 4 * (1 + g + 2 * t);
        uint32_t A[3][4], S[2][4];
        __syncwarp();
#pragma unroll
        for (int h2 = 0; h2 < 3; h2++) { A[h2][0] = lds32(ta + 1024 * h2); A[h2][1] = lds32(ta + 1024 * h2 + 32); A[h2][3] = lds32(ta + 1024 * h2 + 64); A[h2][2] = A[h2][1] ^ zr; }
#pragma unroll
        for (int h2 = 0; h2 < 2; h2++) {
            Bq[h2][1] = lds32(ta + 1024 * h2 + 96); Bq[h2][3] = lds32(ta + 1024 * h2 + 128); Bq[h2][0] = A[h2][3] ^ zr; Bq[h2][2] = Bq[h2][1] ^ zr;
#pragma unroll
            for (int i = 0; i < 4; i++) S[h2][i] = hadd(A[h2][i], Bq[h2][i]);
        }
        const uint32_t an = A[0][0] ^ zr, un = UB + (9 + lane) * 16;
        if (lead) TSTAMP(10);
        mbar_spin(bars + 8 * B_U);
        if (lead) { TSTAMP(3); CSTAMP(27); }
        uint32_t E[8][2], N[8], G[8][2];
#pragma unroll
        for (int jp = 0; jp < 4; jp++) ldsm4(ua + jp * 256, E[2 * jp][0], E[2 * jp][1], E[2 * jp + 1][0], E[2 * jp + 1][1]);
#pragma unroll
        for (int jp = 0; jp < 4; jp++) ldsm4(ua + 2 * U_PL + jp * 256, X[2 * jp][0], X[2 * jp][1], X[2 * jp + 1][0], X[2 * jp + 1][1]);
        ldsm4(un, N[0], N[1], N[2], N[3]); ldsm4(un + 512, N[4], N[5], N[6], N[7]);
#pragma unroll
        for (int J = 0; J < 8; J++) mma_h_z(M[J][0], M[J][1], S[0], E[J][0], E[J][1]);
#pragma unroll
        for (int J = 1; J < 8; J++) mma_h(M[J], S[1], E[J - 1][0], E[J - 1][1]);
#pragma unroll
        for (int J = 2; J < 8; J++) mma_h(M[J], A[2], E[J - 2][0], E[J - 2][1]);
        if (FENCES & 32) FENCE();
#pragma unroll
        for (int J = 0; J < 8; J++) mma_h_k8_z(Ye[J], zr, an, X[J][1]);
#pragma unroll
        for (int J = 0; J < 8; J++) mma_h_k8_z(Yo[J], zr, an, N[J]);
#pragma unroll
        for (int J = 0; J < 8; J++) { G[J][0] = hsub(X[J][0], E[J][0]); G[J][1] = hsub(X[J][1], E[J][1]); }
#pragma unroll
        for (int jp = 0; jp < 4; jp++) ldsm4(ua + 2 * U_PL + jp * 256 - 16, X[2 * jp][0], X[2 * jp][1], X[2 * jp + 1][0], X[2 * jp + 1][1]);
#pragma unroll
        for (int J = 0; J < 8; J++) mma_h(Yo[J], A[0], G[J][0], G[J][1]);
#pragma unroll
        for (int J = 1; J < 8; J++) mma_h(Yo[J], A[1], G[J - 1][0], G[J - 1][1]);
#pragma unroll
        for (int J = 2; J < 8; J++) mma_h(Yo[J], A[2], G[J - 2][0], G[J - 2][1]);
#pragma unroll
        for (int J = 0; J < 8; J++) { F[J][0] = hsub(X[J][0], E[J][0]); F[J][1] = hsub(X[J][1], E[J][1]); }
#pragma unroll kDenseUnroll
        for (int k = 1; k < 8; k++) {
            ua -= 16; ta += 128;
            dense_step(M, Ye, Yo, X, F, Bq, ua, ta, zr);
        }
    }
    mbar_wait_n<2, 8>(bars + 8 * B_TD);
    LANE_VARS;
    if (lead) { TSTAMP(4); CSTAMP(28); }
    __syncwarp();
    const uint32_t ys = lds32(sb + M_SC + 8 + warp * 4), idh = (g == 2 * t) ? ys : (g == 2 * t + 1) ? ys << 16 : 0u;
    const uint32_t sbr = mapa(sb, h ^ 1);
    const uint32_t yl = TB + lane * 16, yr = sbr + (h ? ALT0 : ALT1) + A_YIN + warp * Y_CH + lane * 16;
    uint32_t ea[4];
    auto finish = [&](int J) {
        float m[4], e[4], o[4];
        widen_h(m, M[J], idh); widen_add_h(e, Ye[J], idh, m); widen_add_h(o, Yo[J], idh, m);
        const uint32_t y[4] = {pack_bf(e[0], e[2]), pack_bf(o[0], o[2]), pack_bf(e[1], e[3]), pack_bf(o[1], o[3])};
        if (!(J & 1)) {
#pragma unroll
            for (int i = 0; i < 4; i++) ea[i] = y[i];
        } else {
            st_async16(yr + (J >> 1) * 512, h ? ea[0] : y[0], h ? ea[1] : y[1], h ? ea[2] : y[2], h ? ea[3] : y[3], sbr + M_BARS + 8 * (B_Y + (J >> 1)));
            sts128(yl + (J >> 1) * 512, h ? y[0] : ea[0], h ? y[1] : ea[1], h ? y[2] : ea[2], h ? y[3] : ea[3]);
            __syncwarp();
            if (lane == 0) mbar_arrive(bars + 8 * (B_Y + (J >> 1)));
        }
    };
    const uint32_t a1 = UB + (3 - mi) * U_PL + (8 + r) * 16;
    const uint32_t a2 = UB + ((2 - mi) & 3) * U_PL + (8 + r - (mi == 3)) * 16;
    const uint32_t a3 = UB + (2 - (mi & 1)) * U_PL + (7 + r) * 16;
    const uint32_t bt = sb + OFF_BAND + 4 * (32 + g + 2 * t);
    auto load3 = [&](Chunks& u, int j) { ldsm4(a2 + j * 128, u.d2, u.d1, u.d0, u.dm1); ldsm4(a1 + j * 128, u.c3, u.c2, u.c1, u.c0); ldsm2(a3 + j * 128, u.em2, u.em3); };
    auto load2 = [&](Chunks& u, int j) {
        if (DUP_MOV == 0) load3(u, j);
        else { ldsm4(a1 + j * 128, u.c3, u.c2, u.c1, u.c0); if (DUP_MOV == 1) ldsm4(a2 + j * 128, u.d2, u.d1, u.d0, u.dm1); }
        ldsm4(a1 + j * 128 - 16, u.cm1, u.cm2, u.cm3, u.cm4);
        if (DUP_MOV >= 1) { u.em2 = u.cm2 ^ zr; u.em3 = u.cm3 ^ zr; }
        if (DUP_MOV >= 2) { u.d2 = u.c2 ^ zr; u.d1 = u.c1 ^ zr; u.d0 = u.c0 ^ zr; u.dm1 = u.cm1 ^ zr; }
    };
    Chunks u;
    uint32_t B35[4];
    uint2 Q[4][3], QS[2][3];
    {
        const uint32_t f7 = lds32(bt + 768 - 36), g7 = lds32(bt + 768 - 4), f9 = lds32(bt + 1024 - 32), g9 = lds32(bt + 1024), h9 = lds32(bt + 1024 + 32);
        const uint32_t f1 = hmul(lds32(bt - 28), lds16(TB + T_R2 + 176) * 0x10001u);
        load3(u, 0);
        const uint32_t tq = TB + T_R3 + 8 * (7 + g - 2 * t);
        uint2 Q0[4], Q1[4], Q2[4];
#pragma unroll
        for (int i = 0; i < 4; i++) { Q0[i] = lds64(tq + 64 * i); Q1[i] = lds64(tq + T3_S + 64 * i); Q2[i] = lds64(tq + T3_S - 8 + 64 * i); }
#pragma unroll
        for (int J = 0; J < 8; J++) mma_h(Ye[J], Bq[0], F[J][0], F[J][1]);
#pragma unroll
        for (int J = 1; J < 8; J++) mma_h(Ye[J], Bq[1], F[J - 1][0], F[J - 1][1]);
        const uint32_t B7[4] = {zr, f7, f7 ^ zr, g7}, B9a[4] = {zr + zr, f9, f9 ^ zr, g9}, B9b[4] = {g9 ^ zr, h9, h9 ^ zr, zr * 3}, B1[4] = {zr * 5, f1, f1 ^ zr, zr * 7};
        const uint32_t g7b = g7 ^ zr, z7 = zr * 9;
        if (FENCES & 1) FENCE();
        uint32_t WE[2][4], WO[2][4];
#pragma unroll
        for (int j = 0; j < 5; j++) {
            uint32_t (&we)[4] = WE[j & 1], (&wo)[4] = WO[j & 1], (&pe)[4] = WE[~j & 1], (&po)[4] = WO[~j & 1];
            if (j == 3) {
                const uint32_t t2 = TB + T_R2 + 8 * (6 + g - 2 * t);
                B35[0] = lds32(bt + 256 - 28); B35[1] = lds32(bt + 512 - 40); B35[2] = lds32(bt + 256 + 4); B35[3] = lds32(bt + 512 - 8);
#pragma unroll
                for (int i = 0; i < 3; i++)
#pragma unroll
                    for (int s = 0; s < 4; s++) Q[s][i] = lds64(t2 + T2_S * s + 64 * i);
            }
            if (j < 4) {
                mma_h_z(we[2], we[3], B9a, u.d0, u.dm1); mma_h_z(wo[2], wo[3], B9a, u.d2, u.d1);
                mma_h_z(we[0], we[1], B7, u.c1, u.c0); mma_h_z(wo[0], wo[1], B7, u.c3, u.c2);
            }
            if (j == 0) { finish(0); finish(1); }
#pragma unroll
            for (int i = 0; i < 5 - j && j > 0; i++) { mma_h(Ye[j + 3 + i], pe, Q0[i].x, Q0[i].y); mma_h(Yo[j + 3 + i], pe, Q1[i].x, Q1[i].y); }
            if (j < 4) {
                mma_h2(we[2], we[3], B9b, u.em2, u.em3); mma_h2(wo[2], wo[3], B9b, u.d0, u.dm1);
                mma_h_k8(we[0], we[1], g7b, z7, u.dm1); mma_h_k8(wo[0], wo[1], g7b, z7, u.c1);
                mma_h(Ye[j + 4], B1, u.d0, u.dm1); mma_h(Yo[j + 4], B1, u.d2, u.d1);
                if (j < 3) load3(u, j + 1); else load2(u, 0);
            }
#pragma unroll
            for (int i = 0; i < 5 - j && j > 0; i++) { mma_h(Ye[j + 3 + i], po, Q2[i].x, Q2[i].y); mma_h(Yo[j + 3 + i], po, Q0[i].x, Q0[i].y); }
            if (j == 3) {
#pragma unroll
                for (int i = 0; i < 3; i++)
#pragma unroll
                    for (int s = 0; s < 2; s++) { QS[s][i].x = hadd(Q[s][i].x, Q[s + 2][i].x); QS[s][i].y = hadd(Q[s][i].y, Q[s + 2][i].y); }
            }
            if (j < 3 ? ((FENCES & 2) || (j == 2 && (FENCES & 4))) : (j == 4 && (FENCES & 8))) FENCE();
        }
    }
    uint32_t xo, go, ya, sel, any, wu, oo, gs;
    auto mix_setup = [&]() {
        LANE_VARS;
        const int pos = 2 * (warp & 3) + (t >> 1);
        xo = sb + OFF_S + h * 32768 + (warp & 3) * 2048 + (warp >> 2) * 1024 + (g >> 1) * 128 + (t >> 1) * 64 + (g & 1) * 32 + (((t ^ (g >> 1)) & 1) << 4);
        go = sb + OFF_GP + (8 * pos + g) * 64 + ((warp >> 2) ^ (g >> 1) ^ (2 * (t & 2))) * 8;
        const int ch = 2 * mi + (r & 1);
        ya = sb + ((((r >> 1) & 1) == h) ? OFF_TAB + ch * T_CH : (h ? ALT1 : ALT0) + A_YIN + ch * Y_CH) + (8 * (warp & 3) + (r & 4) + 2 * (warp >> 2)) * 16;
        gs = lds32(sb + M_SC + 4 * (t & 1));
        sel = lds16(sb + M_BMAP + (8 * warp + g) * 2);
        any = __reduce_or_sync(0xffffffffu, sel);
        sel >>= t >> 1;
        oo = (128 * (warp >> 2) + 8 * g + pos) * D_ + 8 * (t & 1);
        wu = UNI_WARP ? wuni : __shfl_sync(0xffffffffu, warp, 0);
    };
    struct MixIn { uint32_t gp[2]; uint4 e[2]; };
    auto mix_load = [&](MixIn& q, int J) {
        const uint2 g2 = lds64(go ^ (16 * J));
        q.gp[0] = hmul2_bf(g2.x, gs); q.gp[1] = hmul2_bf(g2.y, gs);
#pragma unroll
        for (int k = 0; k < 2; k++) {
            const uint4 x = lds128(xo + J * 8192 + k * 512);
            q.e[k] = make_uint4(hi_mul_bf(q.gp[k], x.x), hi_mul_bf(q.gp[k], x.y), hi_mul_bf(q.gp[k], x.z), hi_mul_bf(q.gp[k], x.w));
        }
    };
    auto mix_calc = [&](MixIn& q, int J) {
#pragma unroll
        for (int k = 0; k < 2; k++) {
            uint32_t y[4];
            ldsm4t(ya + J * 512 + k * 16, y[0], y[1], y[2], y[3]);
            q.e[k] = make_uint4(lo_fma_bf(q.gp[k], y[0], q.e[k].x), lo_fma_bf(q.gp[k], y[1], q.e[k].y), lo_fma_bf(q.gp[k], y[2], q.e[k].z), lo_fma_bf(q.gp[k], y[3], q.e[k].w));
            if (J < 2) sts128_if(!((sel >> (4 * J + 2 * k)) & 1u), xo + J * 8192 + k * 512, q.e[k].x, q.e[k].y, q.e[k].z, q.e[k].w);
        }
    };
    auto mix_send = [&](const MixIn& q, int J) {
        if (J >= STG_FROM || (J >= 2 && ((any >> (4 * J)) & 15u))) {
#pragma unroll
            for (int k = 0; k < 2; k++) if (!((sel >> (4 * J + 2 * k)) & 1u)) *(uint4*)(out + (size_t)(512 * J + 256 * h + 64 * k) * D_ + 16 * pr + oo) = q.e[k];
        } else {
#pragma unroll
            for (int k = 0; k < 2 && J >= 2; k++) sts128(xo + J * 8192 + k * 512, q.e[k].x, q.e[k].y, q.e[k].z, q.e[k].w);
            asm volatile("fence.proxy.async.shared::cta;" ::: "memory");
            __syncwarp();
            asm volatile("{ .reg .pred p; elect.sync _|p, 0xffffffff;\n\t@p cp.async.bulk.tensor.5d.global.shared::cta.bulk_group [%0, {%2, %3, %3, %4, %5}], [%1]; }"
                         :: "l"(tm_o), "r"(sb + OFF_S + h * 32768 + J * 8192 + (wu & 3) * 2048 + (wu >> 2) * 1024),
                            "r"(16 * pr), "r"(0), "r"(32 * J + 16 * h + 8 * (wu >> 2)), "r"(wu & 3) : "memory");
        }
    };
    MixIn q, q2, q3;
    const uint32_t zq = zr + zr;
#pragma unroll
    for (int j = 0; j < 6; j++) {
        if (j == SEND0_AT) mix_send(q, 0);
        if (j == SEND1_AT) mix_send(q, 1);
        if (j == MIX0_AT) mbar_wait_n<2, 8 * (B_Y - B_G)>(bars + 8 * B_G);
        else if (j == MIX1_AT) mbar_spin(bars + 8 * (B_Y + 1));
        else if (j > 0 && (FENCES & 16)) FENCE();
        uint32_t H[7][2];
        mma_h_z(H[3][0], H[3][1], B35, u.d0, u.dm1); mma_h_z(H[4][0], H[4][1], B35, u.c1, u.c0);
        mma_h_z(H[5][0], H[5][1], B35, u.d2, u.d1); mma_h_z(H[6][0], H[6][1], B35, u.c3, u.c2);
        mma_h_z(H[2][0], H[2][1], B35, u.cm1, u.cm2); mma_h_z(H[1][0], H[1][1], B35, u.em2, u.em3); mma_h_z(H[0][0], H[0][1], B35, u.cm3, u.cm4);
        if (j < 5) load2(u, j + 1);
        if (j > 0) finish(j + 1);
        if (j == MIX0_AT) { mix_setup(); mix_load(q, 0); mix_calc(q, 0); }
        if (j == MIX1_AT) { mix_load(q, 1); mix_calc(q, 1); }
        if (j == 5) { mix_load(q2, 2); mix_load(q3, 3); }
        const int n = j < 4 ? 3 : 6 - j;
#pragma unroll
        for (int s = 0; s < 2; s++) {
            const int o = 3 - s;
            const uint32_t qe[4] = {H[o][0] ^ zr, H[o + 1][0] ^ zq, H[o][1] ^ zr, H[o + 1][1] ^ zq};
            const uint32_t qg[4] = {hsub(H[o + 2][0], H[o][0]), hsub2(H[o + 3][0], H[o + 1][0]), hsub(H[o + 2][1], H[o][1]), hsub2(H[o + 3][1], H[o + 1][1])};
            const uint32_t qf[4] = {hsub(H[o - 2][0], H[o][0]), hsub2(H[o - 1][0], H[o + 1][0]), hsub(H[o - 2][1], H[o][1]), hsub2(H[o - 1][1], H[o + 1][1])};
#pragma unroll
            for (int i = 0; i < n; i++) mma_h(M[j + 2 + i], qe, QS[s][i].x, QS[s][i].y);
#pragma unroll
            for (int i = 0; i < n; i++) mma_h(Yo[j + 2 + i], qg, Q[s][i].x, Q[s][i].y);
#pragma unroll
            for (int i = 0; i < n; i++) mma_h(Ye[j + 2 + i], qf, Q[s + 2][i].x, Q[s + 2][i].y);
        }
    }
    finish(7);
    if (lead) { TSTAMP(5); CSTAMP(29); }
    if (SEND0_AT == 6) mix_send(q, 0);
    if (SEND1_AT == 6) mix_send(q, 1);
    mbar_spin(bars + 8 * (B_Y + 2));
    asm volatile("cp.async.bulk.commit_group;" ::: "memory");
    mix_calc(q2, 2);
    mix_send(q2, 2);
    asm volatile("cp.async.bulk.wait_group 0;" ::: "memory");
    __syncwarp();
    if (lane == 0) mbar_arrive(bars + 8 * B_SD);
    mbar_spin(bars + 8 * (B_Y + 3));
    if (lead) TSTAMP(6);
    mix_calc(q3, 3);
    mix_send(q3, 3);
    asm volatile("cp.async.bulk.commit_group;" ::: "memory");
    asm volatile("cp.async.bulk.wait_group.read 0;" ::: "memory");
}

__global__ void __cluster_dims__(2, 1, 1) __launch_bounds__(NTHREADS, 1)
fused_kernel(const Params p, const __grid_constant__ CUtensorMap tm_gu, const __grid_constant__ CUtensorMap tm_down, const __grid_constant__ CUtensorMap tm_x,
             const __grid_constant__ CUtensorMap tm_r, const __grid_constant__ CUtensorMap tm_o) {
    extern __shared__ __align__(1024) unsigned char smem[];
    const uint32_t sb = __shfl_sync(0xffffffffu, smem_u32(smem), 0);
    int tid;
    asm volatile("mov.u32 %0, %%tid.x;" : "=r"(tid));
    const int pw = tid >> 5, lane = tid & 31;
    const int kc = ((blockIdx.x >> 1) + 60) & 63, lo = kc < 32, hi = kc >= 60, kq = lo ? kc >> 3 : ((kc - 32) * 37) >> 8;
    const int h = blockIdx.x & 1;
    const int pr = (hi ? 1 : 4) * kc - (lo ? 31 : hi ? 0 : 27) * kq - ((lo | hi) ? 0 : 96);
    const int c = 2 * pr + h;
    const int fb = FB_BLK ? (int)blockIdx.x : c;
    const uint32_t bars = sb + M_BARS;

    uint2 v_la, v_ai, v_cr, v_ci;
    uint32_t ldt16, dsk16;
    {
        const uint32_t ch = 8 * c + pw - MAIN_W0, po = ch * 128 + 4 * lane;
        asm volatile("{ .reg .pred q; setp.ge.u32 q, %16, 8; @q bra.uni L%=;\n\t"
                     "ld.global.nc.v2.u32 {%0,%1}, [%10];\n\tld.global.nc.v2.u32 {%2,%3}, [%11];\n\tld.global.nc.u16 %8, [%14];\n\t"
                     "ld.global.nc.v2.u32 {%4,%5}, [%12];\n\tld.global.nc.v2.u32 {%6,%7}, [%13];\n\tld.global.nc.u16 %9, [%15];\nL%=:\n\t}"
                     : "=r"(v_la.x), "=r"(v_la.y), "=r"(v_ai.x), "=r"(v_ai.y), "=r"(v_cr.x), "=r"(v_cr.y), "=r"(v_ci.x), "=r"(v_ci.y), "=r"(ldt16), "=r"(dsk16)
                     : "l"(p.logA + po), "l"(p.Aim + po), "l"(p.Cre + po), "l"(p.Cim + po), "l"(p.logdt + ch), "l"(p.Dskip + ch), "r"(pw - MAIN_W0));
    }

    if (blockIdx.x >= 128) {
        if (blockIdx.x != 128) return;
        const unsigned tag = (ld_epoch(p.ex) + 1) & 0xffffu;
        const uint32_t idx0 = 2047 - (512 * (tid & 3) + (tid >> 3) + 256 * ((tid >> 2) & 1));
        const uint32_t list = sb + 128;
#pragma unroll 1
        for (int pass = 0; pass < 2; pass++) {
            if (tid == 0) sts32(sb + 64, 0);
            sts128(list + 16 * tid, 0, 0, 0, 0);
            uint4 a = make_uint4(lane == 0 ? 0x10000u : 0u, 0, 0, 0);
            bool ok = pass == 0;
#pragma unroll 1
            for (int it = 0; it < (1 << 22) && !ok; it++) {
                a = ld_gpu128(&p.ex->r[tid]);
                ok = (((a.x ^ tag) | (a.y ^ tag) | (a.z ^ tag) | (a.w ^ tag)) & 0xffffu) == 0;
            }
            if (!ok) __trap();
            const uint32_t key[4] = {(a.x & 0xffff0000u) | idx0, (a.y & 0xffff0000u) | (idx0 - 64), (a.z & 0xffff0000u) | (idx0 - 128), (a.w & 0xffff0000u) | (idx0 - 192)};
            const uint32_t wm = __reduce_max_sync(0xffffffffu, max(max(key[0], key[1]), max(key[2], key[3])));
            if (lane == 0) sts32(sb + pw * 4, wm);
            __syncthreads();
            const uint2 q = lds64(sb + 8 * (lane & 7));
            const uint32_t thr = __reduce_min_sync(0xffffffffu, max(q.x, q.y));
            if (tid == 0) TSTAMP(0);
            const uint32_t n = (key[0] >= thr) + (key[1] >= thr) + (key[2] >= thr) + (key[3] >= thr);
            if (n) {
                uint32_t pos;
                asm volatile("atom.shared.add.u32 %0, [%1], %2;" : "=r"(pos) : "r"(sb + 64), "r"(n) : "memory");
#pragma unroll
                for (int i = 0; i < 4; i++) if (key[i] >= thr) { sts32(list + 4 * pos, key[i]); pos++; }
            }
            __syncthreads();
            const int ncand = (int)lds32(sb + 64);
            const uint2 l0 = lds64(list + 8 * lane);
#pragma unroll 1
            for (int j = pw; j < ncand; j += 16) {
                const uint32_t mine = lds32(list + 4 * j);
                int rank = __popc(__ballot_sync(0xffffffffu, l0.x > mine)) + __popc(__ballot_sync(0xffffffffu, l0.y > mine));
#pragma unroll 1
                for (int i = 64; i < ncand; i += 32) rank += __popc(__ballot_sync(0xffffffffu, lds32(list + 4 * (i + lane)) > mine));
                if (rank < 8 && lane == 0) asm volatile("st.relaxed.gpu.global.v2.u32 [%0], {%1, %2};" :: "l"(&p.ex->top[rank]), "r"(mine), "r"(pass ? tag : tag ^ 0x8000u) : "memory");
            }
            if (tid == 0) TSTAMP(1);
            __syncthreads();
        }
        if (tid == 0) TSDUMP(3u);
        return;
    }

    if (pw != 12) asm volatile("barrier.cluster.arrive.relaxed.aligned;" ::: "memory");

    if (pw >= MAIN_W0 && pw < MAIN_W0 + 8) {
        [[maybe_unused]] const int wuni = __shfl_sync(0xffffffffu, pw - MAIN_W0, 0);
        const int warp = UNI_WARP ? wuni : pw - MAIN_W0;
        [[maybe_unused]] const bool lead = (tid == 32 * MAIN_W0);
        asm volatile("setmaxnreg.inc.sync.aligned.u32 " MAIN_REGS ";");
        cluster_next();
        [[maybe_unused]] const int d = 8 * c + warp;
        const int g = lane >> 2, t = lane & 3, mi = lane >> 3, r = lane & 7;
        const uint32_t TB = sb + OFF_TAB + warp * T_CH;
        const uint32_t UB = sb + OFF_U + warp * U_CH;
        const uint32_t zr = ZR;

        uint32_t Ra[2][2], Rb[2][2], Rc[2], Rl[2];
        int esum;
        {
            const float dt = bf_round(exp_acc(__uint_as_float(ldt16 << 16)));
            const uint32_t ec = max(warp_max16(amax2_bf(amax2_bf(v_cr.x, v_cr.y), amax2_bf(v_ci.x, v_ci.y))) >> 7, 6u);
            const float cf = __uint_as_float((__float_as_uint(dt) & 0x7fffffu) | ((260u - ec) << 23));
            esum = (int)ec + (int)(__float_as_uint(dt) >> 23) - 274;
            kernel_gen(v_la, v_ai, v_cr, v_ci, dt, cf, TB, UB, bars + 8 * B_KD, lane, zr, Ra, Rb, Rc, Rl);
        }
        if (lead) TSTAMP(2);

        {
            uint32_t mk = amax2_h(amax2_h(amax2_h(Ra[0][0], Ra[0][1]), amax2_h(Ra[1][0], Ra[1][1])), amax2_h(amax2_h(Rb[0][0], Rb[0][1]), amax2_h(Rb[1][0], Rb[1][1])));
            mk = amax2_h(amax2_h(mk, hmul(Rl[0], 0x34003400u)), amax2_h(Rc[0], Rc[1]));
            const int eb = (dsk16 >> 7) & 0xff, ek = max((int)(warp_max16(mk) >> 10), eb ? eb - 127 - esum : 0), en = eb - esum - 3 - ek;
            const float ds = (lane == 0 && eb && en > 0) ? __uint_as_float(((dsk16 & 0x807fu) << 16) | (en << 23)) : 0.f;
            const float fs = __uint_as_float(max(139 - ek, 1) << 23);
            const uint32_t ks = pack_h(fs, fs);
            uint32_t va[4], vb[4];
#pragma unroll
            for (int i = 0; i < 4; i++) { va[i] = hmul(Ra[i >> 1][i & 1], ks); vb[i] = hmul(Rb[i >> 1][i & 1], ks); }
            va[0] = hadd(va[0], pack_h(ds, 0.f));
            const uint32_t k512 = __shfl_sync(0xffffffffu, vb[0], 2) & 0xffffu, k255 = __shfl_sync(0xffffffffu, va[3], 31);
#pragma unroll
            for (int i = 0; i < 4; i++) {
                const uint32_t pv = __shfl_sync(0xffffffffu, lane == 31 ? (i ? va[i - 1] : 0u) : va[i], lane - 1);
                sts64(TB + 48 + 256 * i + 8 * lane, __byte_perm(pv, va[i], 0x5432), va[i]);
            }
#pragma unroll
            for (int i = 0; i < 4; i++) {
                const uint32_t nx = __shfl_sync(0xffffffffu, lane == 0 ? (i < 3 ? vb[i + (i < 3)] : k512) : vb[i], lane + 1 + 2 * (lane & 1));
                const uint32_t aa = __byte_perm(vb[i], 0, 0x1010);
                sts128_if(t < 2, TB + 1072 + 256 * i + 32 * g + 16 * t, (i == 0 && lane == 0) ? __byte_perm(k255, aa, 0x5432) : aa ^ zr, aa, vb[i] ^ zr, __byte_perm(vb[i], nx, 0x5432));
            }
            const uint32_t k0 = lane == 3 ? k512 : 0u, kk = k0 * 0x10001u;
            sts128_if(lane < 8, TB + 16 * lane + (lane < 3 ? 0 : 2048), kk, kk ^ zr, kk + zr, k0);
            sts128(TB + T_R2 + 16 * lane, vb[0], vb[1], vb[2], vb[3]);
            esum += (int)ek;
            sts128(TB + T_R2 + 512 + 16 * lane, hmul(Rc[0], ks), hmul(Rc[1], ks), hmul(Rl[0], ks), zr);
            if (lane == 0) sts32(TB + T_ES, (uint32_t)esum);
            __syncwarp();
            if (lane == 0) mbar_arrive(bars + 8 * B_TS);
        }
        if (lead) TSTAMP(11);

        convolve(sb, h, zr, pr, wuni, p.out, &tm_o DBG_ARGS);
        { LANE_VARS; if (lead) { TSTAMP(7); TSDUMP(0x3c000cffu); } }
    } else if (pw < 4) {
        const int v = UNI_V ? __shfl_sync(0xffffffffu, pw, 0) : pw, at = tid;
        const int g = lane >> 2, t = lane & 3, mi = lane >> 3, r = lane & 7;
        const uint32_t dalt = (h ? ALT1 : ALT0) + A_SLOT - ALT_SLOT * 8192;
        cp16(sb + OFF_GP + tid * 16, p.wr + tid * 8);
        cp16(sb + OFF_GP + 2048 + tid * 16, p.gatew + tid * 8);
        const unsigned epoch = ld_epoch(p.ex);
        if (tid == 0) sts128(sb + OFF_S - 16, 0, 0, 0, 0);
        const unsigned tag = (epoch + 1) & 0xffffu;
        const int ftok = 2 * ((at >> 2) & 3) + (at & 1), fch = (at >> 4) + 8 * ((at >> 1) & 1);
        uint32_t eu;
        {
            cluster_next();
            cp_wait_all();
            bar_sync(1, 128);
            const uint32_t wo = sb + OFF_GP + 512 * v + 64 * ((g >> 1) & 1) + 16 * t + 4 * (g & 1);
            uint32_t w0[4], w1[4];
#pragma unroll
            for (int cb = 0; cb < 4; cb++) { w0[cb] = lds32(wo + 128 * cb); w1[cb] = lds32(wo + 128 * cb + 8); }
            const uint32_t go = sb + OFF_GP + 2048 + 512 * v + 64 * (g & 1) + 16 * t;
            const uint32_t ro = sb + M_RG + (g >> 1) * 32 + (2 * v + (g & 1)) * 4;
            const uint32_t xo = sb + OFF_XROW + (g >> 1) * 2048 + 512 * v + 64 * (g & 1) + 16 * t;
            const uint32_t one0 = 0x3F803F80u ^ p.zero, one1 = 0x3F803F80u + p.zero;
            auto row_sum = [&](uint32_t a) {
                const uint4 x = lds128(a), y = lds128(a + 16);
                return ((__uint_as_float(x.x) + __uint_as_float(x.y)) + (__uint_as_float(x.z) + __uint_as_float(x.w)))
                     + ((__uint_as_float(y.x) + __uint_as_float(y.y)) + (__uint_as_float(y.z) + __uint_as_float(y.w)));
            };
            const int dl = 8 * (r >> 1) + 4 - 2 * mi - (r & 1);
            const uint32_t so = sb + OFF_S + (v >> 1) * 32768 + (dl & 6) * 1024 + (8 * (v & 1) + (dl >> 4)) * 128 + (dl & 1) * 64 + (dl & 8) * 4 + ((dl & 16) ^ (h << 4));
            const uint32_t so2 = so + (dl >= 0 ? 0 : v == 2 ? -30720 : v == 0 ? 26624 : 0), so1 = (dl < 0 && v == 0) ? sb + OFF_S - 16 : so2;
            auto src = [&](int k) { return (k == 0 ? so1 : (k & 3) == 0 ? so2 : so) + (k >> 2) * 8192 + (k & 3) * 256; };
            uint32_t xr[16][4], mx = 0, idb = 0;
            auto slice = [&](int k) { ldsm4t(src(k), xr[k][0], xr[k][1], xr[k][2], xr[k][3]); };
            auto to_half = [&](uint32_t (&q)[4]) {
                float f0[4], f1[4];
                widen_bf(f0, q[0], q[1], idb); widen_bf(f1, q[2], q[3], idb);
                q[0] = pack_h(f0[0], f0[1]); q[1] = pack_h(f0[2], f0[3]); q[2] = pack_h(f1[0], f1[1]); q[3] = pack_h(f1[2], f1[3]);
            };
            auto track = [&](int k) { mx = amax2_bf(amax2_bf(mx, amax2_bf(xr[k][0], xr[k][1])), amax2_bf(xr[k][2], xr[k][3])); };
            auto cta_exp = [&]() {
                const uint32_t wm = warp_max16(mx);
                if (lane == 0) sts32(sb + M_MX + v * 4, wm);
                bar_sync(1, 128);
                const uint4 m4 = lds128(sb + M_MX);
                return max(max(m4.x, m4.y), max(m4.z, m4.w)) >> 7;
            };
            auto set_scale = [&]() { const uint32_t sc = (257u - eu) << 7; idb = (g == 2 * t) ? sc : (g == 2 * t + 1) ? sc << 16 : 0u; };
            uint4 x[4], gw[4];
#pragma unroll
            for (int cb = 0; cb < 4; cb++) gw[cb] = lds128(go + 128 * cb);
            auto gate = [&](int i) {
                float e0[4] = {0.f, 0.f, 0.f, 0.f}, e1[4] = {0.f, 0.f, 0.f, 0.f};
#pragma unroll
                for (int cb = 0; cb < 4; cb++)
                    mma_bf((cb & 1) ? e1 : e0, hmul2_bf(x[cb].x, gw[cb].x), hmul2_bf(x[cb].y, gw[cb].y), hmul2_bf(x[cb].z, gw[cb].z), hmul2_bf(x[cb].w, gw[cb].w), one0, one1);
                if (t == 0) stsf(ro + 512 + 128 * i, (e0[0] + e0[3]) + (e1[0] + e1[3]));
            };
#pragma unroll
            for (int i = 0; i < 4; i++) {
                if (i == 0) mbar_spin(bars + 8 * B_X); else mbar_wait_n<2, 8 * (B_X - B_S + 1)>(bars + 8 * (B_S + i - 1));
#pragma unroll
                for (int cb = 0; cb < 4; cb++) x[cb] = lds128(xo + 8192 * i + 128 * cb);
#pragma unroll
                for (int k = max(4 * i - 4, 0); k < 4 * i; k++) slice(k);
                float d0[4] = {0.f, 0.f, 0.f, 0.f}, d1[4] = {0.f, 0.f, 0.f, 0.f};
#pragma unroll
                for (int cb = 0; cb < 4; cb++) mma_bf((cb & 1) ? d1 : d0, x[cb].x, x[cb].y, x[cb].z, x[cb].w, w0[cb], w1[cb]);
                if (t == (g & 1)) stsf(ro + 128 * i, (d0[0] + d0[3]) + (d1[0] + d1[3]));
                if (i == 3) break;
                gate(i);
#pragma unroll
                for (int k = max(4 * i - 4, 0); k < 4 * i; k++) track(k);
                if (i == 1) {
                    eu = min(cta_exp() + 3u, 255u);
                    set_scale();
                }
#pragma unroll
                for (int k = max(4 * i - 4, 0); k < 4 * i; k++) to_half(xr[k]);
            }
            bar_sync(4, 256);
            if (at < 16) {
                const uint32_t rb = pack_bf(0.f, row_sum(sb + M_RG + at * 32));
                st_gpu32((uint32_t*)p.ex->r + 16 * c + at, ((rb ^ (((int)rb >> 31) | 0x80000000u)) & 0xffff0000u) | tag);
            }
            if (at == 32) mbar_arrive(bars + 8 * B_XF);
            if (at == 0) TSTAMP(8);
#pragma unroll
            for (int k = 8; k < 12; k++) { track(k); to_half(xr[k]); }
            mbar_spin(bars + 8 * (B_S + 3));
            if (at == 0) TSTAMP(9);
#pragma unroll
            for (int k = 12; k < 16; k++) slice(k);
            uint32_t utail = 0;
            if (at < 64 && r >= 5) utail = lds16(sb + OFF_S + 57344 + 1952 + ((12 - r) & 6) * 1024 + (r & 1) * 64 + ((h ^ 1) << 4) + 2 * (at >> 3));
#pragma unroll
            for (int k = 12; k < 16; k++) { track(k); to_half(xr[k]); }
            mx = amax2_bf(mx, utail);
            uint32_t over;
            asm volatile("{ .reg .pred p, q; setp.ne.u32 p, %1, 0; bar.red.or.pred q, 1, 128, p; selp.u32 %0, 1, 0, q; }"
                         : "=r"(over) : "r"((uint32_t)(max(mx & 0x7f80u, (mx >> 16) & 0x7f80u) > (eu << 7))) : "memory");
            mbar_spin(bars + 8 * B_KD);
            const uint32_t uo = sb + OFF_U + g * U_CH + t * U_PL;
            auto put = [&](int k, const uint32_t (&q)[4]) { sts128(uo + (8 + 4 * v + 16 * (k >> 2) + (k & 3)) * 16, q[0], q[1], q[2], q[3]); };
            if (!over) {
#pragma unroll
                for (int k = 0; k < 16; k++) put(k, xr[k]);
            } else {
                eu = cta_exp();
                set_scale();
#pragma unroll 1
                for (int k = 0; k < 16; k++) {
                    uint32_t q[4];
                    ldsm4t(src(k), q[0], q[1], q[2], q[3]);
                    to_half(q);
                    put(k, q);
                }
            }
            sts128(uo + v * 32, 0, 0, 0, 0); sts128(uo + v * 32 + 16, 0, 0, 0, 0);
            if (at < 64) sts16(sb + OFF_U + (at >> 3) * U_CH + 72 * 16 + r * 2, pack_h(bf_lo(utail) * bf_lo((257u - eu) << 7), 0.f));
            __syncwarp();
            if (lane == 0) mbar_arrive(bars + 8 * B_U);
#pragma unroll
            for (int cb = 0; cb < 4; cb++) gw[cb] = lds128(go + 128 * cb);
            gate(3);
            bar_sync(1, 128);
            if (at < 16) {
                const float gv = bf_round(sigmoid_f(bf_round(row_sum(sb + M_RG + 512 + at * 32))));
                st_gpu32((uint32_t*)p.ex->g + 1024 * h + 16 * (8 * (pr & 7) + (pr >> 3)) + (at ^ (2 * (pr >> 4) + 8 * (pr & 1))), pack_bf(gv, 1.f - gv));
            }
            if (at == 0) TSTAMP(23);
        }
        const int ct = v & 1, kh = v >> 1;
        uint32_t wa[GU_PRE][4][4];
        uint32_t ta, tb;
        {
            const int krow0 = 8 * (mi >> 1) + r;
            const uint32_t off0 = krow0 * 64 + (((2 * ct + (mi & 1)) ^ ((krow0 >> 1) & 3)) << 4);
            ta = sb + OFF_RING + kh * 2048 + off0 + p.swap_gu; tb = ta + 4096 - 2 * p.swap_gu;
        }
        auto gu_load = [&](uint32_t (&a)[4][4], int s) {
            const uint32_t o = (s % NSLOT) * 8192 + (s % NSLOT >= ALT_SLOT ? dalt : 0);
            ldsm4t(ta + o, a[0][0], a[0][1], a[0][2], a[0][3]);
            ldsm4t(tb + o, a[1][0], a[1][1], a[1][2], a[1][3]);
            ldsm4t(ta + o + 1024, a[2][0], a[2][1], a[2][2], a[2][3]);
            ldsm4t(tb + o + 1024, a[3][0], a[3][1], a[3][2], a[3][3]);
        };
        auto gu_release = [&](const uint32_t (&a)[4][4], int s) {
            if (s < B_S - B_EMPTY && lane == 0) mbar_arrive(bars + 8 * (B_EMPTY + s) + (a[0][0] & a[1][0] & a[2][0] & a[3][0] & p.zero));
        };
        auto gu_park = [&](auto S0, auto N) {
            constexpr int s0 = decltype(S0)::value, n = decltype(N)::value;
            if (fb < NGU_CTA) {
                mbar_wait_n<n, 8>(bars + 8 * s0);
#pragma unroll
                for (int s = s0; s < s0 + n; s++) gu_load(wa[s], s);
#pragma unroll
                for (int s = s0; s < s0 + n; s++) gu_release(wa[s], s);
            }
        };
        gu_park(IC<0>(), IC<4>());
        asm volatile("barrier.cluster.wait.acquire.aligned;" ::: "memory");
        mbar_wait(bars + 8 * B_TS);
        if (v == 3) {
            const int es = (int)lds32(sb + OFF_TAB + r * T_CH + T_ES), em = __reduce_max_sync(0xffffffffu, es);
            if (lane < 8) sts32(sb + M_SC + 8 + lane * 4, pack_h(__uint_as_float(max(142 + es - em, 1) << 23), 0.f));
            if (lane < 2) { const uint32_t o = mapa(sb, lane); st_async4(o + M_SC + 4 * h, ((uint32_t)min(max(em + (int)eu - 15, 1), 254) << 7) | 0x3F800000u, o + M_BARS + 8 * B_SC); }
        }
        group_tables(sb + OFF_TAB + v * T_CH, lane);
        __syncwarp();
        if (lane == 0) mbar_arrive(bars + 8 * B_TD);
        gu_park(IC<4>(), IC<GU_PRE - 4>());
        if (fb < NGU_CTA) {
            float dgt[4] = {0.f, 0.f, 0.f, 0.f}, dup[4] = {0.f, 0.f, 0.f, 0.f}, dg2[4] = {0.f, 0.f, 0.f, 0.f}, du2[4] = {0.f, 0.f, 0.f, 0.f};
            const uint32_t xo = sb + OFF_XSEL + r * XS_ROW + 64 * kh + 16 * mi;
            auto gu_mma = [&](const uint32_t (&a)[4][4], const uint32_t (&b)[4]) {
                mma_bf(dgt, a[0][0], a[0][1], a[0][2], a[0][3], b[0], b[1]);
                mma_bf(dup, a[1][0], a[1][1], a[1][2], a[1][3], b[0], b[1]);
                mma_bf(dg2, a[2][0], a[2][1], a[2][2], a[2][3], b[2], b[3]);
                mma_bf(du2, a[3][0], a[3][1], a[3][2], a[3][3], b[2], b[3]);
            };
            auto gu_batch = [&](auto S0, auto N) {
                constexpr int s0 = decltype(S0)::value, n = decltype(N)::value;
                uint32_t b[n][4];
                mbar_wait_n<n, 8>(bars + 8 * s0);
#pragma unroll
                for (int i = 0; i < n; i++) { ldsm4(xo + 128 * (s0 + i), b[i][0], b[i][1], b[i][2], b[i][3]); gu_load(wa[i], s0 + i); }
#pragma unroll
                for (int i = 0; i < n; i++) gu_mma(wa[i], b[i]);
#pragma unroll
                for (int i = 0; i < n; i++) gu_release(wa[n - 1], s0 + i);
            };
            mbar_spin(bars + 8 * B_XS);
            if (at == 0) TSTAMP(12);
#pragma unroll
            for (int s = 0; s < GU_PRE; s++) { uint32_t b[4]; ldsm4(xo + 128 * s, b[0], b[1], b[2], b[3]); gu_mma(wa[s], b); }
            gu_batch(IC<6>(), IC<2>());
            mbar_spin(bars + 8 * (B_XS + 1));
            gu_batch(IC<8>(), IC<4>()); gu_batch(IC<12>(), IC<3>()); gu_batch(IC<15>(), IC<1>());
#pragma unroll
            for (int i = 0; i < 4; i++) { dgt[i] += dg2[i]; dup[i] += du2[i]; }
            if (at == 0) TSTAMP(13);
            const uint32_t red = sb + M_RG, hs = sb + OFF_XSEL;
            sts128(red + ((v ^ 2) * 32 + lane) * 16, __float_as_uint(kh ? dgt[0] : dgt[2]), __float_as_uint(kh ? dgt[1] : dgt[3]),
                   __float_as_uint(kh ? dup[0] : dup[2]), __float_as_uint(kh ? dup[1] : dup[3]));
            bar_sync(1, 128);
            const uint4 oth = lds128(red + at * 16);
#pragma unroll
            for (int i = 0; i < 2; i++) {
                const float gv = bf_round((kh ? dgt[2 + i] : dgt[i]) + __uint_as_float(i ? oth.y : oth.x));
                const float uv = bf_round((kh ? dup[2 + i] : dup[i]) + __uint_as_float(i ? oth.w : oth.z));
                const float sl = bf_round(gv * sigmoid_f(gv));
                uint32_t hv = pack_bf(sl * uv, 0.f) & 0xffffu;
                hv = (hv == 0x8000u) ? 0x8000u : (hv ^ 0x8000u);
                sts16(hs + (2 * t + i) * 64 + (g >> 1) * 16 + (2 * ct + kh) * 4 + (g & 1) * 2, hv);
            }
            bar_sync(1, 128);
            if (v == 0) st_gpu128(&p.ex->h[32 * fb + lane], lds128(hs + lane * 16));
        }
        else mbar_wait(bars + 8 * (B_XS + 1));
        if (at == 0) TSTAMP(14);
        {
            mbar_wait_n<2, 8>(bars + 8 * B_SC);
            const int row = (int)lds32(sb + M_IDX + ftok * 4);
            const int w = row & 7, jj = (row >> 3) & 7;
            const uint32_t xa = sb + OFF_S + h * 32768 + (row >> 9) * 8192 + (w & 6) * 1024 + ((row >> 4) & 15) * 128 + (w & 1) * 64 + (jj & 1) * 32 + ((2 * fch) ^ (row & 16));
            const float xv = bf_lo(lds16(xa));
            const uint32_t gp = hmul2_bf(lds32(sb + OFF_GP + (8 * w + jj) * 64 + ((4 * (row >> 9) + ((row >> 6) & 3)) ^ ((jj & 6) + 8 * (w & 1))) * 4), lds32(sb + M_SC + (fch >> 3) * 4));
            const uint32_t ya = sb + (((fch >> 3) == h) ? OFF_TAB + (fch & 7) * T_CH : (h ? ALT1 : ALT0) + A_YIN + (fch & 7) * Y_CH) + (row >> 9) * 512 + (4 * w + ((row >> 6) & 3)) * 16 + jj * 2;
            const float rs = bf_round(sigmoid_f(ldsf(sb + M_RSEL + ftok * 4)));
            uint4 hq[14];
            {
                const uint4* hsrc = &p.ex->h[(56 * h + 2 * v) * 32 + lane];
                mbar_wait(bars + 8 * (B_FULL + NST_GU + H_WAIT));
                if (at == 0) TSTAMP(15);
#pragma unroll
                for (int i = 0; i < 14; i++) hq[i] = ld_gpu128(hsrc + (8 * (i >> 1) + (i & 1)) * 32);
                bool ok = false;
#pragma unroll 1
                for (int it = 0; it < (1 << 22); it++) {
                    uint32_t mn = 0xffffffffu;
#pragma unroll
                    for (int i = 0; i < 14; i++) mn = min(mn, hq[i].x);
                    ok = __all_sync(0xffffffffu, mn != 0);
                    if (ok) break;
                    if (PSLEEP > 0) __nanosleep(PSLEEP);
#pragma unroll
                    for (int i = 0; i < 14; i++) if (hq[i].x == 0) hq[i] = ld_gpu128(hsrc + (8 * (i >> 1) + (i & 1)) * 32);
                }
                if (!ok) __trap();
            }
            if (at == 0) TSTAMP(16);
            mbar_wait_n<DN_PRE, 8>(bars + 8 * (B_FULL + NST_GU));
            float dd[4][4];
#pragma unroll
            for (int j = 0; j < 4; j++) { dd[j][0] = dd[j][1] = dd[j][2] = dd[j][3] = 0.f; }
            const int krow0 = 64 * (v & 1) + 8 * (mi >> 1) + r;
            const uint32_t td = sb + OFF_RING + (v >> 1) * 4096 + krow0 * 32 + (((mi & 1) ^ ((krow0 >> 2) & 1)) << 4);
#pragma unroll
            for (int s = 0; s < 7; s++) {
                if (s >= DN_PRE) mbar_spin(bars + 8 * (B_FULL + NST_GU + s));
                const uint32_t tile = td + ((NST_GU + s) % NSLOT) * 8192 + ((NST_GU + s) % NSLOT >= ALT_SLOT ? dalt : 0);
                uint32_t a[4][4];
#pragma unroll
                for (int j = 0; j < 4; j++) ldsm4t(tile + j * 512, a[j][0], a[j][1], a[j][2], a[j][3]);
                mma_bf(dd[0], a[0][0], a[0][1], a[0][2], a[0][3], hq[2 * s].x, hq[2 * s].y);
                mma_bf(dd[1], a[1][0], a[1][1], a[1][2], a[1][3], hq[2 * s].z, hq[2 * s].w);
                mma_bf(dd[2], a[2][0], a[2][1], a[2][2], a[2][3], hq[2 * s + 1].x, hq[2 * s + 1].y);
                mma_bf(dd[3], a[3][0], a[3][1], a[3][2], a[3][3], hq[2 * s + 1].z, hq[2 * s + 1].w);
            }
            uint32_t ds[4];
#pragma unroll
            for (int j = 0; j < 4; j++) ds[j] = __float_as_uint((dd[0][j] + dd[1][j]) + (dd[2][j] + dd[3][j]));
            if (at == 0) TSTAMP(17);
            const uint32_t o = mapa(sb, h ^ 1);
            st_async16(o + OFF_DP + (128 * h + at) * 16, ds[0], ds[1], ds[2], ds[3], o + M_BARS + 8 * B_DP);
            sts128(sb + OFF_DP + (128 * h + at) * 16, ds[0], ds[1], ds[2], ds[3]);
            __syncwarp();
            if (lane == 0) mbar_arrive(bars + 8 * B_DP);
            mbar_spin(bars + 8 * B_DP);
            float pt[8];
#pragma unroll
            for (int k = 0; k < 8; k++) pt[k] = ldsf(sb + OFF_DP + k * 512 + at * 4);
            const float tot = -(((pt[0] + pt[1]) + (pt[2] + pt[3])) + ((pt[4] + pt[5]) + (pt[6] + pt[7])));
            const float eb = bf_round(bf_hi(gp) * bf_round(xv + bf_round(bf_round(tot) * rs)));
            mbar_wait_n<3, 8>(bars + 8 * (B_Y + 2));
            if (((row >> 8) & 1) == h) p.out[(size_t)row * D_ + 16 * pr + fch] = __float2bfloat16_rn(fmaf(bf_lo(gp), bf_lo(lds16(ya)), eb));
        }
        if (at == 0) { TSTAMP(18); TSDUMP(fb < NGU_CTA ? 0x0087f300u : 0x0087c300u); if (c == 0) *(volatile unsigned*)&p.ex->epoch = epoch + 1; }
    } else {
        const uint32_t t_start = now_ns();
        asm volatile("setmaxnreg.dec.sync.aligned.u32 " HELP_REGS ";");
        if (pw != 12) {
            if (pw >= 14) {
#pragma unroll
                for (int k = 0; k < 5; k++) {
                    const int w = 1 + 2 * k, e = (tid & 63) - 32;
                    sts32(sb + OFF_BAND + k * 256 + (tid & 63) * 4, ((e >= 0 && e < w) ? 0x3C00u : 0u) | ((e + 1 >= 0 && e + 1 < w) ? 0x3C000000u : 0u));
                }
                cluster_next();
            } else {
                if (lane == 0) {
                    asm volatile("prefetch.tensormap [%0];" :: "l"(&tm_r) : "memory");
                    asm volatile("prefetch.tensormap [%0];" :: "l"(&tm_x) : "memory");
                }
                sts32(sb + M_BMAP + lane * 4, 0);
                __syncwarp();
                cluster_next();
                uint4* gz = &p.ex->g[256 * h + 4 * (8 * (pr & 7) + (pr >> 3)) + (lane & 3)];
                uint4* hz = fb < NGU_CTA ? &p.ex->h[32 * fb + lane] : gz;
                st_gpu128(gz, make_uint4(0, 0, 0, 0)); st_gpu128(hz, make_uint4(0, 0, 0, 0));
                if ((ld_gpu128(gz).x | ld_gpu128(hz).x) != 0) __trap();
            }
        } else {
            if (lane == 0) {
#pragma unroll
                for (int k = 0; k < 4; k++) { mbar_init(bars + 8 * (B_X + k), 1); mbar_init(bars + 8 * (B_S + k), 1); }
                asm volatile("fence.proxy.async.shared::cta;" ::: "memory");
                asm volatile("fence.mbarrier_init.release.cluster;" ::: "memory");
            }
            __syncwarp();
            asm volatile("barrier.cluster.arrive.relaxed.aligned;" ::: "memory");
            tma4d_warp(sb + OFF_XROW, &tm_r, 4 * h, pr, bars + 8 * B_X);
            asm volatile("barrier.cluster.wait.acquire.aligned;" ::: "memory");
            if (lane == 0) TSTAMP(20);
#pragma unroll
            for (int i = 0; i < 4; i++) {
                tma5d_both(sb + OFF_S + (4 * h + i) * 8192, &tm_x, 16 * pr, 32 * i + 16 * h, bars + 8 * (B_S + i));
                if (i < 3) tma4d_warp(sb + OFF_XROW + (i + 1) * 8192, &tm_r, 8 * (i + 1) + 4 * h, pr, bars + 8 * (B_X + i + 1));
            }
            if (lane == 0) {
                TSTAMP(24);
#pragma unroll
                for (int k = 0; k < 4; k++) { mbar_expect(bars + 8 * (B_X + k), 8192); mbar_expect(bars + 8 * (B_S + k), 16384); }
                asm volatile("prefetch.tensormap [%0];" :: "l"(&tm_gu) : "memory");
                asm volatile("prefetch.tensormap [%0];" :: "l"(&tm_down) : "memory");
                asm volatile("prefetch.tensormap [%0];" :: "l"(&tm_o) : "memory");
#pragma unroll
                for (int k = 0; k < B_S; k++) mbar_init(bars + 8 * k, k < B_EMPTY ? 1 : 4);
#pragma unroll
                for (int k = B_XS; k < B_X; k++) mbar_init(bars + 8 * k, (k >= B_Y && k < B_SD) ? 9 : (k == B_KD || k == B_TS || k == B_SD) ? 8 : (k == B_TD || k == B_U) ? 4 : k == B_XS + 1 ? 2 : k == B_DP ? 5 : 1);
#pragma unroll
                for (int k = 0; k < B_EMPTY; k++) mbar_expect(bars + 8 * k, 8192);
#pragma unroll
                for (int k = B_XS; k < B_SD; k++) if (k != B_TD && k != B_G) mbar_expect(bars + 8 * k, k < B_TD ? (fb < NGU_CTA ? 8192 : 0) : k == B_SC ? 8 : k == B_DP ? 2048 : k == B_NONE ? 0 : 4096);
                asm volatile("fence.proxy.async.shared::cta;" ::: "memory");
                asm volatile("fence.mbarrier_init.release.cluster;" ::: "memory");
            }
            __syncwarp();
            asm volatile("barrier.cluster.arrive.relaxed.aligned;" ::: "memory");
        }
        bar_arrive(4, 256);
        bar_sync(6, 128);
        if (pw == 15) {
            const unsigned tag = (ld_epoch(p.ex) + 1) & 0xffffu;
            const int tok = lane & 7;
            uint32_t top = 0;
            bool ok = false;
            mbar_wait(bars + 8 * B_XF);
#pragma unroll 1
            for (int it = 0; it < (1 << 22); it++) {
                uint32_t tg;
                asm volatile("ld.relaxed.gpu.global.v2.u32 {%0,%1}, [%2];" : "=r"(top), "=r"(tg) : "l"(&p.ex->top[tok]) : "memory");
                ok = __all_sync(0xffffffffu, tg == tag);
                if (ok) break;
            }
            if (!ok) __trap();
            if (lane == 0) TSTAMP(25);
            const int row = 2047 - (int)(top & 0xffffu);
            if (fb < NGU_CTA) {
#pragma unroll
                for (int k = 0; k < 8; k++) {
                    const int tk = 4 * h + ((k + pr) & 3), hf = k >> 2;
                    bulk_load_both(sb + OFF_XSEL + tk * XS_ROW + 1024 * hf, p.u + (size_t)__shfl_sync(0xffffffffu, row, tk) * D_ + 512 * hf, 1024, bars + 8 * (B_XS + hf));
                }
            }
            if (lane == 0) TSTAMP(21);
            if (lane < 8) {
                const uint32_t ord = top >> 16;
                sts32(sb + M_RSEL + tok * 4, ((ord & 0x8000u) ? (ord & 0x7fffu) : (~ord & 0xffffu)) << 16);
                sts32(sb + M_IDX + tok * 4, (uint32_t)row);
                if (((row >> 8) & 1) == h) asm volatile("red.shared.or.b32 [%0], %1;" :: "r"(sb + M_BMAP + ((row >> 7) & 1) * 64 + (row & 6) * 8 + ((row >> 4) & 3) * 4),
                                                   "r"(1u << (4 * (row >> 9) + ((row >> 5) & 2) + (row & 1) + 2 * (row & 8))) : "memory");
            }
            __syncwarp();
            if (lane == 0) { mbar_arrive(bars + 8 * (B_XS + 1)); TSDUMP(0x02200000u); }
            mbar_wait_n<2, 8>(bars + 8 * (B_XS + 1));
            if (lane == 0) bulk_load(sb + OFF_GP, &p.ex->g[256 * h], 4096, bars + 8 * B_GL);
            __syncwarp();
            mbar_wait(bars + 8 * B_GL);
            uint32_t mn = 0xffffffffu;
#pragma unroll
            for (int i = 0; i < 8; i++) { const uint4 a = lds128(sb + OFF_GP + (32 * i + lane) * 16); mn = min(min(mn, min(a.x, a.y)), min(a.z, a.w)); }
            if (mn == 0) {
#pragma unroll 1
                for (int i = lane, it = 0; i < 256; ) {
                    const uint4 a = ld_gpu128(&p.ex->g[256 * h + i]);
                    if (min(min(a.x, a.y), min(a.z, a.w)) != 0) { sts128(sb + OFF_GP + i * 16, a.x, a.y, a.z, a.w); i += 32; }
                    else if (++it > (1 << 22)) __trap();
                }
            }
            __syncwarp();
            if (lane == 0) { TSTAMP(30); TSDUMP(1u << 30); }
            if (lane == 0) mbar_arrive(bars + 8 * B_G);
            return;
        }
        const int s0 = fb < NGU_CTA ? 0 : NST_GU, s = lane, dn = s >= NST_GU;
        const int slot = s < NSLOT ? s : s < 2 * NSLOT ? s - NSLOT : s - 2 * NSLOT, depth = dn ? DEPTH_D : DEPTH_G;
        const uint32_t dst = sb + OFF_RING + slot * 8192 + (slot >= ALT_SLOT ? (h ? ALT1 : ALT0) + A_SLOT - ALT_SLOT * 8192 : 0);
        const uint32_t due = (t_start + T_W + h * (DT_G / 2) + DT_G * s + (dn ? (DT_D - DT_G) * (s - NST_GU) : 0)) & ~63u;
        const uint32_t w_slot = bars + 8 * (s >= s0 + NSLOT ? B_EMPTY + s - NSLOT : slot >= ALT_SLOT ? B_U : s >= X_SLOT ? B_XF : B_NONE);
        const uint32_t w_depth = bars + 8 * (s >= s0 + depth ? B_FULL + s - depth : B_NONE);
        const CUtensorMap* tm = dn ? &tm_down : &tm_gu;
        const int cx = dn ? 16 * pr : 32 * fb, cy = dn ? 1792 * h + 256 * (s - NST_GU) : 64 * s;
#pragma unroll 1
        for (int k = s0 + pw - 12; k < NST; k += 3) {
            if (lane == k) {
#pragma unroll 1
                for (int n = 0; n < 1000; n++) {
                    const uint32_t now = now_ns();
                    if ((int)(due - now) <= 0) break;
                    __nanosleep(min((now ^ due) >> 1, 1023u));
                }
                mbar_wait2(w_slot, w_depth);
                tma3d(dst, tm, cx, cy, 0, bars + 8 * (B_FULL + s));
            }
            __syncwarp();
        }
    }
}

typedef CUresult (*EncodeFn)(CUtensorMap*, CUtensorMapDataType, cuuint32_t, void*, const cuuint64_t*, const cuuint64_t*,
                             const cuuint32_t*, const cuuint32_t*, CUtensorMapInterleave, CUtensorMapSwizzle,
                             CUtensorMapL2promotion, CUtensorMapFloatOOBfill);

void make_map(EncodeFn f, CUtensorMap* m, const void* ptr, int rank, const cuuint64_t* dims, const cuuint64_t* strides, const cuuint32_t* box, CUtensorMapSwizzle sw) {
    const cuuint32_t es[5] = {1, 1, 1, 1, 1};
    f(m, CU_TENSOR_MAP_DATA_TYPE_BFLOAT16, rank, (void*)ptr, dims, strides, box, es, CU_TENSOR_MAP_INTERLEAVE_NONE, sw,
      CU_TENSOR_MAP_L2_PROMOTION_L2_128B, CU_TENSOR_MAP_FLOAT_OOB_FILL_NONE);
}

}

extern "C" void kernel_launch(void* const* d_in, const int* in_sizes, int n_in, void* d_out, int out_size) {
    static EncodeFn enc = nullptr;
    static void* ex = nullptr;
    if (!enc) {
        void* fn = nullptr;
        cudaDriverEntryPointQueryResult qr;
        cudaGetDriverEntryPoint("cuTensorMapEncodeTiled", &fn, cudaEnableDefault, &qr);
        enc = (EncodeFn)fn;
        cudaFuncSetAttribute(fused_kernel, cudaFuncAttributeMaxDynamicSharedMemorySize, SMEM_BYTES);
        cudaGetSymbolAddress(&ex, g_ex);
    }
    CUtensorMap tgu, td, tx, tr, to;
    const char *wg = (const char*)d_in[9], *wu = (const char*)d_in[10];
    const bool swap = wu < wg;
    {
        const cuuint64_t dims[3] = {F_, D_, 2}, str[2] = {F_ * 2, (cuuint64_t)(swap ? wg - wu : wu - wg)};
        const cuuint32_t box[3] = {32, 64, 2};
        make_map(enc, &tgu, swap ? wu : wg, 3, dims, str, box, CU_TENSOR_MAP_SWIZZLE_64B);
    }
    {
        const cuuint64_t dims[3] = {D_, F_, 1}, str[2] = {D_ * 2, (cuuint64_t)D_ * 2 * F_};
        const cuuint32_t box[3] = {16, 256, 1};
        make_map(enc, &td, d_in[11], 3, dims, str, box, CU_TENSOR_MAP_SWIZZLE_32B);
    }
    {
        const cuuint64_t dims[5] = {D_, 2, 2, L_ / 16, 4}, str[4] = {D_ * 2 * 8, D_ * 2, D_ * 2 * 16, D_ * 2 * 2};
        const cuuint32_t box[5] = {16, 2, 2, 16, 4}, obox[5] = {16, 2, 2, 8, 1};
        make_map(enc, &tx, d_in[0], 5, dims, str, box, CU_TENSOR_MAP_SWIZZLE_32B);
        make_map(enc, &to, d_out, 5, dims, str, obox, CU_TENSOR_MAP_SWIZZLE_32B);
    }
    {
        const cuuint64_t dims[4] = {256, 4, L_ / 64, 64}, str[3] = {512, D_ * 2 * 64, D_ * 2};
        const cuuint32_t box[4] = {256, 4, 4, 1};
        make_map(enc, &tr, d_in[0], 4, dims, str, box, CU_TENSOR_MAP_SWIZZLE_NONE);
    }
    Params p;
    p.u = (const bf16*)d_in[0]; p.logA = (const bf16*)d_in[1]; p.Aim = (const bf16*)d_in[2];
    p.Cre = (const bf16*)d_in[3]; p.Cim = (const bf16*)d_in[4]; p.logdt = (const bf16*)d_in[5];
    p.Dskip = (const bf16*)d_in[6]; p.wr = (const bf16*)d_in[8]; p.gatew = (const bf16*)d_in[12];
    p.out = (bf16*)d_out;
    p.ex = (Exchange*)ex;
    p.zero = 0;
    p.swap_gu = swap ? 4096 : 0;
    fused_kernel<<<NCTA, NTHREADS, SMEM_BYTES>>>(p, tgu, td, tx, tr, to);
}
```
